```python
import torch

def _softmax(x, axis=-1):
    return torch.softmax(x, dim=axis)
def _gelu(x):
    return torch.nn.functional.gelu(x, approximate="tanh")
def _silu(x):
    return torch.nn.functional.silu(x)
def _sigmoid(x):
    return torch.sigmoid(x)
def _layernorm(x, axis=-1, eps=1e-5):
    m = x.mean(dim=axis, keepdim=True)
    v = x.var(dim=axis, keepdim=True, unbiased=False)
    return (x - m) / torch.sqrt(v + eps)
def _scatter_add(tgt, idx, src, axis=0):
    return tgt.clone().index_add_(axis, idx, src)
def _segment_sum(src, seg, n):
    out = torch.zeros((n,) + src.shape[1:], dtype=src.dtype)
    return out.index_add_(0, seg, src)
def _pad(x, pw):
    flat = tuple(v for pair in reversed(pw) for v in pair)
    return torch.nn.functional.pad(x, flat)

kernel_name = 'parallel_sum__ssm_conv_s4d__geglu_ffn__prompt'

def setup_inputs():

    _w = (lambda a: (lambda t: t.to(torch.bfloat16) if t.is_floating_point() else t)(torch.as_tensor(a)))
    def _A_setup():
        Bsz, L, D, N = 1, 2048, 576, 128
        return {
            "u": _w((lambda *s: torch.randn(*s, dtype=torch.bfloat16) * 0.05)(Bsz, L, D)),
            "log_A_real": _w((lambda *s: torch.randn(*s, dtype=torch.bfloat16) * 3.2)(D, N) * 0.5),
            "A_imag": _w((lambda *s: torch.randn(*s, dtype=torch.bfloat16) * 0.2)(D, N) * 3.14),
            "C_real": _w((lambda *s: torch.randn(*s, dtype=torch.bfloat16) * 3.2)(D, N) / N ** 0.5),
            "C_imag": _w((lambda *s: torch.randn(*s, dtype=torch.bfloat16) * 3.2)(D, N) / N ** 0.5),
            "log_dt": _w((lambda *s: torch.randn(*s, dtype=torch.bfloat16) * 0.2)(D) * 0.5 - 4.0),
            "D_skip": _w((lambda *s: torch.randn(*s, dtype=torch.bfloat16) * 0.4)(D)),
        }
    _A_in = _A_setup()

    def _B_setup():
        B, S, D, F = 1, 2048, 576, 4608
        return {
            "x": _w((lambda *s: torch.randn(*s, dtype=torch.bfloat16) * 0.05)(B, S, D)),
            "w_gate": _w((lambda *s: torch.randn(*s, dtype=torch.bfloat16) * 0.05)(D, F)),
            "w_up": _w((lambda *s: torch.randn(*s, dtype=torch.bfloat16) * 0.05)(D, F)),
            "w_down": _w((lambda *s: torch.randn(*s, dtype=torch.bfloat16) * 0.05)(F, D)),
        }
    _B_in = _B_setup()

    return {
        "A_u": _A_in["u"],
        "A_log_A_real": _A_in["log_A_real"],
        "A_A_imag": _A_in["A_imag"],
        "A_C_real": _A_in["C_real"],
        "A_C_imag": _A_in["C_imag"],
        "A_log_dt": _A_in["log_dt"],
        "A_D_skip": _A_in["D_skip"],
        "B_x": _B_in["x"],
        "B_w_gate": _B_in["w_gate"],
        "B_w_up": _B_in["w_up"],
        "B_w_down": _B_in["w_down"],
    }

def reference(A_u, A_log_A_real, A_A_imag, A_C_real, A_C_imag, A_log_dt, A_D_skip, B_x, B_w_gate, B_w_up, B_w_down):
    def _A_ref(u, log_A_real, A_imag, C_real, C_imag, log_dt, D_skip):
        L = u.shape[1]
        dt = torch.exp(log_dt)
        A = -torch.exp(log_A_real) + 1j * A_imag
        C = (C_real + 1j * C_imag) * dt[:, None]
        pos = (lambda x, dt: x.to(dt))(torch.arange(L), log_dt.dtype)
        P = torch.exp((A * dt[:, None])[:, :, None] * pos[None, None, :])
        K = 2.0 * torch.einsum("dn,dnl->dl", C, P).real
        L2 = 2 * L
        u_t = (lambda x, *d: x.permute(*d))(u, 0, 2, 1)
        Kf = (lambda x, *a, **k: torch.fft.rfft(x.float(), *a, **k))(K, L2)
        Uf = (lambda x, *a, **k: torch.fft.rfft(x.float(), *a, **k))(u_t, L2)
        y = (lambda x, *a, **k: torch.fft.irfft(x, *a, **k).to(torch.bfloat16))(Uf * Kf[None, :, :], L2)[:, :, :L]
        y = (lambda x, *d: x.permute(*d))(y, 0, 2, 1)
        return y + u * D_skip[None, None, :]

    def _B_ref(x, w_gate, w_up, w_down):
        return (_gelu(x @ w_gate) * (x @ w_up)) @ w_down

    x = A_u
    xn = _layernorm(x, axis=-1)
    return x + _A_ref(xn, A_log_A_real, A_A_imag, A_C_real, A_C_imag, A_log_dt, A_D_skip) + _B_ref(xn, B_w_gate, B_w_up, B_w_down)
```

```cpp
#include <cuda_runtime.h>
#include <cuda_bf16.h>
#include <cuda.h>
#include <stdint.h>
#include <type_traits>
#define CV_BASEOFF 0

namespace {

constexpr int L_ = 2048, D_ = 576, F_ = 4608, NM_ = 128;
constexpr int KP_LEN = 2112;

__device__ __align__(1024) __nv_bfloat16 g_xn[L_ * D_];
__device__ __align__(1024) __nv_bfloat16 g_xnT[D_ * L_];
__device__ __align__(1024) __nv_bfloat16 g_baseT[D_ * L_];
__device__ __align__(1024) uint32_t g_kp[D_ * KP_LEN];
__device__ __align__(1024) __nv_bfloat16 g_part[4 * D_ * L_];

__device__ __forceinline__ uint32_t smem_u32(const void* p) { return (uint32_t)__cvta_generic_to_shared(p); }
__device__ __forceinline__ void mbar_init(uint32_t bar, uint32_t cnt) { asm volatile("mbarrier.init.shared::cta.b64 [%0], %1;" ::"r"(bar), "r"(cnt)); }
__device__ __forceinline__ void mbar_expect_tx(uint32_t bar, uint32_t bytes) { asm volatile("mbarrier.arrive.expect_tx.shared::cta.b64 _, [%0], %1;" ::"r"(bar), "r"(bytes) : "memory"); }
__device__ __forceinline__ void mbar_arrive(uint32_t bar) { asm volatile("mbarrier.arrive.shared::cta.b64 _, [%0];" ::"r"(bar) : "memory"); }
__device__ __forceinline__ void mbar_arrive_remote(uint32_t bar) { asm volatile("mbarrier.arrive.shared::cluster.b64 _, [%0];" ::"r"(bar) : "memory"); }
__device__ __forceinline__ bool mbar_try_wait(uint32_t bar, uint32_t parity) {
  uint32_t ok;
  asm volatile("{\n.reg .pred p;\nmbarrier.try_wait.parity.shared::cta.b64 p, [%1], %2;\nselp.u32 %0, 1, 0, p;\n}" : "=r"(ok) : "r"(bar), "r"(parity) : "memory");
  return ok;
}
__device__ __forceinline__ void mbar_wait(uint32_t bar, uint32_t parity) {
  asm volatile("{\n.reg .pred p, q;\n.reg .u32 n;\nmov.u32 n, 0;\nLW:\nmbarrier.try_wait.parity.shared::cta.b64 p, [%0], %1;\n"
               "add.u32 n, n, 1;\nsetp.lt.and.u32 q, n, 65536, !p;\n@q bra LW;\n}" ::"r"(bar), "r"(parity) : "memory");
}
__device__ __forceinline__ bool elect_one() {
  uint32_t ok;
  asm volatile("{\n.reg .pred p;\nelect.sync _|p, 0xffffffff;\nselp.u32 %0, 1, 0, p;\n}" : "=r"(ok));
  return ok;
}
__device__ __forceinline__ void tma_2d(uint32_t dst, const CUtensorMap* map, int c0, int c1, uint32_t bar) {
  asm volatile("cp.async.bulk.tensor.2d.shared::cluster.global.mbarrier::complete_tx::bytes [%0], [%1, {%3, %4}], [%2];"
               ::"r"(dst), "l"(map), "r"(bar), "r"(c0), "r"(c1) : "memory");
}
__device__ __forceinline__ void tma_3d(uint32_t dst, const CUtensorMap* map, int c0, int c1, int c2, uint32_t bar) {
  asm volatile("cp.async.bulk.tensor.3d.shared::cluster.global.mbarrier::complete_tx::bytes [%0], [%1, {%3, %4, %5}], [%2];"
               ::"r"(dst), "l"(map), "r"(bar), "r"(c0), "r"(c1), "r"(c2) : "memory");
}
__device__ __forceinline__ void tma_5d(uint32_t dst, const CUtensorMap* map, int c0, int c1, int c2, int c3, int c4, uint32_t bar) {
  asm volatile("cp.async.bulk.tensor.5d.shared::cluster.global.mbarrier::complete_tx::bytes [%0], [%1, {%3, %4, %5, %6, %7}], [%2];"
               ::"r"(dst), "l"(map), "r"(bar), "r"(c0), "r"(c1), "r"(c2), "r"(c3), "r"(c4) : "memory");
}
__device__ __forceinline__ void tma_store_3d(const CUtensorMap* map, uint32_t src, int c0, int c1, int c2) {
  asm volatile("cp.async.bulk.tensor.3d.global.shared::cta.bulk_group [%0, {%2, %3, %4}], [%1];"
               ::"l"(map), "r"(src), "r"(c0), "r"(c1), "r"(c2) : "memory");
}
__device__ __forceinline__ void bulk_g2s(uint32_t dst, const void* src, uint32_t bytes, uint32_t bar) {
  asm volatile("cp.async.bulk.shared::cluster.global.mbarrier::complete_tx::bytes [%0], [%1], %2, [%3];"
               ::"r"(dst), "l"(src), "r"(bytes), "r"(bar) : "memory");
}
__device__ __forceinline__ void prefetch_map(const CUtensorMap* m) { asm volatile("prefetch.tensormap [%0];" ::"l"(m) : "memory"); }
__device__ __forceinline__ uint32_t mapa(uint32_t addr, uint32_t rank) { uint32_t r; asm volatile("mapa.shared::cluster.u32 %0, %1, %2;" : "=r"(r) : "r"(addr), "r"(rank)); return r; }
__device__ __forceinline__ void cluster_sync() { asm volatile("barrier.cluster.arrive.release.aligned;\nbarrier.cluster.wait.acquire.aligned;" ::: "memory"); }
__device__ __forceinline__ void fence_async_smem() { asm volatile("fence.proxy.async.shared::cta;" ::: "memory"); }
__device__ __forceinline__ void wg_fence() { asm volatile("wgmma.fence.sync.aligned;" ::: "memory"); }
__device__ __forceinline__ void wg_commit() { asm volatile("wgmma.commit_group.sync.aligned;" ::: "memory"); }
template <int N> __device__ __forceinline__ void wg_wait() { asm volatile("wgmma.wait_group.sync.aligned %0;" ::"n"(N) : "memory"); }
template <int N> __device__ __forceinline__ void reg_fence(float (&d)[N]) {
#pragma unroll
  for (int i = 0; i < N; i++) asm volatile("" : "+f"(d[i])::"memory");
}
__device__ __forceinline__ void named_bar(int id, int n) { asm volatile("bar.sync %0, %1;" ::"r"(id), "r"(n) : "memory"); }
__device__ __forceinline__ uint64_t mk_desc(uint32_t addr, uint32_t lbo, uint32_t sbo, uint32_t sw) {
  return (uint64_t)((addr & 0x3FFFF) >> 4) | ((uint64_t)(lbo >> 4) << 16) | ((uint64_t)(sbo >> 4) << 32) | ((uint64_t)sw << 62);
}
__device__ __forceinline__ uint32_t pack_bf16(float lo, float hi) {
  uint32_t r; asm("cvt.rn.bf16x2.f32 %0, %1, %2;" : "=r"(r) : "f"(hi), "f"(lo)); return r;
}
__device__ __forceinline__ float bf_lo(uint32_t v) { return __uint_as_float(v << 16); }
__device__ __forceinline__ float bf_hi(uint32_t v) { return __uint_as_float(v & 0xffff0000u); }
__device__ __forceinline__ float bf_round(float x) { return __bfloat162float(__float2bfloat16_rn(x)); }
__device__ __forceinline__ void st_async_v4(uint32_t addr, uint32_t a, uint32_t b, uint32_t c, uint32_t d, uint32_t bar) {
  asm volatile("st.async.weak.shared::cluster.mbarrier::complete_tx::bytes.v4.b32 [%0], {%1, %2, %3, %4}, [%5];"
               ::"r"(addr), "r"(a), "r"(b), "r"(c), "r"(d), "r"(bar) : "memory");
}
__device__ __forceinline__ void stmatrix_x4_t(uint32_t addr, uint32_t a, uint32_t b, uint32_t c, uint32_t d) {
  asm volatile("stmatrix.sync.aligned.m8n8.x4.trans.shared.b16 [%0], {%1, %2, %3, %4};" ::"r"(addr), "r"(a), "r"(b), "r"(c), "r"(d) : "memory");
}
__device__ __forceinline__ void ldmatrix_x4_t(uint32_t addr, uint32_t& a, uint32_t& b, uint32_t& c, uint32_t& d) {
  asm volatile("ldmatrix.sync.aligned.m8n8.x4.trans.shared.b16 {%0, %1, %2, %3}, [%4];" : "=r"(a), "=r"(b), "=r"(c), "=r"(d) : "r"(addr) : "memory");
}
__device__ __forceinline__ uint32_t lds32(uint32_t addr) { uint32_t v; asm volatile("ld.shared.b32 %0, [%1];" : "=r"(v) : "r"(addr) : "memory"); return v; }
__device__ __forceinline__ float geglu(float g, float u) {
  float z = g * fmaf(g * g, 0.0356774081f, 0.7978845608f);
  float t; asm("tanh.approx.f32 %0, %1;" : "=f"(t) : "f"(z));
  return (g * u) * fmaf(t, 0.5f, 0.5f);
}

template <int TB>
__device__ __forceinline__ void wg_ss128_init(float (&d)[64], uint64_t da, uint64_t db) {
  asm volatile(
    "wgmma.mma_async.sync.aligned.m64n128k16.f32.bf16.bf16 {%0, %1, %2, %3, %4, %5, %6, %7, %8, %9, %10, %11, %12, %13, %14, %15, %16, %17, %18, %19, %20, %21, %22, %23, %24, %25, %26, %27, %28, %29, %30, %31, %32, %33, %34, %35, %36, %37, %38, %39, %40, %41, %42, %43, %44, %45, %46, %47, %48, %49, %50, %51, %52, %53, %54, %55, %56, %57, %58, %59, %60, %61, %62, %63}, %64, %65, 0, 1, 1, 0, %66;"
    : "=f"(d[0]), "=f"(d[1]), "=f"(d[2]), "=f"(d[3]), "=f"(d[4]), "=f"(d[5]), "=f"(d[6]), "=f"(d[7]), "=f"(d[8]), "=f"(d[9]), "=f"(d[10]), "=f"(d[11]), "=f"(d[12]), "=f"(d[13]), "=f"(d[14]), "=f"(d[15]), "=f"(d[16]), "=f"(d[17]), "=f"(d[18]), "=f"(d[19]), "=f"(d[20]), "=f"(d[21]), "=f"(d[22]), "=f"(d[23]), "=f"(d[24]), "=f"(d[25]), "=f"(d[26]), "=f"(d[27]), "=f"(d[28]), "=f"(d[29]), "=f"(d[30]), "=f"(d[31]), "=f"(d[32]), "=f"(d[33]), "=f"(d[34]), "=f"(d[35]), "=f"(d[36]), "=f"(d[37]), "=f"(d[38]), "=f"(d[39]), "=f"(d[40]), "=f"(d[41]), "=f"(d[42]), "=f"(d[43]), "=f"(d[44]), "=f"(d[45]), "=f"(d[46]), "=f"(d[47]), "=f"(d[48]), "=f"(d[49]), "=f"(d[50]), "=f"(d[51]), "=f"(d[52]), "=f"(d[53]), "=f"(d[54]), "=f"(d[55]), "=f"(d[56]), "=f"(d[57]), "=f"(d[58]), "=f"(d[59]), "=f"(d[60]), "=f"(d[61]), "=f"(d[62]), "=f"(d[63])
    : "l"(da), "l"(db), "n"(TB));
}
template <int TB>
__device__ __forceinline__ void wg_ss128(float (&d)[64], uint64_t da, uint64_t db) {
  asm volatile(
    "wgmma.mma_async.sync.aligned.m64n128k16.f32.bf16.bf16 {%0, %1, %2, %3, %4, %5, %6, %7, %8, %9, %10, %11, %12, %13, %14, %15, %16, %17, %18, %19, %20, %21, %22, %23, %24, %25, %26, %27, %28, %29, %30, %31, %32, %33, %34, %35, %36, %37, %38, %39, %40, %41, %42, %43, %44, %45, %46, %47, %48, %49, %50, %51, %52, %53, %54, %55, %56, %57, %58, %59, %60, %61, %62, %63}, %64, %65, 1, 1, 1, 0, %66;"
    : "+f"(d[0]), "+f"(d[1]), "+f"(d[2]), "+f"(d[3]), "+f"(d[4]), "+f"(d[5]), "+f"(d[6]), "+f"(d[7]), "+f"(d[8]), "+f"(d[9]), "+f"(d[10]), "+f"(d[11]), "+f"(d[12]), "+f"(d[13]), "+f"(d[14]), "+f"(d[15]), "+f"(d[16]), "+f"(d[17]), "+f"(d[18]), "+f"(d[19]), "+f"(d[20]), "+f"(d[21]), "+f"(d[22]), "+f"(d[23]), "+f"(d[24]), "+f"(d[25]), "+f"(d[26]), "+f"(d[27]), "+f"(d[28]), "+f"(d[29]), "+f"(d[30]), "+f"(d[31]), "+f"(d[32]), "+f"(d[33]), "+f"(d[34]), "+f"(d[35]), "+f"(d[36]), "+f"(d[37]), "+f"(d[38]), "+f"(d[39]), "+f"(d[40]), "+f"(d[41]), "+f"(d[42]), "+f"(d[43]), "+f"(d[44]), "+f"(d[45]), "+f"(d[46]), "+f"(d[47]), "+f"(d[48]), "+f"(d[49]), "+f"(d[50]), "+f"(d[51]), "+f"(d[52]), "+f"(d[53]), "+f"(d[54]), "+f"(d[55]), "+f"(d[56]), "+f"(d[57]), "+f"(d[58]), "+f"(d[59]), "+f"(d[60]), "+f"(d[61]), "+f"(d[62]), "+f"(d[63])
    : "l"(da), "l"(db), "n"(TB));
}
template <int TB>
__device__ __forceinline__ void wg_ss160(float (&d)[80], uint64_t da, uint64_t db) {
  asm volatile(
    "wgmma.mma_async.sync.aligned.m64n160k16.f32.bf16.bf16 {%0, %1, %2, %3, %4, %5, %6, %7, %8, %9, %10, %11, %12, %13, %14, %15, %16, %17, %18, %19, %20, %21, %22, %23, %24, %25, %26, %27, %28, %29, %30, %31, %32, %33, %34, %35, %36, %37, %38, %39, %40, %41, %42, %43, %44, %45, %46, %47, %48, %49, %50, %51, %52, %53, %54, %55, %56, %57, %58, %59, %60, %61, %62, %63, %64, %65, %66, %67, %68, %69, %70, %71, %72, %73, %74, %75, %76, %77, %78, %79}, %80, %81, 1, 1, 1, 0, %82;"
    : "+f"(d[0]), "+f"(d[1]), "+f"(d[2]), "+f"(d[3]), "+f"(d[4]), "+f"(d[5]), "+f"(d[6]), "+f"(d[7]), "+f"(d[8]), "+f"(d[9]), "+f"(d[10]), "+f"(d[11]), "+f"(d[12]), "+f"(d[13]), "+f"(d[14]), "+f"(d[15]), "+f"(d[16]), "+f"(d[17]), "+f"(d[18]), "+f"(d[19]), "+f"(d[20]), "+f"(d[21]), "+f"(d[22]), "+f"(d[23]), "+f"(d[24]), "+f"(d[25]), "+f"(d[26]), "+f"(d[27]), "+f"(d[28]), "+f"(d[29]), "+f"(d[30]), "+f"(d[31]), "+f"(d[32]), "+f"(d[33]), "+f"(d[34]), "+f"(d[35]), "+f"(d[36]), "+f"(d[37]), "+f"(d[38]), "+f"(d[39]), "+f"(d[40]), "+f"(d[41]), "+f"(d[42]), "+f"(d[43]), "+f"(d[44]), "+f"(d[45]), "+f"(d[46]), "+f"(d[47]), "+f"(d[48]), "+f"(d[49]), "+f"(d[50]), "+f"(d[51]), "+f"(d[52]), "+f"(d[53]), "+f"(d[54]), "+f"(d[55]), "+f"(d[56]), "+f"(d[57]), "+f"(d[58]), "+f"(d[59]), "+f"(d[60]), "+f"(d[61]), "+f"(d[62]), "+f"(d[63]), "+f"(d[64]), "+f"(d[65]), "+f"(d[66]), "+f"(d[67]), "+f"(d[68]), "+f"(d[69]), "+f"(d[70]), "+f"(d[71]), "+f"(d[72]), "+f"(d[73]), "+f"(d[74]), "+f"(d[75]), "+f"(d[76]), "+f"(d[77]), "+f"(d[78]), "+f"(d[79])
    : "l"(da), "l"(db), "n"(TB));
}
template <int TB>
__device__ __forceinline__ void wg_rs128(float (&d)[64], uint32_t a0, uint32_t a1, uint32_t a2, uint32_t a3, uint64_t db) {
  asm volatile(
    "wgmma.mma_async.sync.aligned.m64n128k16.f32.bf16.bf16 {%0, %1, %2, %3, %4, %5, %6, %7, %8, %9, %10, %11, %12, %13, %14, %15, %16, %17, %18, %19, %20, %21, %22, %23, %24, %25, %26, %27, %28, %29, %30, %31, %32, %33, %34, %35, %36, %37, %38, %39, %40, %41, %42, %43, %44, %45, %46, %47, %48, %49, %50, %51, %52, %53, %54, %55, %56, %57, %58, %59, %60, %61, %62, %63}, {%64, %65, %66, %67}, %68, 1, 1, 1, %69;"
    : "+f"(d[0]), "+f"(d[1]), "+f"(d[2]), "+f"(d[3]), "+f"(d[4]), "+f"(d[5]), "+f"(d[6]), "+f"(d[7]), "+f"(d[8]), "+f"(d[9]), "+f"(d[10]), "+f"(d[11]), "+f"(d[12]), "+f"(d[13]), "+f"(d[14]), "+f"(d[15]), "+f"(d[16]), "+f"(d[17]), "+f"(d[18]), "+f"(d[19]), "+f"(d[20]), "+f"(d[21]), "+f"(d[22]), "+f"(d[23]), "+f"(d[24]), "+f"(d[25]), "+f"(d[26]), "+f"(d[27]), "+f"(d[28]), "+f"(d[29]), "+f"(d[30]), "+f"(d[31]), "+f"(d[32]), "+f"(d[33]), "+f"(d[34]), "+f"(d[35]), "+f"(d[36]), "+f"(d[37]), "+f"(d[38]), "+f"(d[39]), "+f"(d[40]), "+f"(d[41]), "+f"(d[42]), "+f"(d[43]), "+f"(d[44]), "+f"(d[45]), "+f"(d[46]), "+f"(d[47]), "+f"(d[48]), "+f"(d[49]), "+f"(d[50]), "+f"(d[51]), "+f"(d[52]), "+f"(d[53]), "+f"(d[54]), "+f"(d[55]), "+f"(d[56]), "+f"(d[57]), "+f"(d[58]), "+f"(d[59]), "+f"(d[60]), "+f"(d[61]), "+f"(d[62]), "+f"(d[63])
    : "r"(a0), "r"(a1), "r"(a2), "r"(a3), "l"(db), "n"(TB));
}
template <int TB>
__device__ __forceinline__ void wg_rs160(float (&d)[80], uint32_t a0, uint32_t a1, uint32_t a2, uint32_t a3, uint64_t db) {
  asm volatile(
    "wgmma.mma_async.sync.aligned.m64n160k16.f32.bf16.bf16 {%0, %1, %2, %3, %4, %5, %6, %7, %8, %9, %10, %11, %12, %13, %14, %15, %16, %17, %18, %19, %20, %21, %22, %23, %24, %25, %26, %27, %28, %29, %30, %31, %32, %33, %34, %35, %36, %37, %38, %39, %40, %41, %42, %43, %44, %45, %46, %47, %48, %49, %50, %51, %52, %53, %54, %55, %56, %57, %58, %59, %60, %61, %62, %63, %64, %65, %66, %67, %68, %69, %70, %71, %72, %73, %74, %75, %76, %77, %78, %79}, {%80, %81, %82, %83}, %84, 1, 1, 1, %85;"
    : "+f"(d[0]), "+f"(d[1]), "+f"(d[2]), "+f"(d[3]), "+f"(d[4]), "+f"(d[5]), "+f"(d[6]), "+f"(d[7]), "+f"(d[8]), "+f"(d[9]), "+f"(d[10]), "+f"(d[11]), "+f"(d[12]), "+f"(d[13]), "+f"(d[14]), "+f"(d[15]), "+f"(d[16]), "+f"(d[17]), "+f"(d[18]), "+f"(d[19]), "+f"(d[20]), "+f"(d[21]), "+f"(d[22]), "+f"(d[23]), "+f"(d[24]), "+f"(d[25]), "+f"(d[26]), "+f"(d[27]), "+f"(d[28]), "+f"(d[29]), "+f"(d[30]), "+f"(d[31]), "+f"(d[32]), "+f"(d[33]), "+f"(d[34]), "+f"(d[35]), "+f"(d[36]), "+f"(d[37]), "+f"(d[38]), "+f"(d[39]), "+f"(d[40]), "+f"(d[41]), "+f"(d[42]), "+f"(d[43]), "+f"(d[44]), "+f"(d[45]), "+f"(d[46]), "+f"(d[47]), "+f"(d[48]), "+f"(d[49]), "+f"(d[50]), "+f"(d[51]), "+f"(d[52]), "+f"(d[53]), "+f"(d[54]), "+f"(d[55]), "+f"(d[56]), "+f"(d[57]), "+f"(d[58]), "+f"(d[59]), "+f"(d[60]), "+f"(d[61]), "+f"(d[62]), "+f"(d[63]), "+f"(d[64]), "+f"(d[65]), "+f"(d[66]), "+f"(d[67]), "+f"(d[68]), "+f"(d[69]), "+f"(d[70]), "+f"(d[71]), "+f"(d[72]), "+f"(d[73]), "+f"(d[74]), "+f"(d[75]), "+f"(d[76]), "+f"(d[77]), "+f"(d[78]), "+f"(d[79])
    : "r"(a0), "r"(a1), "r"(a2), "r"(a3), "l"(db), "n"(TB));
}
template <int TB>
__device__ __forceinline__ void wg_cv32(float (&d)[16], uint32_t a0, uint32_t a1, uint32_t a2, uint32_t a3, uint64_t db) {
  asm volatile(
    "wgmma.mma_async.sync.aligned.m64n32k16.f32.bf16.bf16 {%0, %1, %2, %3, %4, %5, %6, %7, %8, %9, %10, %11, %12, %13, %14, %15}, {%16, %17, %18, %19}, %20, 1, 1, 1, %21;"
    : "+f"(d[0]), "+f"(d[1]), "+f"(d[2]), "+f"(d[3]), "+f"(d[4]), "+f"(d[5]), "+f"(d[6]), "+f"(d[7]), "+f"(d[8]), "+f"(d[9]), "+f"(d[10]), "+f"(d[11]), "+f"(d[12]), "+f"(d[13]), "+f"(d[14]), "+f"(d[15])
    : "r"(a0), "r"(a1), "r"(a2), "r"(a3), "l"(db), "n"(TB));
}
template <int TB>
__device__ __forceinline__ void wg_cv24(float (&d)[16], uint32_t a0, uint32_t a1, uint32_t a2, uint32_t a3, uint64_t db) {
  asm volatile(
    "wgmma.mma_async.sync.aligned.m64n24k16.f32.bf16.bf16 {%0, %1, %2, %3, %4, %5, %6, %7, %8, %9, %10, %11}, {%12, %13, %14, %15}, %16, 1, 1, 1, %17;"
    : "+f"(d[4]), "+f"(d[5]), "+f"(d[6]), "+f"(d[7]), "+f"(d[8]), "+f"(d[9]), "+f"(d[10]), "+f"(d[11]), "+f"(d[12]), "+f"(d[13]), "+f"(d[14]), "+f"(d[15])
    : "r"(a0), "r"(a1), "r"(a2), "r"(a3), "l"(db), "n"(TB));
}
template <int TB>
__device__ __forceinline__ void wg_cv16(float (&d)[16], uint32_t a0, uint32_t a1, uint32_t a2, uint32_t a3, uint64_t db) {
  asm volatile(
    "wgmma.mma_async.sync.aligned.m64n16k16.f32.bf16.bf16 {%0, %1, %2, %3, %4, %5, %6, %7}, {%8, %9, %10, %11}, %12, 1, 1, 1, %13;"
    : "+f"(d[8]), "+f"(d[9]), "+f"(d[10]), "+f"(d[11]), "+f"(d[12]), "+f"(d[13]), "+f"(d[14]), "+f"(d[15])
    : "r"(a0), "r"(a1), "r"(a2), "r"(a3), "l"(db), "n"(TB));
}
template <int TB>
__device__ __forceinline__ void wg_cv8(float (&d)[16], uint32_t a0, uint32_t a1, uint32_t a2, uint32_t a3, uint64_t db) {
  asm volatile(
    "wgmma.mma_async.sync.aligned.m64n8k16.f32.bf16.bf16 {%0, %1, %2, %3}, {%4, %5, %6, %7}, %8, 1, 1, 1, %9;"
    : "+f"(d[12]), "+f"(d[13]), "+f"(d[14]), "+f"(d[15])
    : "r"(a0), "r"(a1), "r"(a2), "r"(a3), "l"(db), "n"(TB));
}

__global__ void __launch_bounds__(512) prep_kernel(const __nv_bfloat16* __restrict__ x, const __nv_bfloat16* __restrict__ logA,
                                                   const __nv_bfloat16* __restrict__ Aim, const __nv_bfloat16* __restrict__ Cre,
                                                   const __nv_bfloat16* __restrict__ Cim, const __nv_bfloat16* __restrict__ logdt,
                                                   const __nv_bfloat16* __restrict__ Dsk) {
  __shared__ __align__(16) unsigned char sm[40960];
  const int tid = threadIdx.x, warp = tid >> 5, lane = tid & 31;
  if (blockIdx.x < 128) {
    constexpr int PITCH = 289;
    uint32_t* s_xn = (uint32_t*)sm;
    uint32_t* s_bs = s_xn + 16 * PITCH;
    const int row = blockIdx.x * 16 + warp;
    const uint32_t* xr = (const uint32_t*)(x + (size_t)row * D_);
    uint32_t v[9];
#pragma unroll
    for (int i = 0; i < 9; i++) v[i] = __ldg(xr + lane + 32 * i);
    float s = 0.f;
#pragma unroll
    for (int i = 0; i < 9; i++) s += bf_lo(v[i]) + bf_hi(v[i]);
#pragma unroll
    for (int o = 16; o; o >>= 1) s += __shfl_xor_sync(0xffffffffu, s, o);
    const float mean = s * (1.0f / D_);
    float q = 0.f;
#pragma unroll
    for (int i = 0; i < 9; i++) { float a = bf_lo(v[i]) - mean, b = bf_hi(v[i]) - mean; q = fmaf(a, a, q); q = fmaf(b, b, q); }
#pragma unroll
    for (int o = 16; o; o >>= 1) q += __shfl_xor_sync(0xffffffffu, q, o);
    const float mb = bf_round(mean);
    const float den = bf_round(sqrtf(bf_round(bf_round(q * (1.0f / D_)) + 1e-5f)));
    const float rinv = 1.0f / den;
    uint32_t* xo = (uint32_t*)(g_xn + (size_t)row * D_);
#pragma unroll
    for (int i = 0; i < 9; i++) {
      float x0 = bf_lo(v[i]), x1 = bf_hi(v[i]);
      uint32_t n = pack_bf16(bf_round(x0 - mb) * rinv, bf_round(x1 - mb) * rinv);
      uint32_t dk = __ldg((const uint32_t*)Dsk + lane + 32 * i);
      uint32_t b = pack_bf16(fmaf(bf_lo(n), bf_lo(dk), x0), fmaf(bf_hi(n), bf_hi(dk), x1));
      xo[lane + 32 * i] = n;
      s_xn[warp * PITCH + lane + 32 * i] = n;
      s_bs[warp * PITCH + lane + 32 * i] = b;
    }
    __syncthreads();
    for (int t = tid; t < 576; t += 512) {
      const int arr = t >= 288, cp = t - arr * 288;
      const uint32_t* src = (arr ? s_bs : s_xn) + cp;
      uint32_t lo[8], hi[8];
#pragma unroll
      for (int r = 0; r < 8; r++) {
        uint32_t a = src[(2 * r) * PITCH], b = src[(2 * r + 1) * PITCH];
        lo[r] = __byte_perm(a, b, 0x5410);
        hi[r] = __byte_perm(a, b, 0x7632);
      }
      __nv_bfloat16* dst = (arr ? g_baseT : g_xnT) + (size_t)(2 * cp) * L_ + blockIdx.x * 16;
      ((uint4*)dst)[0] = make_uint4(lo[0], lo[1], lo[2], lo[3]);
      ((uint4*)dst)[1] = make_uint4(lo[4], lo[5], lo[6], lo[7]);
      ((uint4*)(dst + L_))[0] = make_uint4(hi[0], hi[1], hi[2], hi[3]);
      ((uint4*)(dst + L_))[1] = make_uint4(hi[4], hi[5], hi[6], hi[7]);
    }
  } else {
    float4* s_par = (float4*)sm;
    float* s_red = (float*)(sm + 8192);
    const int ch0 = (blockIdx.x - 128) * 4;
    {
      const int ch = ch0 + (tid >> 7), n = tid & 127;
      const float dt = bf_round(expf(__bfloat162float(logdt[ch])));
      const float are = -bf_round(expf(__bfloat162float(logA[ch * NM_ + n]))) * dt;
      const float aim = __bfloat162float(Aim[ch * NM_ + n]) * dt;
      const float cr = __bfloat162float(Cre[ch * NM_ + n]) * dt, ci = __bfloat162float(Cim[ch * NM_ + n]) * dt;
      s_par[tid] = make_float4(are * 1.4426950408889634f, aim * 0.15915494309189535f, 2.f * cr, 2.f * ci);
    }
    __syncthreads();
    const int g = lane >> 2, q = lane & 3;
    float acc[6][4];
#pragma unroll
    for (int t = 0; t < 6; t++) { acc[t][0] = acc[t][1] = acc[t][2] = acc[t][3] = 0.f; }
    const float j1 = (float)g, j2 = (float)(g + 8);
#pragma unroll 2
    for (int ks = 0; ks < 8; ks++) {
      const float4 p = s_par[warp * 32 + ks * 4 + q];
      float r1, i1, r2, i2;
      {
        float m1 = exp2f(p.x * j1), m2 = exp2f(p.x * j2);
        float t1 = p.y * j1, t2 = p.y * j2;
        t1 = (t1 - rintf(t1)) * 6.283185307179586f; t2 = (t2 - rintf(t2)) * 6.283185307179586f;
        r1 = m1 * __cosf(t1); i1 = m1 * __sinf(t1); r2 = m2 * __cosf(t2); i2 = m2 * __sinf(t2);
      }
      float ar1[4], ai1[4], ar2[4], ai2[4];
#pragma unroll
      for (int s = 0; s < 4; s++) {
        ar1[s] = r1; ai1[s] = i1; ar2[s] = r2; ai2[s] = i2;
        float nr = fmaf(r1, r1, -i1 * i1); i1 = 2.f * r1 * i1; r1 = nr;
        nr = fmaf(r2, r2, -i2 * i2); i2 = 2.f * r2 * i2; r2 = nr;
      }
      auto mma = [&](float (&d)[4], int s, float er, float ei) {
        float b0 = fmaf(p.z, er, -p.w * ei), b1 = -fmaf(p.z, ei, p.w * er);
        asm volatile("mma.sync.aligned.m16n8k8.row.col.f32.tf32.tf32.f32 {%0,%1,%2,%3}, {%4,%5,%6,%7}, {%8,%9}, {%0,%1,%2,%3};"
                     : "+f"(d[0]), "+f"(d[1]), "+f"(d[2]), "+f"(d[3])
                     : "r"(__float_as_uint(ar1[s])), "r"(__float_as_uint(ar2[s])), "r"(__float_as_uint(ai1[s])), "r"(__float_as_uint(ai2[s])),
                       "r"(__float_as_uint(b0)), "r"(__float_as_uint(b1)));
      };
      mma(acc[0], 0, r1, i1);
      mma(acc[1], 0, r2, i2);
#pragma unroll
      for (int s = 1; s <= 4; s++) {
        float nr = fmaf(r2, r2, -i2 * i2); i2 = 2.f * r2 * i2; r2 = nr;
        mma(acc[1 + s], s < 4 ? s : 0, r2, i2);
      }
    }
    const int chl = warp >> 2, wq = warp & 3;
    float* red = s_red + chl * 648 * 2;
    auto put = [&](float* dst) {
#pragma unroll
      for (int t = 0; t < 5; t++) {
        dst[t * 128 + 16 * (2 * q) + g] = acc[t][0]; dst[t * 128 + 16 * (2 * q + 1) + g] = acc[t][1];
        dst[t * 128 + 16 * (2 * q) + g + 8] = acc[t][2]; dst[t * 128 + 16 * (2 * q + 1) + g + 8] = acc[t][3];
      }
      if (lane == 0) dst[640] = acc[5][0];
    };
    auto add = [&](const float* src) {
#pragma unroll
      for (int t = 0; t < 5; t++) {
        acc[t][0] += src[t * 128 + 16 * (2 * q) + g]; acc[t][1] += src[t * 128 + 16 * (2 * q + 1) + g];
        acc[t][2] += src[t * 128 + 16 * (2 * q) + g + 8]; acc[t][3] += src[t * 128 + 16 * (2 * q + 1) + g + 8];
      }
      acc[5][0] += src[640];
    };
    if (wq >= 2) put(red + (wq - 2) * 648);
    __syncthreads();
    if (wq < 2) add(red + wq * 648);
    __syncthreads();
    if (wq == 1) put(red);
    __syncthreads();
    if (wq == 0) { add(red); put(red + 648); }
    __syncthreads();
    {
      const int chl2 = tid >> 7;
      const float* kd = s_red + chl2 * 648 * 2 + 648;
      auto kval = [&](int l) -> float {
        if (l < 0) return 0.f;
        int pos = (int)bf_round((float)l);
        int idx = pos < 256 ? pos : pos < 512 ? 128 + (pos >> 1) : pos < 1024 ? 256 + (pos >> 2) : 384 + (pos >> 3);
        return kd[idx];
      };
      uint32_t* dst = g_kp + (size_t)(ch0 + chl2) * KP_LEN;
      for (int i = tid & 127; i < KP_LEN; i += 128) dst[i] = pack_bf16(kval(i - 64), kval(i - 65));
    }
  }
}

constexpr int NST = 7, SLOT = 9216;
constexpr uint32_t SM_XN = 0, SM_HIN = 147456, SM_RING = 163840, SM_BAR = SM_RING + NST * SLOT;
constexpr uint32_t FFN_SMEM = SM_BAR + 256;
constexpr uint32_t B_FULL = 0, B_EMPTY = 56, B_XN = 112, B_HF = 184, B_HE = 200;

__global__ void __cluster_dims__(2, 1, 1) __launch_bounds__(384, 1)
ffn_kernel(const __grid_constant__ CUtensorMap m_xn, const __grid_constant__ CUtensorMap m_gate, const __grid_constant__ CUtensorMap m_up,
           const __grid_constant__ CUtensorMap m_dn, const __grid_constant__ CUtensorMap m_dp, const __grid_constant__ CUtensorMap m_part) {
  extern __shared__ __align__(1024) unsigned char smem_raw[];
  const uint32_t sb = smem_u32(smem_raw);
  const uint32_t bar = sb + SM_BAR;
  const int j = blockIdx.x & 1, pair = blockIdx.x >> 1, mt = pair & 15, sp = pair >> 4;
  const int wg = __shfl_sync(0xffffffffu, threadIdx.x >> 7, 0);
  if (threadIdx.x == 0) {
    if (sb & 1023) __trap();
    for (int i = 0; i < NST; i++) { mbar_init(bar + B_FULL + 8 * i, 1); mbar_init(bar + B_EMPTY + 8 * i, 2); }
    for (int i = 0; i < 9; i++) mbar_init(bar + B_XN + 8 * i, 1);
    for (int i = 0; i < 2; i++) { mbar_init(bar + B_HF + 8 * i, 1); mbar_init(bar + B_HE + 8 * i, 1); }
    mbar_expect_tx(bar + B_HF, 8192); mbar_expect_tx(bar + B_HF + 8, 8192);
    asm volatile("fence.mbarrier_init.release.cluster;" ::: "memory");
  }
  __syncthreads();
  cluster_sync();

  if (wg == 2) {
    asm volatile("setmaxnreg.dec.sync.aligned.u32 24;");
    if (threadIdx.x < 288) {
      const int f0 = sp * 1152;
      uint32_t slot = 0, ph = 1;
      bool el = elect_one();
      if (el) {
        for (int kb = 0; kb < 9; kb++) {
          mbar_expect_tx(bar + B_XN + 8 * kb, 16384);
          tma_2d(sb + SM_XN + kb * 16384, &m_xn, kb * 64, mt * 128, bar + B_XN + 8 * kb);
        }
      }
      for (int c = 0; c <= 9; c++) {
        const int fc = f0 + c * 128;
        if (c < 9) {
          for (int u = 0; u < 18; u++) {
            mbar_wait(bar + B_EMPTY + 8 * slot, ph);
            if (el) {
              const uint32_t dst = sb + SM_RING + slot * SLOT, fb = bar + B_FULL + 8 * slot;
              mbar_expect_tx(fb, 8192);
              tma_2d(dst, &m_gate, fc + 64 * j, 32 * u, fb);
              tma_2d(dst + 4096, &m_up, fc + 64 * j, 32 * u, fb);
            }
            if (++slot == NST) { slot = 0; ph ^= 1; }
          }
        }
        if (c > 0) {
          const int fp = fc - 128 + 64 * (1 - j);
          for (int u = 0; u < 4; u++) {
            mbar_wait(bar + B_EMPTY + 8 * slot, ph);
            if (el) {
              const uint32_t dst = sb + SM_RING + slot * SLOT, fb = bar + B_FULL + 8 * slot;
              mbar_expect_tx(fb, 9216);
              tma_5d(dst, &m_dp, 0, 0, (fp >> 3) + 4 * (u >> 1), 2 * (u & 1), 9 * j, fb);
            }
            if (++slot == NST) { slot = 0; ph ^= 1; }
          }
        }
        if (c < 9) {
          for (int u = 0; u < 4; u++) {
            mbar_wait(bar + B_EMPTY + 8 * slot, ph);
            if (el) {
              const uint32_t dst = sb + SM_RING + slot * SLOT, fb = bar + B_FULL + 8 * slot;
              mbar_expect_tx(fb, 9216);
              tma_3d(dst, &m_dn, 0, fc + 64 * j + 16 * u, 9 * j, fb);
            }
            if (++slot == NST) { slot = 0; ph ^= 1; }
          }
        }
      }
    }
  } else {
    asm volatile("setmaxnreg.inc.sync.aligned.u32 240;");
    const int t = threadIdx.x & 127, w = t >> 5, lane = t & 31;
    const bool leader = (t == 0);
    float O1[80], O2[64];
#pragma unroll
    for (int i = 0; i < 80; i++) O1[i] = 0.f;
#pragma unroll
    for (int i = 0; i < 64; i++) O2[i] = 0.f;
    uint32_t slot = 0, ph = 0, prev = 0;
    const uint32_t hin = sb + SM_HIN + wg * 8192;
    const uint32_t r_hin = mapa(hin + (16 * w + (lane >> 2)) * 128 + (((lane & 3) ^ (lane >> 2)) << 4), j ^ 1);
    const uint32_t r_hf = mapa(bar + B_HF + 8 * wg, j ^ 1), r_he = mapa(bar + B_HE + 8 * wg, j ^ 1);
    const uint64_t dA0 = mk_desc(sb + SM_XN + wg * 8192, 16, 1024, 1);
    const uint64_t dH0 = mk_desc(hin, 16, 1024, 1);
    const uint64_t dG0 = mk_desc(sb + SM_RING, 4096, 1024, 1);
    const uint64_t dW0 = mk_desc(sb + SM_RING, 1024, 512, 2);
    auto adv = [&]() { prev = slot; if (++slot == NST) { slot = 0; ph ^= 1; } };
    auto release = [&](uint32_t s) { if (leader) mbar_arrive(bar + B_EMPTY + 8 * s); };
    uint32_t p0 = 0, p1 = 0, p2 = 0;
    auto g2_peer = [&](int cp) {
      mbar_wait(bar + B_HF + 8 * wg, cp & 1);
      if (leader && cp < 8) mbar_expect_tx(bar + B_HF + 8 * wg, 8192);
      fence_async_smem();
      const uint32_t lastg = prev;
#pragma unroll
      for (int u = 0; u < 4; u++) {
        mbar_wait(bar + B_FULL + 8 * slot, ph);
        const uint64_t db = dW0 + (uint64_t)(slot * (SLOT >> 4));
        wg_fence();
        wg_ss160<1>(O1, dH0 + 2 * u, db);
        wg_ss128<1>(O2, dH0 + 2 * u, db + 320);
        wg_commit();
        if (u == 0) { wg_wait<1>(); if (cp < 8) release(lastg); p0 = slot; }
        if (u == 1) p1 = slot;
        if (u == 2) p2 = slot;
        adv();
      }
    };

    auto chunk = [&](auto first_c, const int c) {
      constexpr bool FIRST = decltype(first_c)::value;
      float S[64];
      {
        if (FIRST) mbar_wait(bar + B_XN, 0);
        mbar_wait(bar + B_FULL + 8 * slot, ph);
        const uint64_t db = dG0 + (uint64_t)(slot * (SLOT >> 4));
        wg_fence();
        wg_ss128_init<1>(S, dA0, db);
        wg_ss128<1>(S, dA0 + 2, db + 128);
        wg_commit();
        adv();
      }
#pragma unroll 1
      for (int u = 1; u < 18; u++) {
        if (FIRST && !(u & 1)) mbar_wait(bar + B_XN + 8 * (u >> 1), 0);
        mbar_wait(bar + B_FULL + 8 * slot, ph);
        const uint64_t da = dA0 + (uint64_t)((u >> 1) * 1024 + (u & 1) * 4);
        const uint64_t db = dG0 + (uint64_t)(slot * (SLOT >> 4));
        wg_fence();
        wg_ss128<1>(S, da, db);
        wg_ss128<1>(S, da + 2, db + 128);
        wg_commit();
        wg_wait<1>();
        release(prev);
        adv();
      }
      if constexpr (!FIRST) g2_peer(c - 1);
      else { wg_wait<0>(); release(prev); }
      reg_fence(S);
      uint32_t H[16];
#pragma unroll
      for (int g = 0; g < 8; g++) {
        H[2 * g] = pack_bf16(geglu(S[4 * g], S[32 + 4 * g]), geglu(S[4 * g + 1], S[33 + 4 * g]));
        H[2 * g + 1] = pack_bf16(geglu(S[4 * g + 2], S[34 + 4 * g]), geglu(S[4 * g + 3], S[35 + 4 * g]));
        if constexpr (!FIRST) {
          if (g == 2) { wg_wait<3>(); release(p0); }
          if (g == 5) { wg_wait<2>(); release(p1); }
        }
      }
#pragma unroll
      for (int u = 0; u < 4; u++) {
        mbar_wait(bar + B_FULL + 8 * slot, ph);
        const uint64_t db = dW0 + (uint64_t)(slot * (SLOT >> 4));
        wg_fence();
        wg_rs160<1>(O1, H[4 * u], H[4 * u + 1], H[4 * u + 2], H[4 * u + 3], db);
        wg_rs128<1>(O2, H[4 * u], H[4 * u + 1], H[4 * u + 2], H[4 * u + 3], db + 320);
        wg_commit();
        if (u == 2) {
          mbar_wait(bar + B_HE + 8 * wg, (c & 1) ^ 1);
          st_async_v4(r_hin, H[0], H[2], H[4], H[6], r_hf);
          st_async_v4(r_hin ^ 64, H[8], H[10], H[12], H[14], r_hf);
          st_async_v4(r_hin + 1024, H[1], H[3], H[5], H[7], r_hf);
          st_async_v4((r_hin ^ 64) + 1024, H[9], H[11], H[13], H[15], r_hf);
        }
        if (u < 3) wg_wait<1>(); else wg_wait<0>();
        if (u == 0) {
          if constexpr (!FIRST) { release(p2); release(prev); if (leader) mbar_arrive_remote(r_he); }
        } else release(prev);
        if (u == 3) release(slot);
        adv();
      }
    };
    chunk(std::true_type{}, 0);
#pragma unroll 1
    for (int c = 1; c < 9; c++) chunk(std::false_type{}, c);
    g2_peer(8);
    wg_wait<0>();
    reg_fence(O1); reg_fence(O2);
    const uint32_t stg = sb + SM_XN + wg * 8192;
    const int mi = lane >> 3, li = lane & 7;
    const uint32_t lane_off = (uint32_t)((8 * (mi >> 1) + li) * 128 + (((2 * w + (mi & 1)) ^ li) << 4));
#pragma unroll
    for (int g = 0; g < 36; g += 2) {
      const uint32_t a = stg + (g >> 3) * 16384 + (g & 7) * 1024 + lane_off;
      if (g < 20) stmatrix_x4_t(a, pack_bf16(O1[4 * g], O1[4 * g + 1]), pack_bf16(O1[4 * g + 2], O1[4 * g + 3]), pack_bf16(O1[4 * g + 4], O1[4 * g + 5]), pack_bf16(O1[4 * g + 6], O1[4 * g + 7]));
      else { const int h = g - 20; stmatrix_x4_t(a, pack_bf16(O2[4 * h], O2[4 * h + 1]), pack_bf16(O2[4 * h + 2], O2[4 * h + 3]), pack_bf16(O2[4 * h + 4], O2[4 * h + 5]), pack_bf16(O2[4 * h + 6], O2[4 * h + 7])); }
    }
    fence_async_smem();
    named_bar(1 + wg, 128);
    if (leader) {
#pragma unroll
      for (int i = 0; i < 9; i++) tma_store_3d(&m_part, stg + (i >> 1) * 16384 + (i & 1) * 4096, mt * 128 + wg * 64, 288 * j + 32 * i, sp);
      asm volatile("cp.async.bulk.commit_group;" ::: "memory");
      asm volatile("cp.async.bulk.wait_group 0;" ::: "memory");
    }
  }
}

constexpr uint32_t CV_U = 0, CV_BASE = 20480, CV_PART = CV_BASE + 16384, CV_KP = CV_PART + 65536, CV_X = CV_KP + 4 * 8448, CV_BAR = CV_X + 32768;
constexpr uint32_t CV_SMEM = CV_BAR + 64;

template <int NB>
__device__ __forceinline__ void conv_mma(float (&d)[16], const uint32_t* a, uint64_t db) {
  if constexpr (NB == 0) wg_cv32<0>(d, a[0], a[1], a[2], a[3], db);
  else if constexpr (NB == 1) wg_cv24<0>(d, a[0], a[1], a[2], a[3], db);
  else if constexpr (NB == 2) wg_cv16<0>(d, a[0], a[1], a[2], a[3], db);
  else wg_cv8<0>(d, a[0], a[1], a[2], a[3], db);
}

__global__ void __launch_bounds__(256, 1)
conv_kernel(const __grid_constant__ CUtensorMap m_u, const __grid_constant__ CUtensorMap m_base, const __grid_constant__ CUtensorMap m_pld,
            __nv_bfloat16* __restrict__ out) {
  extern __shared__ __align__(1024) unsigned char smem_raw[];
  const uint32_t sb = smem_u32(smem_raw);
  const uint32_t bar = sb + CV_BAR;
  const int ch0 = blockIdx.x * 4;
  const int wg = __shfl_sync(0xffffffffu, threadIdx.x >> 7, 0);
  const int t = threadIdx.x & 127, w = t >> 5, lane = t & 31;
  if (threadIdx.x == 0) {
    if (sb & 1023) __trap();
    mbar_init(bar, 1); mbar_init(bar + 8, 1);
    asm volatile("fence.mbarrier_init.release.cluster;" ::: "memory");
    mbar_expect_tx(bar, 20480 + 4 * 8448);
    for (int c = 0; c < 4; c++) tma_3d(sb + CV_U + c * 5120, &m_u, 0, -8, ch0 + c, bar);
    bulk_g2s(sb + CV_KP, g_kp + (size_t)ch0 * KP_LEN, 4 * 8448, bar);
    mbar_expect_tx(bar + 8, 16384 + 65536);
    tma_2d(sb + CV_BASE, &m_base, 0, ch0 * 32, bar + 8);
    for (int s = 0; s < 4; s++) tma_2d(sb + CV_PART + s * 16384, &m_pld, 0, (s * D_ + ch0) * 32, bar + 8);
  }
  __syncthreads();
  float acc[4][16];
#pragma unroll
  for (int c = 0; c < 4; c++)
#pragma unroll
    for (int i = 0; i < 16; i++) acc[c][i] = 0.f;
  mbar_wait(bar, 0);
  const uint32_t kp_t = sb + CV_KP + 4 * (64 + 16 * w + (lane >> 2) - 2 * (lane & 3));
  const uint64_t dU0 = mk_desc(sb + CV_U, 16, 1024, 1);
  auto block = [&](auto nbc, int c) {
    constexpr int NB = decltype(nbc)::value;
    uint32_t a[4][4][4];
#pragma unroll
    for (int ch = 0; ch < 4; ch++) {
      uint32_t v[9];
#pragma unroll
      for (int i = 0; i < 9; i++) v[i] = lds32(kp_t + ch * 8448 + 4 * (64 * c - 56 + 8 * i));
#pragma unroll
      for (int k = 0; k < 4; k++) {
        a[ch][k][0] = v[7 - 2 * k]; a[ch][k][1] = v[8 - 2 * k]; a[ch][k][2] = v[6 - 2 * k]; a[ch][k][3] = v[7 - 2 * k];
      }
    }
    wg_fence();
#pragma unroll
    for (int k = 0; k < 4; k++)
#pragma unroll
      for (int ch = 0; ch < 4; ch++) {
        const uint32_t rowoff = (uint32_t)(8 + 8 * NB - c);
        uint64_t db = dU0 + (uint64_t)(ch * 320 + rowoff * 8 + 2 * k);
        conv_mma<NB>(acc[ch], a[ch][k], db);
      }
    wg_commit();
    wg_wait<0>();
  };
  for (int c = wg; c < 8; c += 2) block(std::integral_constant<int, 0>{}, c);
  for (int c = 8 + wg; c < 16; c += 2) block(std::integral_constant<int, 1>{}, c);
  for (int c = 16 + wg; c < 24; c += 2) block(std::integral_constant<int, 2>{}, c);
  for (int c = 24 + wg; c < 32; c += 2) block(std::integral_constant<int, 3>{}, c);
#pragma unroll
  for (int c = 0; c < 4; c++) reg_fence(acc[c]);
  float fin[4][8];
  {
    float4* xw = (float4*)(smem_raw + CV_X) + wg * 1024 + t;
    const float4* xr = (const float4*)(smem_raw + CV_X) + (wg ^ 1) * 1024 + t;
    if (wg == 0) {
#pragma unroll
      for (int c = 0; c < 4; c++) {
        xw[(2 * c) * 128] = make_float4(acc[c][8], acc[c][9], acc[c][10], acc[c][11]);
        xw[(2 * c + 1) * 128] = make_float4(acc[c][12], acc[c][13], acc[c][14], acc[c][15]);
#pragma unroll
        for (int i = 0; i < 8; i++) fin[c][i] = acc[c][i];
      }
    } else {
#pragma unroll
      for (int c = 0; c < 4; c++) {
        xw[(2 * c) * 128] = make_float4(acc[c][0], acc[c][1], acc[c][2], acc[c][3]);
        xw[(2 * c + 1) * 128] = make_float4(acc[c][4], acc[c][5], acc[c][6], acc[c][7]);
#pragma unroll
        for (int i = 0; i < 8; i++) fin[c][i] = acc[c][8 + i];
      }
    }
    __syncthreads();
#pragma unroll
    for (int c = 0; c < 4; c++) {
      float4 u = xr[(2 * c) * 128], v = xr[(2 * c + 1) * 128];
      fin[c][0] += u.x; fin[c][1] += u.y; fin[c][2] += u.z; fin[c][3] += u.w;
      fin[c][4] += v.x; fin[c][5] += v.y; fin[c][6] += v.z; fin[c][7] += v.w;
    }
  }
  mbar_wait(bar + 8, 0);
  {
    const int mi = lane >> 3, li = lane & 7;
    const uint32_t off = (uint32_t)((16 * wg + 8 * (mi >> 1) + li) * 128 + (((2 * w + (mi & 1)) ^ li) << 4));
#pragma unroll
    for (int c = 0; c < 4; c++)
#pragma unroll
      for (int s = 0; s < 5; s++) {
        uint32_t r0, r1, r2, r3;
        ldmatrix_x4_t(sb + CV_BASE + s * 16384 + c * 4096 + off, r0, r1, r2, r3);
        fin[c][0] += bf_lo(r0); fin[c][1] += bf_hi(r0); fin[c][2] += bf_lo(r1); fin[c][3] += bf_hi(r1);
        fin[c][4] += bf_lo(r2); fin[c][5] += bf_hi(r2); fin[c][6] += bf_lo(r3); fin[c][7] += bf_hi(r3);
      }
#pragma unroll
    for (int i = 0; i < 8; i++) {
      const int a = 16 * wg + 8 * (i >> 2) + 2 * (lane & 3) + (i & 1), b = 16 * w + (lane >> 2) + 8 * ((i >> 1) & 1);
      uint2 v = make_uint2(pack_bf16(fin[0][i], fin[1][i]), pack_bf16(fin[2][i], fin[3][i]));
      *(uint2*)(out + (size_t)(64 * a + b) * D_ + ch0) = v;
    }
  }
}

typedef CUresult (*PFN_enc)(CUtensorMap*, CUtensorMapDataType, cuuint32_t, void*, const cuuint64_t*, const cuuint64_t*, const cuuint32_t*,
                            const cuuint32_t*, CUtensorMapInterleave, CUtensorMapSwizzle, CUtensorMapL2promotion, CUtensorMapFloatOOBfill);
struct Maps { CUtensorMap xn, gate, up, dn, dp, part, u, base, pld; };

void enc(PFN_enc fn, CUtensorMap* m, void* ptr, int rank, const cuuint64_t* dims, const cuuint64_t* strides, const cuuint32_t* box, CUtensorMapSwizzle sw) {
  cuuint32_t es[5] = {1, 1, 1, 1, 1};
  fn(m, CU_TENSOR_MAP_DATA_TYPE_BFLOAT16, rank, ptr, dims, strides, box, es, CU_TENSOR_MAP_INTERLEAVE_NONE, sw,
     CU_TENSOR_MAP_L2_PROMOTION_L2_128B, CU_TENSOR_MAP_FLOAT_OOB_FILL_NONE);
}

}

extern "C" void kernel_launch(void* const* d_in, const int* in_sizes, int n_in, void* d_out, int out_size) {
  static Maps mp;
  static void* key[3] = {nullptr, nullptr, nullptr};
  if (key[0] != d_in[8] || key[1] != d_in[9] || key[2] != d_in[10]) {
    key[0] = d_in[8]; key[1] = d_in[9]; key[2] = d_in[10];
    void* fnp = nullptr; cudaDriverEntryPointQueryResult st;
    cudaGetDriverEntryPoint("cuTensorMapEncodeTiled", &fnp, cudaEnableDefault, &st);
    PFN_enc fn = (PFN_enc)fnp;
    void *p_xn, *p_xnT, *p_base, *p_part;
    cudaGetSymbolAddress(&p_xn, g_xn); cudaGetSymbolAddress(&p_xnT, g_xnT); cudaGetSymbolAddress(&p_base, g_baseT); cudaGetSymbolAddress(&p_part, g_part);
    { cuuint64_t d[2] = {D_, L_}, s[1] = {D_ * 2}; cuuint32_t b[2] = {64, 128}; enc(fn, &mp.xn, p_xn, 2, d, s, b, CU_TENSOR_MAP_SWIZZLE_128B); }
    { cuuint64_t d[2] = {F_, D_}, s[1] = {F_ * 2}; cuuint32_t b[2] = {64, 32};
      enc(fn, &mp.gate, d_in[8], 2, d, s, b, CU_TENSOR_MAP_SWIZZLE_128B); enc(fn, &mp.up, d_in[9], 2, d, s, b, CU_TENSOR_MAP_SWIZZLE_128B); }
    { cuuint64_t d[3] = {32, F_, 18}, s[2] = {D_ * 2, 64}; cuuint32_t b[3] = {32, 16, 9}; enc(fn, &mp.dn, d_in[10], 3, d, s, b, CU_TENSOR_MAP_SWIZZLE_64B); }
    { cuuint64_t d[5] = {32, 2, F_ / 8, 4, 18}, s[4] = {D_ * 2, D_ * 16, D_ * 4, 64}; cuuint32_t b[5] = {32, 2, 4, 2, 9};
      enc(fn, &mp.dp, d_in[10], 5, d, s, b, CU_TENSOR_MAP_SWIZZLE_64B); }
    { cuuint64_t d[3] = {L_, D_, 4}, s[2] = {L_ * 2, (cuuint64_t)L_ * D_ * 2}; cuuint32_t b[3] = {64, 32, 1}; enc(fn, &mp.part, p_part, 3, d, s, b, CU_TENSOR_MAP_SWIZZLE_128B); }
    { cuuint64_t d[3] = {64, 32, D_}, s[2] = {128, L_ * 2}; cuuint32_t b[3] = {64, 40, 1}; enc(fn, &mp.u, p_xnT, 3, d, s, b, CU_TENSOR_MAP_SWIZZLE_128B); }
    { cuuint64_t d[2] = {64, 32 * D_}, s[1] = {128}; cuuint32_t b[2] = {64, 128}; enc(fn, &mp.base, p_base, 2, d, s, b, CU_TENSOR_MAP_SWIZZLE_128B); }
    { cuuint64_t d[2] = {64, 4 * 32 * D_}, s[1] = {128}; cuuint32_t b[2] = {64, 128}; enc(fn, &mp.pld, p_part, 2, d, s, b, CU_TENSOR_MAP_SWIZZLE_128B); }
    cudaFuncSetAttribute(ffn_kernel, cudaFuncAttributeMaxDynamicSharedMemorySize, FFN_SMEM);
    cudaFuncSetAttribute(conv_kernel, cudaFuncAttributeMaxDynamicSharedMemorySize, CV_SMEM);
  }
  const __nv_bfloat16* const* in = (const __nv_bfloat16* const*)d_in;
  prep_kernel<<<128 + 144, 512>>>(in[0], in[1], in[2], in[3], in[4], in[5], in[6]);
  ffn_kernel<<<128, 384, FFN_SMEM>>>(mp.xn, mp.gate, mp.up, mp.dn, mp.dp, mp.part);
  conv_kernel<<<144, 256, CV_SMEM>>>(mp.u, mp.base, mp.pld, (__nv_bfloat16*)d_out);
}
```

```cpp
#include <cuda_runtime.h>
#include <cuda_bf16.h>
#include <cuda.h>
#include <stdint.h>
#include <stdio.h>
#include <type_traits>
#define CV_BASEOFF 0

namespace {

constexpr int L_ = 2048, D_ = 576, F_ = 4608, NM_ = 128;
constexpr int KP_LEN = 2080;
constexpr int U_LEN = 2176;

__device__ __align__(1024) __nv_bfloat16 g_xn[L_ * D_];
__device__ __align__(1024) __nv_bfloat16 g_u[D_ * U_LEN];
__device__ __align__(1024) uint32_t g_kp[D_ * KP_LEN];
__device__ __align__(1024) __nv_bfloat16 g_part[4 * 512 * L_];
__device__ __align__(1024) __nv_bfloat16 g_part2[4 * L_ * 64];
__device__ __align__(1024) __nv_bfloat16 g_y5[L_ * 64];
__device__ __align__(1024) unsigned int g_cnt[32 * 32];
constexpr int C_LN = 0, C_U = 16, C_PART = 17, C_Y5 = 19, C_DONE = 20;

#define PROF_T(idx) do {} while (0)
#define PROF_ACC(idx) do {} while (0)
__device__ __forceinline__ uint32_t smem_u32(const void* p) { return (uint32_t)__cvta_generic_to_shared(p); }
__device__ __forceinline__ void mbar_init(uint32_t bar, uint32_t cnt) { asm volatile("mbarrier.init.shared::cta.b64 [%0], %1;" ::"r"(bar), "r"(cnt)); }
__device__ __forceinline__ void mbar_expect_tx(uint32_t bar, uint32_t bytes) { asm volatile("mbarrier.arrive.expect_tx.shared::cta.b64 _, [%0], %1;" ::"r"(bar), "r"(bytes) : "memory"); }
__device__ __forceinline__ void mbar_arrive(uint32_t bar) { asm volatile("mbarrier.arrive.shared::cta.b64 _, [%0];" ::"r"(bar) : "memory"); }
__device__ __forceinline__ void mbar_arrive_remote(uint32_t bar) { asm volatile("mbarrier.arrive.shared::cluster.b64 _, [%0];" ::"r"(bar) : "memory"); }
__device__ __forceinline__ bool mbar_try_wait(uint32_t bar, uint32_t parity) {
  uint32_t ok;
  asm volatile("{\n.reg .pred p;\nmbarrier.try_wait.parity.shared::cta.b64 p, [%1], %2;\nselp.u32 %0, 1, 0, p;\n}" : "=r"(ok) : "r"(bar), "r"(parity) : "memory");
  return ok;
}
__device__ __forceinline__ bool mbar_test(uint32_t bar, uint32_t parity) {
  uint32_t ok;
  asm volatile("{\n.reg .pred p;\nmbarrier.test_wait.parity.shared::cta.b64 p, [%1], %2;\nselp.u32 %0, 1, 0, p;\n}" : "=r"(ok) : "r"(bar), "r"(parity) : "memory");
  return ok;
}
__device__ __forceinline__ void mbar_wait(uint32_t bar, uint32_t parity) {
  asm volatile("{\n.reg .pred p, q;\n.reg .u32 n;\nmov.u32 n, 0;\nLW:\nmbarrier.try_wait.parity.shared::cta.b64 p, [%0], %1;\n"
               "add.u32 n, n, 1;\nsetp.lt.and.u32 q, n, 65536, !p;\n@q bra LW;\n}" ::"r"(bar), "r"(parity) : "memory");
}
__device__ __forceinline__ bool elect_one() {
  uint32_t ok;
  asm volatile("{\n.reg .pred p;\nelect.sync _|p, 0xffffffff;\nselp.u32 %0, 1, 0, p;\n}" : "=r"(ok));
  return ok;
}
__device__ __forceinline__ void tma_2d(uint32_t dst, const CUtensorMap* map, int c0, int c1, uint32_t bar) {
  asm volatile("cp.async.bulk.tensor.2d.shared::cluster.global.mbarrier::complete_tx::bytes [%0], [%1, {%3, %4}], [%2];"
               ::"r"(dst), "l"(map), "r"(bar), "r"(c0), "r"(c1) : "memory");
}
__device__ __forceinline__ void tma_3d(uint32_t dst, const CUtensorMap* map, int c0, int c1, int c2, uint32_t bar) {
  asm volatile("cp.async.bulk.tensor.3d.shared::cluster.global.mbarrier::complete_tx::bytes [%0], [%1, {%3, %4, %5}], [%2];"
               ::"r"(dst), "l"(map), "r"(bar), "r"(c0), "r"(c1), "r"(c2) : "memory");
}
__device__ __forceinline__ void tma_4d(uint32_t dst, const CUtensorMap* map, int c0, int c1, int c2, int c3, uint32_t bar) {
  asm volatile("cp.async.bulk.tensor.4d.shared::cluster.global.mbarrier::complete_tx::bytes [%0], [%1, {%3, %4, %5, %6}], [%2];"
               ::"r"(dst), "l"(map), "r"(bar), "r"(c0), "r"(c1), "r"(c2), "r"(c3) : "memory");
}
__device__ __forceinline__ void tma_5d(uint32_t dst, const CUtensorMap* map, int c0, int c1, int c2, int c3, int c4, uint32_t bar) {
  asm volatile("cp.async.bulk.tensor.5d.shared::cluster.global.mbarrier::complete_tx::bytes [%0], [%1, {%3, %4, %5, %6, %7}], [%2];"
               ::"r"(dst), "l"(map), "r"(bar), "r"(c0), "r"(c1), "r"(c2), "r"(c3), "r"(c4) : "memory");
}
__device__ __forceinline__ void tma_store_3d(const CUtensorMap* map, uint32_t src, int c0, int c1, int c2) {
  asm volatile("cp.async.bulk.tensor.3d.global.shared::cta.bulk_group [%0, {%2, %3, %4}], [%1];"
               ::"l"(map), "r"(src), "r"(c0), "r"(c1), "r"(c2) : "memory");
}
__device__ __forceinline__ void bulk_g2s(uint32_t dst, const void* src, uint32_t bytes, uint32_t bar) {
  asm volatile("cp.async.bulk.shared::cluster.global.mbarrier::complete_tx::bytes [%0], [%1], %2, [%3];"
               ::"r"(dst), "l"(src), "r"(bytes), "r"(bar) : "memory");
}
__device__ __forceinline__ void prefetch_map(const CUtensorMap* m) { asm volatile("prefetch.tensormap [%0];" ::"l"(m) : "memory"); }
__device__ __forceinline__ uint32_t mapa(uint32_t addr, uint32_t rank) { uint32_t r; asm volatile("mapa.shared::cluster.u32 %0, %1, %2;" : "=r"(r) : "r"(addr), "r"(rank)); return r; }
__device__ __forceinline__ void cluster_sync() { asm volatile("barrier.cluster.arrive.release.aligned;\nbarrier.cluster.wait.acquire.aligned;" ::: "memory"); }
__device__ __forceinline__ void fence_async_smem() { asm volatile("fence.proxy.async.shared::cta;" ::: "memory"); }
__device__ __forceinline__ void wg_fence() { asm volatile("wgmma.fence.sync.aligned;" ::: "memory"); }
__device__ __forceinline__ void wg_commit() { asm volatile("wgmma.commit_group.sync.aligned;" ::: "memory"); }
template <int N> __device__ __forceinline__ void wg_wait() { asm volatile("wgmma.wait_group.sync.aligned %0;" ::"n"(N) : "memory"); }
template <int N> __device__ __forceinline__ void reg_fence(float (&d)[N]) {
#pragma unroll
  for (int i = 0; i < N; i++) asm volatile("" : "+f"(d[i])::"memory");
}
__device__ __forceinline__ void named_bar(int id, int n) { asm volatile("bar.sync %0, %1;" ::"r"(id), "r"(n) : "memory"); }
__device__ __forceinline__ uint64_t mk_desc(uint32_t addr, uint32_t lbo, uint32_t sbo, uint32_t sw) {
  return (uint64_t)((addr & 0x3FFFF) >> 4) | ((uint64_t)(lbo >> 4) << 16) | ((uint64_t)(sbo >> 4) << 32) | ((uint64_t)sw << 62);
}
__device__ __forceinline__ uint32_t pack_bf16(float lo, float hi) {
  uint32_t r; asm("cvt.rn.bf16x2.f32 %0, %1, %2;" : "=r"(r) : "f"(hi), "f"(lo)); return r;
}
__device__ __forceinline__ float bf_lo(uint32_t v) { return __uint_as_float(v << 16); }
__device__ __forceinline__ float bf_hi(uint32_t v) { return __uint_as_float(v & 0xffff0000u); }
__device__ __forceinline__ float bf_round(float x) { return __bfloat162float(__float2bfloat16_rn(x)); }
__device__ __forceinline__ void st_async_v4(uint32_t addr, uint32_t a, uint32_t b, uint32_t c, uint32_t d, uint32_t bar) {
  asm volatile("st.async.weak.shared::cluster.mbarrier::complete_tx::bytes.v4.b32 [%0], {%1, %2, %3, %4}, [%5];"
               ::"r"(addr), "r"(a), "r"(b), "r"(c), "r"(d), "r"(bar) : "memory");
}
__device__ __forceinline__ void stmatrix_x4_t(uint32_t addr, uint32_t a, uint32_t b, uint32_t c, uint32_t d) {
  asm volatile("stmatrix.sync.aligned.m8n8.x4.trans.shared.b16 [%0], {%1, %2, %3, %4};" ::"r"(addr), "r"(a), "r"(b), "r"(c), "r"(d) : "memory");
}
__device__ __forceinline__ void ldmatrix_x4_t(uint32_t addr, uint32_t& a, uint32_t& b, uint32_t& c, uint32_t& d) {
  asm volatile("ldmatrix.sync.aligned.m8n8.x4.trans.shared.b16 {%0, %1, %2, %3}, [%4];" : "=r"(a), "=r"(b), "=r"(c), "=r"(d) : "r"(addr) : "memory");
}
__device__ __forceinline__ uint32_t lds32(uint32_t addr) { uint32_t v; asm volatile("ld.shared.b32 %0, [%1];" : "=r"(v) : "r"(addr) : "memory"); return v; }
__device__ __forceinline__ float geglu(float g, float u) {
  float z = g * fmaf(g * g, 0.0356774081f, 0.7978845608f);
  float t; asm("tanh.approx.f32 %0, %1;" : "=f"(t) : "f"(z));
  return (g * u) * fmaf(t, 0.5f, 0.5f);
}

__device__ __forceinline__ uint4 lds128(uint32_t addr) { uint4 v; asm volatile("ld.shared.v4.b32 {%0,%1,%2,%3}, [%4];" : "=r"(v.x), "=r"(v.y), "=r"(v.z), "=r"(v.w) : "r"(addr) : "memory"); return v; }
__device__ __forceinline__ void sts32(uint32_t addr, uint32_t v) { asm volatile("st.shared.b32 [%0], %1;" ::"r"(addr), "r"(v) : "memory"); }
__device__ __forceinline__ void stmatrix_x4(uint32_t addr, uint32_t a, uint32_t b, uint32_t c, uint32_t d) {
  asm volatile("stmatrix.sync.aligned.m8n8.x4.shared.b16 [%0], {%1, %2, %3, %4};" ::"r"(addr), "r"(a), "r"(b), "r"(c), "r"(d) : "memory");
}
__device__ __forceinline__ void named_arrive(int id, int n) { asm volatile("bar.arrive %0, %1;" ::"r"(id), "r"(n) : "memory"); }
__device__ __forceinline__ void fence_async_all() { asm volatile("fence.proxy.async;" ::: "memory"); }
__device__ __forceinline__ void cnt_add(int idx) {
  asm volatile("red.release.gpu.global.add.u32 [%0], 1;" ::"l"(g_cnt + idx * 32) : "memory");
}
__device__ __forceinline__ void cnt_wait(int idx, uint32_t target) {
  const unsigned int* p = g_cnt + idx * 32;
  for (int it = 0; it < (1 << 18); it++) {
    uint32_t v; asm volatile("ld.acquire.gpu.global.u32 %0, [%1];" : "=r"(v) : "l"(p) : "memory");
    if (v >= target) break;
    __nanosleep(20);
  }
}
__device__ __forceinline__ void prefetch_l2(const void* p, uint32_t bytes) { asm volatile("cp.async.bulk.prefetch.L2.global [%0], %1;" ::"l"(p), "r"(bytes) : "memory"); }

template <int TB>
__device__ __forceinline__ void wg_ss128_init(float (&d)[64], uint64_t da, uint64_t db) {
  asm volatile(
    "wgmma.mma_async.sync.aligned.m64n128k16.f32.bf16.bf16 {%0, %1, %2, %3, %4, %5, %6, %7, %8, %9, %10, %11, %12, %13, %14, %15, %16, %17, %18, %19, %20, %21, %22, %23, %24, %25, %26, %27, %28, %29, %30, %31, %32, %33, %34, %35, %36, %37, %38, %39, %40, %41, %42, %43, %44, %45, %46, %47, %48, %49, %50, %51, %52, %53, %54, %55, %56, %57, %58, %59, %60, %61, %62, %63}, %64, %65, 0, 1, 1, 0, %66;"
    : "=f"(d[0]), "=f"(d[1]), "=f"(d[2]), "=f"(d[3]), "=f"(d[4]), "=f"(d[5]), "=f"(d[6]), "=f"(d[7]), "=f"(d[8]), "=f"(d[9]), "=f"(d[10]), "=f"(d[11]), "=f"(d[12]), "=f"(d[13]), "=f"(d[14]), "=f"(d[15]), "=f"(d[16]), "=f"(d[17]), "=f"(d[18]), "=f"(d[19]), "=f"(d[20]), "=f"(d[21]), "=f"(d[22]), "=f"(d[23]), "=f"(d[24]), "=f"(d[25]), "=f"(d[26]), "=f"(d[27]), "=f"(d[28]), "=f"(d[29]), "=f"(d[30]), "=f"(d[31]), "=f"(d[32]), "=f"(d[33]), "=f"(d[34]), "=f"(d[35]), "=f"(d[36]), "=f"(d[37]), "=f"(d[38]), "=f"(d[39]), "=f"(d[40]), "=f"(d[41]), "=f"(d[42]), "=f"(d[43]), "=f"(d[44]), "=f"(d[45]), "=f"(d[46]), "=f"(d[47]), "=f"(d[48]), "=f"(d[49]), "=f"(d[50]), "=f"(d[51]), "=f"(d[52]), "=f"(d[53]), "=f"(d[54]), "=f"(d[55]), "=f"(d[56]), "=f"(d[57]), "=f"(d[58]), "=f"(d[59]), "=f"(d[60]), "=f"(d[61]), "=f"(d[62]), "=f"(d[63])
    : "l"(da), "l"(db), "n"(TB));
}
template <int TB>
__device__ __forceinline__ void wg_ss128(float (&d)[64], uint64_t da, uint64_t db) {
  asm volatile(
    "wgmma.mma_async.sync.aligned.m64n128k16.f32.bf16.bf16 {%0, %1, %2, %3, %4, %5, %6, %7, %8, %9, %10, %11, %12, %13, %14, %15, %16, %17, %18, %19, %20, %21, %22, %23, %24, %25, %26, %27, %28, %29, %30, %31, %32, %33, %34, %35, %36, %37, %38, %39, %40, %41, %42, %43, %44, %45, %46, %47, %48, %49, %50, %51, %52, %53, %54, %55, %56, %57, %58, %59, %60, %61, %62, %63}, %64, %65, 1, 1, 1, 0, %66;"
    : "+f"(d[0]), "+f"(d[1]), "+f"(d[2]), "+f"(d[3]), "+f"(d[4]), "+f"(d[5]), "+f"(d[6]), "+f"(d[7]), "+f"(d[8]), "+f"(d[9]), "+f"(d[10]), "+f"(d[11]), "+f"(d[12]), "+f"(d[13]), "+f"(d[14]), "+f"(d[15]), "+f"(d[16]), "+f"(d[17]), "+f"(d[18]), "+f"(d[19]), "+f"(d[20]), "+f"(d[21]), "+f"(d[22]), "+f"(d[23]), "+f"(d[24]), "+f"(d[25]), "+f"(d[26]), "+f"(d[27]), "+f"(d[28]), "+f"(d[29]), "+f"(d[30]), "+f"(d[31]), "+f"(d[32]), "+f"(d[33]), "+f"(d[34]), "+f"(d[35]), "+f"(d[36]), "+f"(d[37]), "+f"(d[38]), "+f"(d[39]), "+f"(d[40]), "+f"(d[41]), "+f"(d[42]), "+f"(d[43]), "+f"(d[44]), "+f"(d[45]), "+f"(d[46]), "+f"(d[47]), "+f"(d[48]), "+f"(d[49]), "+f"(d[50]), "+f"(d[51]), "+f"(d[52]), "+f"(d[53]), "+f"(d[54]), "+f"(d[55]), "+f"(d[56]), "+f"(d[57]), "+f"(d[58]), "+f"(d[59]), "+f"(d[60]), "+f"(d[61]), "+f"(d[62]), "+f"(d[63])
    : "l"(da), "l"(db), "n"(TB));
}
template <int TB>
__device__ __forceinline__ void wg_ss256(float (&d)[128], uint64_t da, uint64_t db) {
  asm volatile(
    "wgmma.mma_async.sync.aligned.m64n256k16.f32.bf16.bf16 {%0, %1, %2, %3, %4, %5, %6, %7, %8, %9, %10, %11, %12, %13, %14, %15, %16, %17, %18, %19, %20, %21, %22, %23, %24, %25, %26, %27, %28, %29, %30, %31, %32, %33, %34, %35, %36, %37, %38, %39, %40, %41, %42, %43, %44, %45, %46, %47, %48, %49, %50, %51, %52, %53, %54, %55, %56, %57, %58, %59, %60, %61, %62, %63, %64, %65, %66, %67, %68, %69, %70, %71, %72, %73, %74, %75, %76, %77, %78, %79, %80, %81, %82, %83, %84, %85, %86, %87, %88, %89, %90, %91, %92, %93, %94, %95, %96, %97, %98, %99, %100, %101, %102, %103, %104, %105, %106, %107, %108, %109, %110, %111, %112, %113, %114, %115, %116, %117, %118, %119, %120, %121, %122, %123, %124, %125, %126, %127}, %128, %129, 1, 1, 1, 0, %130;"
    : "+f"(d[0]), "+f"(d[1]), "+f"(d[2]), "+f"(d[3]), "+f"(d[4]), "+f"(d[5]), "+f"(d[6]), "+f"(d[7]), "+f"(d[8]), "+f"(d[9]), "+f"(d[10]), "+f"(d[11]), "+f"(d[12]), "+f"(d[13]), "+f"(d[14]), "+f"(d[15]), "+f"(d[16]), "+f"(d[17]), "+f"(d[18]), "+f"(d[19]), "+f"(d[20]), "+f"(d[21]), "+f"(d[22]), "+f"(d[23]), "+f"(d[24]), "+f"(d[25]), "+f"(d[26]), "+f"(d[27]), "+f"(d[28]), "+f"(d[29]), "+f"(d[30]), "+f"(d[31]), "+f"(d[32]), "+f"(d[33]), "+f"(d[34]), "+f"(d[35]), "+f"(d[36]), "+f"(d[37]), "+f"(d[38]), "+f"(d[39]), "+f"(d[40]), "+f"(d[41]), "+f"(d[42]), "+f"(d[43]), "+f"(d[44]), "+f"(d[45]), "+f"(d[46]), "+f"(d[47]), "+f"(d[48]), "+f"(d[49]), "+f"(d[50]), "+f"(d[51]), "+f"(d[52]), "+f"(d[53]), "+f"(d[54]), "+f"(d[55]), "+f"(d[56]), "+f"(d[57]), "+f"(d[58]), "+f"(d[59]), "+f"(d[60]), "+f"(d[61]), "+f"(d[62]), "+f"(d[63]), "+f"(d[64]), "+f"(d[65]), "+f"(d[66]), "+f"(d[67]), "+f"(d[68]), "+f"(d[69]), "+f"(d[70]), "+f"(d[71]), "+f"(d[72]), "+f"(d[73]), "+f"(d[74]), "+f"(d[75]), "+f"(d[76]), "+f"(d[77]), "+f"(d[78]), "+f"(d[79]), "+f"(d[80]), "+f"(d[81]), "+f"(d[82]), "+f"(d[83]), "+f"(d[84]), "+f"(d[85]), "+f"(d[86]), "+f"(d[87]), "+f"(d[88]), "+f"(d[89]), "+f"(d[90]), "+f"(d[91]), "+f"(d[92]), "+f"(d[93]), "+f"(d[94]), "+f"(d[95]), "+f"(d[96]), "+f"(d[97]), "+f"(d[98]), "+f"(d[99]), "+f"(d[100]), "+f"(d[101]), "+f"(d[102]), "+f"(d[103]), "+f"(d[104]), "+f"(d[105]), "+f"(d[106]), "+f"(d[107]), "+f"(d[108]), "+f"(d[109]), "+f"(d[110]), "+f"(d[111]), "+f"(d[112]), "+f"(d[113]), "+f"(d[114]), "+f"(d[115]), "+f"(d[116]), "+f"(d[117]), "+f"(d[118]), "+f"(d[119]), "+f"(d[120]), "+f"(d[121]), "+f"(d[122]), "+f"(d[123]), "+f"(d[124]), "+f"(d[125]), "+f"(d[126]), "+f"(d[127])
    : "l"(da), "l"(db), "n"(TB));
}
template <int TB>
__device__ __forceinline__ void wg_ss32(float (&d)[16], uint64_t da, uint64_t db) {
  asm volatile(
    "wgmma.mma_async.sync.aligned.m64n32k16.f32.bf16.bf16 {%0, %1, %2, %3, %4, %5, %6, %7, %8, %9, %10, %11, %12, %13, %14, %15}, %16, %17, 1, 1, 1, 0, %18;"
    : "+f"(d[0]), "+f"(d[1]), "+f"(d[2]), "+f"(d[3]), "+f"(d[4]), "+f"(d[5]), "+f"(d[6]), "+f"(d[7]), "+f"(d[8]), "+f"(d[9]), "+f"(d[10]), "+f"(d[11]), "+f"(d[12]), "+f"(d[13]), "+f"(d[14]), "+f"(d[15])
    : "l"(da), "l"(db), "n"(TB));
}
template <int TB>
__device__ __forceinline__ void wg_rs256(float (&d)[128], uint32_t a0, uint32_t a1, uint32_t a2, uint32_t a3, uint64_t db) {
  asm volatile(
    "wgmma.mma_async.sync.aligned.m64n256k16.f32.bf16.bf16 {%0, %1, %2, %3, %4, %5, %6, %7, %8, %9, %10, %11, %12, %13, %14, %15, %16, %17, %18, %19, %20, %21, %22, %23, %24, %25, %26, %27, %28, %29, %30, %31, %32, %33, %34, %35, %36, %37, %38, %39, %40, %41, %42, %43, %44, %45, %46, %47, %48, %49, %50, %51, %52, %53, %54, %55, %56, %57, %58, %59, %60, %61, %62, %63, %64, %65, %66, %67, %68, %69, %70, %71, %72, %73, %74, %75, %76, %77, %78, %79, %80, %81, %82, %83, %84, %85, %86, %87, %88, %89, %90, %91, %92, %93, %94, %95, %96, %97, %98, %99, %100, %101, %102, %103, %104, %105, %106, %107, %108, %109, %110, %111, %112, %113, %114, %115, %116, %117, %118, %119, %120, %121, %122, %123, %124, %125, %126, %127}, {%128, %129, %130, %131}, %132, 1, 1, 1, %133;"
    : "+f"(d[0]), "+f"(d[1]), "+f"(d[2]), "+f"(d[3]), "+f"(d[4]), "+f"(d[5]), "+f"(d[6]), "+f"(d[7]), "+f"(d[8]), "+f"(d[9]), "+f"(d[10]), "+f"(d[11]), "+f"(d[12]), "+f"(d[13]), "+f"(d[14]), "+f"(d[15]), "+f"(d[16]), "+f"(d[17]), "+f"(d[18]), "+f"(d[19]), "+f"(d[20]), "+f"(d[21]), "+f"(d[22]), "+f"(d[23]), "+f"(d[24]), "+f"(d[25]), "+f"(d[26]), "+f"(d[27]), "+f"(d[28]), "+f"(d[29]), "+f"(d[30]), "+f"(d[31]), "+f"(d[32]), "+f"(d[33]), "+f"(d[34]), "+f"(d[35]), "+f"(d[36]), "+f"(d[37]), "+f"(d[38]), "+f"(d[39]), "+f"(d[40]), "+f"(d[41]), "+f"(d[42]), "+f"(d[43]), "+f"(d[44]), "+f"(d[45]), "+f"(d[46]), "+f"(d[47]), "+f"(d[48]), "+f"(d[49]), "+f"(d[50]), "+f"(d[51]), "+f"(d[52]), "+f"(d[53]), "+f"(d[54]), "+f"(d[55]), "+f"(d[56]), "+f"(d[57]), "+f"(d[58]), "+f"(d[59]), "+f"(d[60]), "+f"(d[61]), "+f"(d[62]), "+f"(d[63]), "+f"(d[64]), "+f"(d[65]), "+f"(d[66]), "+f"(d[67]), "+f"(d[68]), "+f"(d[69]), "+f"(d[70]), "+f"(d[71]), "+f"(d[72]), "+f"(d[73]), "+f"(d[74]), "+f"(d[75]), "+f"(d[76]), "+f"(d[77]), "+f"(d[78]), "+f"(d[79]), "+f"(d[80]), "+f"(d[81]), "+f"(d[82]), "+f"(d[83]), "+f"(d[84]), "+f"(d[85]), "+f"(d[86]), "+f"(d[87]), "+f"(d[88]), "+f"(d[89]), "+f"(d[90]), "+f"(d[91]), "+f"(d[92]), "+f"(d[93]), "+f"(d[94]), "+f"(d[95]), "+f"(d[96]), "+f"(d[97]), "+f"(d[98]), "+f"(d[99]), "+f"(d[100]), "+f"(d[101]), "+f"(d[102]), "+f"(d[103]), "+f"(d[104]), "+f"(d[105]), "+f"(d[106]), "+f"(d[107]), "+f"(d[108]), "+f"(d[109]), "+f"(d[110]), "+f"(d[111]), "+f"(d[112]), "+f"(d[113]), "+f"(d[114]), "+f"(d[115]), "+f"(d[116]), "+f"(d[117]), "+f"(d[118]), "+f"(d[119]), "+f"(d[120]), "+f"(d[121]), "+f"(d[122]), "+f"(d[123]), "+f"(d[124]), "+f"(d[125]), "+f"(d[126]), "+f"(d[127])
    : "r"(a0), "r"(a1), "r"(a2), "r"(a3), "l"(db), "n"(TB));
}
template <int TB>
__device__ __forceinline__ void wg_rs32(float (&d)[16], uint32_t a0, uint32_t a1, uint32_t a2, uint32_t a3, uint64_t db) {
  asm volatile(
    "wgmma.mma_async.sync.aligned.m64n32k16.f32.bf16.bf16 {%0, %1, %2, %3, %4, %5, %6, %7, %8, %9, %10, %11, %12, %13, %14, %15}, {%16, %17, %18, %19}, %20, 1, 1, 1, %21;"
    : "+f"(d[0]), "+f"(d[1]), "+f"(d[2]), "+f"(d[3]), "+f"(d[4]), "+f"(d[5]), "+f"(d[6]), "+f"(d[7]), "+f"(d[8]), "+f"(d[9]), "+f"(d[10]), "+f"(d[11]), "+f"(d[12]), "+f"(d[13]), "+f"(d[14]), "+f"(d[15])
    : "r"(a0), "r"(a1), "r"(a2), "r"(a3), "l"(db), "n"(TB));
}
template <int TB>
__device__ __forceinline__ void wg_cv128(float (&d)[64], uint32_t a0, uint32_t a1, uint32_t a2, uint32_t a3, uint64_t db) {
  asm volatile(
    "wgmma.mma_async.sync.aligned.m64n128k16.f32.bf16.bf16 {%0, %1, %2, %3, %4, %5, %6, %7, %8, %9, %10, %11, %12, %13, %14, %15, %16, %17, %18, %19, %20, %21, %22, %23, %24, %25, %26, %27, %28, %29, %30, %31, %32, %33, %34, %35, %36, %37, %38, %39, %40, %41, %42, %43, %44, %45, %46, %47, %48, %49, %50, %51, %52, %53, %54, %55, %56, %57, %58, %59, %60, %61, %62, %63}, {%64, %65, %66, %67}, %68, 1, 1, 1, %69;"
    : "+f"(d[0]), "+f"(d[1]), "+f"(d[2]), "+f"(d[3]), "+f"(d[4]), "+f"(d[5]), "+f"(d[6]), "+f"(d[7]), "+f"(d[8]), "+f"(d[9]), "+f"(d[10]), "+f"(d[11]), "+f"(d[12]), "+f"(d[13]), "+f"(d[14]), "+f"(d[15]), "+f"(d[16]), "+f"(d[17]), "+f"(d[18]), "+f"(d[19]), "+f"(d[20]), "+f"(d[21]), "+f"(d[22]), "+f"(d[23]), "+f"(d[24]), "+f"(d[25]), "+f"(d[26]), "+f"(d[27]), "+f"(d[28]), "+f"(d[29]), "+f"(d[30]), "+f"(d[31]), "+f"(d[32]), "+f"(d[33]), "+f"(d[34]), "+f"(d[35]), "+f"(d[36]), "+f"(d[37]), "+f"(d[38]), "+f"(d[39]), "+f"(d[40]), "+f"(d[41]), "+f"(d[42]), "+f"(d[43]), "+f"(d[44]), "+f"(d[45]), "+f"(d[46]), "+f"(d[47]), "+f"(d[48]), "+f"(d[49]), "+f"(d[50]), "+f"(d[51]), "+f"(d[52]), "+f"(d[53]), "+f"(d[54]), "+f"(d[55]), "+f"(d[56]), "+f"(d[57]), "+f"(d[58]), "+f"(d[59]), "+f"(d[60]), "+f"(d[61]), "+f"(d[62]), "+f"(d[63])
    : "r"(a0), "r"(a1), "r"(a2), "r"(a3), "l"(db), "n"(TB));
}
template <int TB>
__device__ __forceinline__ void wg_cv96(float (&d)[48], uint32_t a0, uint32_t a1, uint32_t a2, uint32_t a3, uint64_t db) {
  asm volatile(
    "wgmma.mma_async.sync.aligned.m64n96k16.f32.bf16.bf16 {%0, %1, %2, %3, %4, %5, %6, %7, %8, %9, %10, %11, %12, %13, %14, %15, %16, %17, %18, %19, %20, %21, %22, %23, %24, %25, %26, %27, %28, %29, %30, %31, %32, %33, %34, %35, %36, %37, %38, %39, %40, %41, %42, %43, %44, %45, %46, %47}, {%48, %49, %50, %51}, %52, 1, 1, 1, %53;"
    : "+f"(d[0]), "+f"(d[1]), "+f"(d[2]), "+f"(d[3]), "+f"(d[4]), "+f"(d[5]), "+f"(d[6]), "+f"(d[7]), "+f"(d[8]), "+f"(d[9]), "+f"(d[10]), "+f"(d[11]), "+f"(d[12]), "+f"(d[13]), "+f"(d[14]), "+f"(d[15]), "+f"(d[16]), "+f"(d[17]), "+f"(d[18]), "+f"(d[19]), "+f"(d[20]), "+f"(d[21]), "+f"(d[22]), "+f"(d[23]), "+f"(d[24]), "+f"(d[25]), "+f"(d[26]), "+f"(d[27]), "+f"(d[28]), "+f"(d[29]), "+f"(d[30]), "+f"(d[31]), "+f"(d[32]), "+f"(d[33]), "+f"(d[34]), "+f"(d[35]), "+f"(d[36]), "+f"(d[37]), "+f"(d[38]), "+f"(d[39]), "+f"(d[40]), "+f"(d[41]), "+f"(d[42]), "+f"(d[43]), "+f"(d[44]), "+f"(d[45]), "+f"(d[46]), "+f"(d[47])
    : "r"(a0), "r"(a1), "r"(a2), "r"(a3), "l"(db), "n"(TB));
}
template <int TB>
__device__ __forceinline__ void wg_cv64(float (&d)[32], uint32_t a0, uint32_t a1, uint32_t a2, uint32_t a3, uint64_t db) {
  asm volatile(
    "wgmma.mma_async.sync.aligned.m64n64k16.f32.bf16.bf16 {%0, %1, %2, %3, %4, %5, %6, %7, %8, %9, %10, %11, %12, %13, %14, %15, %16, %17, %18, %19, %20, %21, %22, %23, %24, %25, %26, %27, %28, %29, %30, %31}, {%32, %33, %34, %35}, %36, 1, 1, 1, %37;"
    : "+f"(d[0]), "+f"(d[1]), "+f"(d[2]), "+f"(d[3]), "+f"(d[4]), "+f"(d[5]), "+f"(d[6]), "+f"(d[7]), "+f"(d[8]), "+f"(d[9]), "+f"(d[10]), "+f"(d[11]), "+f"(d[12]), "+f"(d[13]), "+f"(d[14]), "+f"(d[15]), "+f"(d[16]), "+f"(d[17]), "+f"(d[18]), "+f"(d[19]), "+f"(d[20]), "+f"(d[21]), "+f"(d[22]), "+f"(d[23]), "+f"(d[24]), "+f"(d[25]), "+f"(d[26]), "+f"(d[27]), "+f"(d[28]), "+f"(d[29]), "+f"(d[30]), "+f"(d[31])
    : "r"(a0), "r"(a1), "r"(a2), "r"(a3), "l"(db), "n"(TB));
}
template <int TB>
__device__ __forceinline__ void wg_cv128_init(float (&d)[64], uint32_t a0, uint32_t a1, uint32_t a2, uint32_t a3, uint64_t db) {
  asm volatile(
    "wgmma.mma_async.sync.aligned.m64n128k16.f32.bf16.bf16 {%0, %1, %2, %3, %4, %5, %6, %7, %8, %9, %10, %11, %12, %13, %14, %15, %16, %17, %18, %19, %20, %21, %22, %23, %24, %25, %26, %27, %28, %29, %30, %31, %32, %33, %34, %35, %36, %37, %38, %39, %40, %41, %42, %43, %44, %45, %46, %47, %48, %49, %50, %51, %52, %53, %54, %55, %56, %57, %58, %59, %60, %61, %62, %63}, {%64, %65, %66, %67}, %68, 0, 1, 1, %69;"
    : "=f"(d[0]), "=f"(d[1]), "=f"(d[2]), "=f"(d[3]), "=f"(d[4]), "=f"(d[5]), "=f"(d[6]), "=f"(d[7]), "=f"(d[8]), "=f"(d[9]), "=f"(d[10]), "=f"(d[11]), "=f"(d[12]), "=f"(d[13]), "=f"(d[14]), "=f"(d[15]), "=f"(d[16]), "=f"(d[17]), "=f"(d[18]), "=f"(d[19]), "=f"(d[20]), "=f"(d[21]), "=f"(d[22]), "=f"(d[23]), "=f"(d[24]), "=f"(d[25]), "=f"(d[26]), "=f"(d[27]), "=f"(d[28]), "=f"(d[29]), "=f"(d[30]), "=f"(d[31]), "=f"(d[32]), "=f"(d[33]), "=f"(d[34]), "=f"(d[35]), "=f"(d[36]), "=f"(d[37]), "=f"(d[38]), "=f"(d[39]), "=f"(d[40]), "=f"(d[41]), "=f"(d[42]), "=f"(d[43]), "=f"(d[44]), "=f"(d[45]), "=f"(d[46]), "=f"(d[47]), "=f"(d[48]), "=f"(d[49]), "=f"(d[50]), "=f"(d[51]), "=f"(d[52]), "=f"(d[53]), "=f"(d[54]), "=f"(d[55]), "=f"(d[56]), "=f"(d[57]), "=f"(d[58]), "=f"(d[59]), "=f"(d[60]), "=f"(d[61]), "=f"(d[62]), "=f"(d[63])
    : "r"(a0), "r"(a1), "r"(a2), "r"(a3), "l"(db), "n"(TB));
}

constexpr int NST = 7, SLOT = 9216;
constexpr uint32_t SM_XN = 0, SM_HIN = 147456, SM_RING = 163840, SM_BAR = SM_RING + NST * SLOT;
constexpr uint32_t SMEM_BYTES = SM_BAR + 256;
constexpr uint32_t B_FULL = 0, B_EMPTY = 56, B_XN = 112, B_HF = 184, B_HE = 200, B_CV = 216, B_ST = 224, B_PT = 232, B_SG = 240;
constexpr uint32_t PR_LN = 81920, PR_PAR = 102400, PR_RED = 110592;
constexpr uint32_t T_U = 81920, T_KP = 99328, T_Y = 0, T_PART = SM_HIN;
constexpr uint32_t U_BYTES = U_LEN * 2, KP_BYTES = KP_LEN * 4, Y_BYTES = 9216;

struct Params {
  CUtensorMap xn, gate, up, part, part2, dn, dn5, dp, dp5;
  const __nv_bfloat16 *x, *logA, *Aim, *Cre, *Cim, *logdt, *Dsk;
  __nv_bfloat16* out;
};

__device__ __forceinline__ void kgen4(const Params& p, unsigned char* sm, int ch0, int tid) {
  float4* s_par = (float4*)(sm + PR_PAR);
  float* s_red = (float*)(sm + PR_RED);
  const int warp = tid >> 5, lane = tid & 31;
#pragma unroll
  for (int r = 0; r < 2; r++) {
    const int i = tid + 256 * r, ch = ch0 + (i >> 7), e = ch0 * NM_ + i;
    const float dt = bf_round(expf(__bfloat162float(p.logdt[ch])));
    const float are = -bf_round(expf(__bfloat162float(p.logA[e]))) * dt;
    const float aim = __bfloat162float(p.Aim[e]) * dt;
    const float cr = __bfloat162float(p.Cre[e]) * dt, ci = __bfloat162float(p.Cim[e]) * dt;
    s_par[i] = make_float4(are * 1.4426950408889634f, aim * 0.15915494309189535f, 2.f * cr, 2.f * ci);
  }
  named_bar(3, 256);
  const int g = lane >> 2, q = lane & 3;
  float acc[6][4];
#pragma unroll
  for (int t = 0; t < 6; t++) { acc[t][0] = acc[t][1] = acc[t][2] = acc[t][3] = 0.f; }
  const float j1 = (float)g, j2 = (float)(g + 8);
#pragma unroll 2
  for (int ks = 0; ks < 16; ks++) {
    const float4 pr = s_par[warp * 64 + ks * 4 + q];
    float r1, i1, r2, i2;
    {
      float m1, m2;
      asm("ex2.approx.ftz.f32 %0, %1;" : "=f"(m1) : "f"(pr.x * j1));
      asm("ex2.approx.ftz.f32 %0, %1;" : "=f"(m2) : "f"(pr.x * j2));
      float t1 = pr.y * j1, t2 = pr.y * j2;
      t1 = (t1 - rintf(t1)) * 6.283185307179586f; t2 = (t2 - rintf(t2)) * 6.283185307179586f;
      r1 = m1 * __cosf(t1); i1 = m1 * __sinf(t1); r2 = m2 * __cosf(t2); i2 = m2 * __sinf(t2);
    }
    float ar1[4], ai1[4], ar2[4], ai2[4];
#pragma unroll
    for (int s = 0; s < 4; s++) {
      ar1[s] = r1; ai1[s] = i1; ar2[s] = r2; ai2[s] = i2;
      float nr = fmaf(r1, r1, -i1 * i1); i1 = (r1 + r1) * i1; r1 = nr;
      nr = fmaf(r2, r2, -i2 * i2); i2 = (r2 + r2) * i2; r2 = nr;
    }
    auto mma = [&](float (&d)[4], int s, float er, float ei) {
      float b0 = fmaf(pr.z, er, -pr.w * ei), b1 = -fmaf(pr.z, ei, pr.w * er);
      asm volatile("mma.sync.aligned.m16n8k8.row.col.f32.tf32.tf32.f32 {%0,%1,%2,%3}, {%4,%5,%6,%7}, {%8,%9}, {%0,%1,%2,%3};"
                   : "+f"(d[0]), "+f"(d[1]), "+f"(d[2]), "+f"(d[3])
                   : "r"(__float_as_uint(ar1[s])), "r"(__float_as_uint(ar2[s])), "r"(__float_as_uint(ai1[s])), "r"(__float_as_uint(ai2[s])),
                     "r"(__float_as_uint(b0)), "r"(__float_as_uint(b1)));
    };
    mma(acc[0], 0, r1, i1);
    mma(acc[1], 0, r2, i2);
#pragma unroll
    for (int s = 1; s <= 4; s++) {
      float nr = fmaf(r2, r2, -i2 * i2); i2 = (r2 + r2) * i2; r2 = nr;
      mma(acc[1 + s], s < 4 ? s : 0, r2, i2);
    }
  }
  float* red = s_red + (warp >> 1) * 648;
  if (warp & 1) {
#pragma unroll
    for (int t = 0; t < 5; t++) {
      red[t * 128 + 32 * q + g] = acc[t][0]; red[t * 128 + 32 * q + 16 + g] = acc[t][1];
      red[t * 128 + 32 * q + g + 8] = acc[t][2]; red[t * 128 + 32 * q + 24 + g] = acc[t][3];
    }
    if (lane == 0) red[640] = acc[5][0];
  }
  named_bar(3, 256);
  if (!(warp & 1)) {
    uint32_t* kb = (uint32_t*)red;
    if (lane == 0) acc[0][0] += __bfloat162float(p.Dsk[ch0 + (warp >> 1)]);
#pragma unroll
    for (int t = 0; t < 5; t++) {
      const int o = t * 128 + 32 * q + g;
      kb[o] = pack_bf16(acc[t][0] + red[o], 0.f); kb[o + 16] = pack_bf16(acc[t][1] + red[o + 16], 0.f);
      kb[o + 8] = pack_bf16(acc[t][2] + red[o + 8], 0.f); kb[o + 24] = pack_bf16(acc[t][3] + red[o + 24], 0.f);
    }
    if (lane == 0) kb[640] = pack_bf16(acc[5][0] + red[640], 0.f);
  }
  named_bar(3, 256);
  {
    const uint32_t* kb = (const uint32_t*)(s_red + (tid >> 6) * 648);
    uint32_t* dst = g_kp + (size_t)(ch0 + (tid >> 6)) * KP_LEN;
    for (int it = tid & 63; it < KP_LEN / 8; it += 64) {
      const int i0 = it * 8 - 16;
      uint32_t v[9];
#pragma unroll
      for (int k = 0; k < 9; k++) {
        const int l = i0 - 1 + k;
        const int sh = max(0, 24 - __clz(l | 1));
        const int idx = sh ? 128 * sh + ((l + (1 << (sh - 1)) - 1 + ((l >> sh) & 1)) >> sh) : l;
        v[k] = (l >= 0 && l < L_) ? kb[idx] : 0u;
      }
      uint4 a = make_uint4(v[1] | (v[0] << 16), v[2] | (v[1] << 16), v[3] | (v[2] << 16), v[4] | (v[3] << 16));
      uint4 b = make_uint4(v[5] | (v[4] << 16), v[6] | (v[5] << 16), v[7] | (v[6] << 16), v[8] | (v[7] << 16));
      ((uint4*)(dst + it * 8))[0] = a; ((uint4*)(dst + it * 8))[1] = b;
    }
  }
  fence_async_all();
}

template <int NR>
__device__ __forceinline__ void conv_mma(float (&d)[NR], const uint32_t* a, uint64_t db) {
  if constexpr (NR == 64) wg_cv128<0>(d, a[0], a[1], a[2], a[3], db);
  else if constexpr (NR == 48) wg_cv96<0>(d, a[0], a[1], a[2], a[3], db);
  else if constexpr (NR == 32) wg_cv64<0>(d, a[0], a[1], a[2], a[3], db);
  else wg_rs32<0>(d, a[0], a[1], a[2], a[3], db);
}
template <int GI>
__device__ __forceinline__ void conv_load(uint32_t (&a)[16], uint32_t kp) {
#pragma unroll
  for (int h = 0; h < 2; h++) {
    const int st = 2 * GI + h, s = 32 * (st >> 3) + (st & 7);
#pragma unroll
    for (int c = 0; c < 2; c++) {
      const uint32_t o = kp + c * KP_BYTES + 64 * s;
      a[8 * h + 4 * c + 0] = lds32(o); a[8 * h + 4 * c + 1] = lds32(o + 512); a[8 * h + 4 * c + 2] = lds32(o - 32); a[8 * h + 4 * c + 3] = lds32(o + 480);
    }
  }
}
template <int GI, int NR>
__device__ __forceinline__ void conv_group(float (&dA)[NR], float (&dB)[NR], uint32_t (&cur)[16], uint32_t (&nxt)[16], uint32_t kp, uint64_t dU) {
  wg_fence();
#pragma unroll
  for (int h = 0; h < 2; h++) {
    const uint64_t db = dU - (uint64_t)(2 * ((2 * GI + h) & 7));
    if constexpr (GI == 0) {
      if (h == 0) {
        wg_cv128_init<0>(dA, cur[0], cur[1], cur[2], cur[3], db);
        wg_cv128_init<0>(dB, cur[4], cur[5], cur[6], cur[7], db + (U_BYTES >> 4));
        continue;
      }
    }
    conv_mma<NR>(dA, cur + 8 * h, db);
    conv_mma<NR>(dB, cur + 8 * h + 4, db + (U_BYTES >> 4));
  }
  wg_commit();
  if constexpr (GI < 15) { wg_wait<1>(); conv_load<GI + 1>(nxt, kp); }
}
template <int PH, int NR>
__device__ __forceinline__ void conv_phase(float (&dA)[NR], float (&dB)[NR], uint32_t (&a0)[16], uint32_t (&a1)[16], uint32_t kp, uint64_t dU) {
  conv_group<4 * PH, NR>(dA, dB, a0, a1, kp, dU);
  conv_group<4 * PH + 1, NR>(dA, dB, a1, a0, kp, dU);
  conv_group<4 * PH + 2, NR>(dA, dB, a0, a1, kp, dU);
  conv_group<4 * PH + 3, NR>(dA, dB, a1, a0, kp, dU);
  wg_wait<0>();
  reg_fence(dA); reg_fence(dB);
}
template <int NR>
__device__ __forceinline__ void upper_copy(float (&dst)[NR - 16], const float (&src)[NR]) {
#pragma unroll
  for (int i = 0; i < NR - 16; i++) asm volatile("mov.b32 %0, %1;" : "=f"(dst[i]) : "f"(src[i + 16]));
}
__device__ __forceinline__ void conv2(uint32_t sb, int wg, int w, int lane, uint32_t bar_st, bool wait_st) {
  const int g = lane >> 2, q = lane & 3;
  float dA[64], dB[64];
  uint32_t a0[16], a1[16];
  const uint32_t kp = sb + T_KP + 2 * wg * KP_BYTES + 4 * (16 + 256 * (w >> 1) + 8 * (w & 1) + g - 2 * q);
  const uint64_t dU = mk_desc(sb + T_U + 2 * wg * U_BYTES + 256, 16, 256, 3);
  conv_load<0>(a0, kp);
  conv_phase<0, 64>(dA, dB, a0, a1, kp, dU);
  {
    float eA[48], eB[48];
    upper_copy<64>(eA, dA); upper_copy<64>(eB, dB);
    conv_phase<1, 48>(eA, eB, a0, a1, kp, dU);
    float fA[32], fB[32];
    upper_copy<48>(fA, eA); upper_copy<48>(fB, eB);
    conv_phase<2, 32>(fA, fB, a0, a1, kp, dU);
    float gA[16], gB[16];
    upper_copy<32>(gA, fA); upper_copy<32>(gB, fB);
    conv_phase<3, 16>(gA, gB, a0, a1, kp, dU);
#pragma unroll
    for (int i = 0; i < 16; i++) {
      dA[16 + i] = eA[i]; dA[32 + i] = fA[i]; dA[48 + i] = gA[i];
      dB[16 + i] = eB[i]; dB[32 + i] = fB[i]; dB[48 + i] = gB[i];
    }
  }
  if (wait_st) mbar_wait(bar_st, 0);
  const uint32_t y = sb + T_Y + (2 * (w >> 1) + wg) * Y_BYTES + 4 * (256 * (w >> 1) + 32 * q + g);
#pragma unroll
  for (int m = 0; m < 16; m++)
#pragma unroll
    for (int e = 0; e < 2; e++) {
      const float zA = m ? dA[4 * m + e] + dA[4 * m - 2 + e] : dA[e];
      const float zB = m ? dB[4 * m + e] + dB[4 * m - 2 + e] : dB[e];
      sts32(y + 4 * (128 * m + (((2 * e + (w & 1)) ^ q) << 3)), pack_bf16(zA, zB));
    }
}
__device__ __forceinline__ void sum_y(uint32_t sb, int t, float (&f)[8][4]) {
  const uint32_t o = sb + T_Y + 32 * (t ^ ((t >> 2) & 3));
#pragma unroll
  for (int wgi = 0; wgi < 2; wgi++) {
    uint4 a = lds128(o + wgi * Y_BYTES), b = lds128(o + wgi * Y_BYTES + 16);
    uint32_t v[8] = {a.x, a.y, a.z, a.w, b.x, b.y, b.z, b.w};
#pragma unroll
    for (int i = 0; i < 8; i++) { f[i][2 * wgi] = bf_lo(v[i]); f[i][2 * wgi + 1] = bf_hi(v[i]); }
    if (t >= 32) {
      a = lds128(o + (2 + wgi) * Y_BYTES); b = lds128(o + (2 + wgi) * Y_BYTES + 16);
      uint32_t u[8] = {a.x, a.y, a.z, a.w, b.x, b.y, b.z, b.w};
#pragma unroll
      for (int i = 0; i < 8; i++) { f[i][2 * wgi] += bf_lo(u[i]); f[i][2 * wgi + 1] += bf_hi(u[i]); }
    }
  }
}

__global__ void __cluster_dims__(2, 1, 1) __launch_bounds__(384, 1) fused_kernel(const __grid_constant__ Params p) {
  extern __shared__ __align__(1024) unsigned char smem_raw[];
  const uint32_t sb = smem_u32(smem_raw);
  const uint32_t bar = sb + SM_BAR;
  const int j = blockIdx.x & 1, pair = blockIdx.x >> 1, mt = pair & 15, sp = pair >> 4;
  const bool spare = pair >= 64;
  const int wg = __shfl_sync(0xffffffffu, threadIdx.x >> 7, 0);
  if (threadIdx.x == 256) {
    for (int i = 0; i < NST; i++) { mbar_init(bar + B_FULL + 8 * i, 1); mbar_init(bar + B_EMPTY + 8 * i, 8); }
    for (int i = 0; i < 9; i++) mbar_init(bar + B_XN + 8 * i, 1);
    for (int i = 0; i < 2; i++) { mbar_init(bar + B_HF + 8 * i, 1); mbar_init(bar + B_HE + 8 * i, 1); }
    mbar_init(bar + B_CV, 1); mbar_init(bar + B_ST, 1); mbar_init(bar + B_PT, 1); mbar_init(bar + B_SG, 2);
    mbar_expect_tx(bar + B_HF, 8192); mbar_expect_tx(bar + B_HF + 8, 8192);
    asm volatile("fence.mbarrier_init.release.cluster;" ::: "memory");
  }
  __syncthreads();
  asm volatile("barrier.cluster.arrive.relaxed.aligned;" ::: "memory");

  if (wg == 2) {
    const int t = threadIdx.x & 127, w = t >> 5, lane = t & 31;
    const int f0 = sp * 1152;
    const bool el = elect_one();
    if (!spare) {
      const int row0 = mt * 128 + (2 * sp + j) * 16;
      uint32_t v[4][9];
#pragma unroll
      for (int r = 0; r < 4; r++) {
        const uint32_t* xr = (const uint32_t*)(p.x + (size_t)(row0 + 4 * w + r) * D_);
#pragma unroll
        for (int i = 0; i < 9; i++) v[r][i] = __ldg(xr + lane + 32 * i);
      }
      if (w == 0 && el) {
        for (int u = 0; u < NST; u++) {
          const uint32_t dst = sb + SM_RING + u * SLOT, fb = bar + B_FULL + 8 * u;
          mbar_expect_tx(fb, 8192);
          tma_2d(dst, &p.gate, f0 + 64 * j, 32 * u, fb);
          tma_2d(dst + 4096, &p.up, f0 + 64 * j, 32 * u, fb);
        }
      }
      uint32_t* s_ln = (uint32_t*)(smem_raw + PR_LN);
#pragma unroll
      for (int r = 0; r < 4; r++) {
        float s = 0.f;
#pragma unroll
        for (int i = 0; i < 9; i++) s += bf_lo(v[r][i]) + bf_hi(v[r][i]);
#pragma unroll
        for (int o = 16; o; o >>= 1) s += __shfl_xor_sync(0xffffffffu, s, o);
        const float mean = s * (1.0f / D_);
        float q = 0.f;
#pragma unroll
        for (int i = 0; i < 9; i++) { float a = bf_lo(v[r][i]) - mean, b = bf_hi(v[r][i]) - mean; q = fmaf(a, a, q); q = fmaf(b, b, q); }
#pragma unroll
        for (int o = 16; o; o >>= 1) q += __shfl_xor_sync(0xffffffffu, q, o);
        const float mb = bf_round(mean);
        const float rinv = 1.0f / bf_round(sqrtf(bf_round(bf_round(q * (1.0f / D_)) + 1e-5f)));
        uint32_t* xo = (uint32_t*)(g_xn + (size_t)(row0 + 4 * w + r) * D_);
#pragma unroll
        for (int i = 0; i < 9; i++) {
          const uint32_t n = pack_bf16(bf_round(bf_lo(v[r][i]) - mb) * rinv, bf_round(bf_hi(v[r][i]) - mb) * rinv);
          xo[lane + 32 * i] = n;
          s_ln[(4 * w + r) * 289 + lane + 32 * i] = n;
        }
      }
      __syncwarp();
      if (lane == 0) { fence_async_all(); cnt_add(C_LN + mt); }
      named_bar(5, 128);
      {
        const int blk = row0 >> 4, sw = (blk >> 2) & 1;
        for (int cp = t; cp < 288; cp += 128) {
          uint32_t lo[8], hi[8];
#pragma unroll
          for (int r = 0; r < 8; r++) {
            const uint32_t a = s_ln[(2 * r) * 289 + cp], b = s_ln[(2 * r + 1) * 289 + cp];
            lo[r] = __byte_perm(a, b, 0x5410); hi[r] = __byte_perm(a, b, 0x7632);
          }
          uint4* d0 = (uint4*)(g_u + (size_t)(2 * cp) * U_LEN + 128 + row0);
          uint4* d1 = (uint4*)(g_u + (size_t)(2 * cp + 1) * U_LEN + 128 + row0);
          d0[sw] = make_uint4(lo[0], lo[1], lo[2], lo[3]); d0[sw ^ 1] = make_uint4(lo[4], lo[5], lo[6], lo[7]);
          d1[sw] = make_uint4(hi[0], hi[1], hi[2], hi[3]); d1[sw ^ 1] = make_uint4(hi[4], hi[5], hi[6], hi[7]);
        }
        __syncwarp();
        if (lane == 0) { fence_async_all(); cnt_add(C_U); }
      }
      named_bar(5, 128);
    }
    asm volatile("barrier.cluster.wait.aligned;" ::: "memory");
    asm volatile("setmaxnreg.dec.sync.aligned.u32 24;");
    if (w == 0) {
      if (!spare) {
        cnt_wait(C_LN + mt, 32);
        fence_async_all();
        if (el) {
          for (int kb = 0; kb < 5; kb++) {
            mbar_expect_tx(bar + B_XN + 8 * kb, 16384);
            tma_2d(sb + SM_XN + kb * 16384, &p.xn, kb * 64, mt * 128, bar + B_XN + 8 * kb);
          }
        }
        named_bar(4, 288);
        if (el) {
          for (int kb = 5; kb < 9; kb++) {
            mbar_expect_tx(bar + B_XN + 8 * kb, 16384);
            tma_2d(sb + SM_XN + kb * 16384, &p.xn, kb * 64, mt * 128, bar + B_XN + 8 * kb);
          }
        }
        uint32_t slot = 0, ph = 0;
        for (int c = 0; c <= 9; c++) {
          const int fc = f0 + c * 128;
          if (c < 9) {
            for (int u = c ? 0 : NST; u < 18; u++) {
              mbar_wait(bar + B_EMPTY + 8 * slot, ph);
              if (el) {
                const uint32_t dst = sb + SM_RING + slot * SLOT, fb = bar + B_FULL + 8 * slot;
                mbar_expect_tx(fb, 8192);
                tma_2d(dst, &p.gate, fc + 64 * j, 32 * u, fb);
                tma_2d(dst + 4096, &p.up, fc + 64 * j, 32 * u, fb);
              }
              if (++slot == NST) { slot = 0; ph ^= 1; }
            }
          }
          const int fp = fc - 128 + 64 * (1 - j), fo = fc + 64 * j;
#pragma unroll
          for (int i = 0; i < 8; i++) {
            const bool isP = (i < 3 || i == 4);
            const int u = isP ? (i < 3 ? i : 3) : (i == 3 ? 0 : i - 4);
            if (isP ? (c == 0) : (c == 9)) continue;
            mbar_wait(bar + B_EMPTY + 8 * slot, ph);
            if (el) {
              const uint32_t dst = sb + SM_RING + slot * SLOT, fb = bar + B_FULL + 8 * slot;
              mbar_expect_tx(fb, 9216);
              if (isP) {
                tma_5d(dst, &p.dp, 0, 0, (fp >> 3) + 4 * (u >> 1), 2 * (u & 1), 4 * j, fb);
                tma_4d(dst + 8192, &p.dp5, 512 + 32 * j, 0, (fp >> 3) + 4 * (u >> 1), 2 * (u & 1), fb);
              } else {
                tma_3d(dst, &p.dn, 0, fo + 16 * u, 4 * j, fb);
                tma_2d(dst + 8192, &p.dn5, 512 + 32 * j, fo + 16 * u, fb);
              }
            }
            if (++slot == NST) { slot = 0; ph ^= 1; }
          }
        }
        const int ch0 = blockIdx.x * 4;
        cnt_wait(C_U, 512);
        fence_async_all();
        if (el) {
          mbar_expect_tx(bar + B_CV, 4 * U_BYTES + 4 * KP_BYTES);
          bulk_g2s(sb + T_KP, g_kp + (size_t)ch0 * KP_LEN, 4 * KP_BYTES, bar + B_CV);
          bulk_g2s(sb + T_U, g_u + (size_t)ch0 * U_LEN, 4 * U_BYTES, bar + B_CV);
        }
        mbar_wait(bar + B_SG, 0);
        if (el) {
#pragma unroll
          for (int h = 0; h < 2; h++) {
#pragma unroll
            for (int i = 0; i < 4; i++) tma_store_3d(&p.part, sb + i * 16384 + h * 8192, mt * 128 + h * 64, 256 * j + 64 * i, sp);
            tma_store_3d(&p.part2, sb + 65536 + h * 8192, 32 * j, mt * 128 + h * 64, sp);
          }
          asm volatile("cp.async.bulk.commit_group;" ::: "memory");
          asm volatile("cp.async.bulk.wait_group 0;" ::: "memory");
          fence_async_all();
          cnt_add(C_PART + j);
          mbar_arrive(bar + B_ST);
        }
        __syncwarp();
        cnt_wait(C_PART + (ch0 >> 8), 64);
        fence_async_all();
        if (el) {
          mbar_expect_tx(bar + B_PT, 65536);
#pragma unroll
          for (int s = 0; s < 4; s++) bulk_g2s(sb + T_PART + s * 16384, g_part + ((size_t)s * 512 + ch0) * L_, 16384, bar + B_PT);
        }
        cnt_wait(C_PART + ((ch0 >> 8) ^ 1), 64);
        cnt_wait(C_Y5, 128);
      } else {
        named_bar(4, 288);
        cnt_wait(C_U, 512);
        fence_async_all();
        for (int grp = 0; grp < 4; grp++) {
          const int ch0 = 512 + ((int)blockIdx.x - 128) * 16 + grp * 4;
          if (grp) mbar_wait(bar + B_SG, (grp - 1) & 1);
          if (el) {
            mbar_expect_tx(bar + B_CV, 4 * U_BYTES + 4 * KP_BYTES);
            bulk_g2s(sb + T_KP, g_kp + (size_t)ch0 * KP_LEN, 4 * KP_BYTES, bar + B_CV);
            bulk_g2s(sb + T_U, g_u + (size_t)ch0 * U_LEN, 4 * U_BYTES, bar + B_CV);
          }
        }
      }
      if (el) {
        const unsigned int old = atomicAdd(g_cnt + C_DONE * 32, 1u);
        if (old == gridDim.x - 1) { for (int i = 0; i <= C_DONE; i++) g_cnt[i * 32] = 0u; }
      }
    }
    if (!spare) {
      named_bar(6, 128);
      const size_t ro = (size_t)(mt * 128 + (2 * sp + j) * 16 + (t >> 3));
      const int co = 8 * (t & 7);
      uint4 v = __ldcg((const uint4*)(g_y5 + ro * 64 + co));
      float f[8] = {bf_lo(v.x), bf_hi(v.x), bf_lo(v.y), bf_hi(v.y), bf_lo(v.z), bf_hi(v.z), bf_lo(v.w), bf_hi(v.w)};
#pragma unroll
      for (int s = 0; s < 4; s++) {
        v = __ldcg((const uint4*)(g_part2 + ((size_t)s * L_ + ro) * 64 + co));
        f[0] += bf_lo(v.x); f[1] += bf_hi(v.x); f[2] += bf_lo(v.y); f[3] += bf_hi(v.y);
        f[4] += bf_lo(v.z); f[5] += bf_hi(v.z); f[6] += bf_lo(v.w); f[7] += bf_hi(v.w);
      }
      *(uint4*)(p.out + ro * D_ + 512 + co) = make_uint4(pack_bf16(f[0], f[1]), pack_bf16(f[2], f[3]), pack_bf16(f[4], f[5]), pack_bf16(f[6], f[7]));
    }
  } else {
    const int t = threadIdx.x & 127, w = t >> 5, lane = t & 31;
    PROF_T(0);
    if (!spare) kgen4(p, smem_raw, blockIdx.x * 4, threadIdx.x);
    else {
#pragma unroll 1
      for (int grp = 0; grp < 4; grp++) kgen4(p, smem_raw, 512 + ((int)blockIdx.x - 128) * 16 + grp * 4, threadIdx.x);
    }
    named_arrive(4, 288);
    PROF_T(41);
    asm volatile("barrier.cluster.wait.aligned;" ::: "memory");
    asm volatile("setmaxnreg.inc.sync.aligned.u32 240;");
    if (!spare) {
      const bool leader = (t == 0);
      float O1[128], O2[16];
      if (sp == 0) {
        const uint32_t* x0 = (const uint32_t*)(p.x + (size_t)(mt * 128 + wg * 64 + 16 * w + (lane >> 2)) * D_) + (lane & 3);
#pragma unroll
        for (int g = 0; g < 32; g++) {
          const uint32_t a = __ldg(x0 + 128 * j + 4 * g), b = __ldg(x0 + 8 * 288 + 128 * j + 4 * g);
          O1[4 * g] = bf_lo(a); O1[4 * g + 1] = bf_hi(a); O1[4 * g + 2] = bf_lo(b); O1[4 * g + 3] = bf_hi(b);
        }
#pragma unroll
        for (int g = 0; g < 4; g++) {
          const uint32_t a = __ldg(x0 + 256 + 16 * j + 4 * g), b = __ldg(x0 + 8 * 288 + 256 + 16 * j + 4 * g);
          O2[4 * g] = bf_lo(a); O2[4 * g + 1] = bf_hi(a); O2[4 * g + 2] = bf_lo(b); O2[4 * g + 3] = bf_hi(b);
        }
      } else {
#pragma unroll
        for (int i = 0; i < 128; i++) O1[i] = 0.f;
#pragma unroll
        for (int i = 0; i < 16; i++) O2[i] = 0.f;
      }
      reg_fence(O1); reg_fence(O2);
      uint32_t slot = 0, ph = 0, prev = 0;
      const uint32_t hin = sb + SM_HIN + wg * 8192;
      const uint32_t r_hin = mapa(hin + (16 * w + (lane >> 2)) * 128 + (((lane & 3) ^ (lane >> 2)) << 4), j ^ 1);
      const uint32_t r_hf = mapa(bar + B_HF + 8 * wg, j ^ 1), r_he = mapa(bar + B_HE + 8 * wg, j ^ 1);
      const uint64_t dA0 = mk_desc(sb + SM_XN + wg * 8192, 16, 1024, 1);
      const uint64_t dH0 = mk_desc(hin, 16, 1024, 1);
      const uint64_t dG0 = mk_desc(sb + SM_RING, 4096, 1024, 1);
      const uint64_t dW0 = mk_desc(sb + SM_RING, 2048, 1024, 1);
      const uint64_t dX0 = mk_desc(sb + SM_RING + 8192, 512, 512, 2);
      auto adv = [&]() { prev = slot; if (++slot == NST) { slot = 0; ph ^= 1; } };
      auto release = [&](uint32_t s) { if (lane == 0) mbar_arrive(bar + B_EMPTY + 8 * s); };
      auto acquire = [&]() -> bool {
        if (__all_sync(0xffffffffu, mbar_test(bar + B_FULL + 8 * slot, ph))) return true;
        wg_wait<0>();
        release(prev);
        mbar_wait(bar + B_FULL + 8 * slot, ph);
        return false;
      };
      auto peer_begin = [&](int cp) {
        mbar_wait(bar + B_HF + 8 * wg, cp & 1);
        if (leader && cp < 8) mbar_expect_tx(bar + B_HF + 8 * wg, 8192);
        fence_async_smem();
      };
      auto peer_unit = [&](int u) {
        wg_fence();
        wg_ss256<1>(O1, dH0 + 2 * u, dW0 + (uint64_t)(slot * (SLOT >> 4)));
        wg_ss32<1>(O2, dH0 + 2 * u, dX0 + (uint64_t)(slot * (SLOT >> 4)));
        wg_commit();
      };
      auto chunk = [&](auto first_c, const int c) {
        constexpr bool FIRST = decltype(first_c)::value;
        float S[64];
        {
          if (FIRST) mbar_wait(bar + B_XN, 0);
          mbar_wait(bar + B_FULL + 8 * slot, ph);
          if (FIRST) PROF_T(42);
          const uint64_t db = dG0 + (uint64_t)(slot * (SLOT >> 4));
          wg_fence();
          wg_ss128_init<1>(S, dA0, db);
          wg_ss128<1>(S, dA0 + 2, db + 128);
          wg_commit();
          adv();
        }
#pragma unroll 1
        for (int u = 1; u < 18; u++) {
          if (FIRST && !(u & 1)) mbar_wait(bar + B_XN + 8 * (u >> 1), 0);
          const bool rel = acquire();
          const uint64_t da = dA0 + (uint64_t)((u >> 1) * 1024 + (u & 1) * 4);
          const uint64_t db = dG0 + (uint64_t)(slot * (SLOT >> 4));
          wg_fence();
          wg_ss128<1>(S, da, db);
          wg_ss128<1>(S, da + 2, db + 128);
          wg_commit();
          wg_wait<1>();
          if (rel) release(prev);
          adv();
        }
        uint32_t H[16];
        if constexpr (!FIRST) peer_begin(c - 1);
        else { wg_wait<0>(); release(prev); }
        auto P = [&](int u) { if constexpr (!FIRST) { const bool rel = acquire(); peer_unit(u); wg_wait<1>(); if (rel) release(prev); adv(); } };
        auto E = [&](int u) {
#pragma unroll
          for (int i = 8 * u; i < 8 * u + 8; i++) asm volatile("" : "+f"(S[i]), "+f"(S[32 + i])::"memory");
#pragma unroll
          for (int g = 2 * u; g < 2 * u + 2; g++) {
            H[2 * g] = pack_bf16(geglu(S[4 * g], S[32 + 4 * g]), geglu(S[4 * g + 1], S[33 + 4 * g]));
            H[2 * g + 1] = pack_bf16(geglu(S[4 * g + 2], S[34 + 4 * g]), geglu(S[4 * g + 3], S[35 + 4 * g]));
          }
#pragma unroll
          for (int i = 4 * u; i < 4 * u + 4; i++) asm volatile("" : "+r"(H[i])::"memory");
        };
        auto O = [&](int u) {
          bool rel;
          if (FIRST && u == 0) { mbar_wait(bar + B_FULL + 8 * slot, ph); rel = false; } else rel = acquire();
          wg_fence();
          wg_rs256<1>(O1, H[4 * u], H[4 * u + 1], H[4 * u + 2], H[4 * u + 3], dW0 + (uint64_t)(slot * (SLOT >> 4)));
          wg_rs32<1>(O2, H[4 * u], H[4 * u + 1], H[4 * u + 2], H[4 * u + 3], dX0 + (uint64_t)(slot * (SLOT >> 4)));
          wg_commit();
          if (u == 3) {
            mbar_wait(bar + B_HE + 8 * wg, (c & 1) ^ 1);
            st_async_v4(r_hin, H[0], H[2], H[4], H[6], r_hf);
            st_async_v4(r_hin ^ 64, H[8], H[10], H[12], H[14], r_hf);
            st_async_v4(r_hin + 1024, H[1], H[3], H[5], H[7], r_hf);
            st_async_v4((r_hin ^ 64) + 1024, H[9], H[11], H[13], H[15], r_hf);
            named_bar(3, 256);
          }
          wg_wait<1>();
          if (rel) release(prev);
          if (u == 1) { if constexpr (!FIRST) { if (leader) mbar_arrive_remote(r_he); } }
          if (u == 3) { wg_wait<0>(); release(slot); }
          adv();
        };
        P(0); E(0); P(1); E(1); P(2); O(0); E(2); P(3); O(1); E(3); O(2); O(3);
        PROF_T(4 + 4 * c);
      };
      chunk(std::true_type{}, 0);
#pragma unroll 1
      for (int c = 1; c < 9; c++) chunk(std::false_type{}, c);
      peer_begin(8);
#pragma unroll
      for (int u = 0; u < 4; u++) { mbar_wait(bar + B_FULL + 8 * slot, ph); peer_unit(u); adv(); }
      wg_wait<0>();
      reg_fence(O1); reg_fence(O2);
      PROF_T(40);
      {
        const uint32_t stg = sb + SM_XN + wg * 8192;
        const int mi = lane >> 3, li = lane & 7;
        const uint32_t lo_t = (uint32_t)((8 * (mi >> 1) + li) * 128 + (((2 * w + (mi & 1)) ^ li) << 4));
#pragma unroll
        for (int g = 0; g < 32; g += 2)
          stmatrix_x4_t(stg + (g >> 3) * 16384 + (g & 7) * 1024 + lo_t, pack_bf16(O1[4 * g], O1[4 * g + 1]), pack_bf16(O1[4 * g + 2], O1[4 * g + 3]),
                        pack_bf16(O1[4 * g + 4], O1[4 * g + 5]), pack_bf16(O1[4 * g + 6], O1[4 * g + 7]));
        const int row = 16 * w + 8 * (mi & 1) + li;
#pragma unroll
        for (int g = 0; g < 4; g += 2)
          stmatrix_x4(stg + 65536 + row * 64 + (((g + (mi >> 1)) ^ ((row >> 1) & 3)) << 4), pack_bf16(O2[4 * g], O2[4 * g + 1]), pack_bf16(O2[4 * g + 2], O2[4 * g + 3]),
                      pack_bf16(O2[4 * g + 4], O2[4 * g + 5]), pack_bf16(O2[4 * g + 6], O2[4 * g + 7]));
        fence_async_smem();
        named_bar(1 + wg, 128);
        if (leader) mbar_arrive(bar + B_SG);
      }
      mbar_wait(bar + B_CV, 0);
      PROF_T(43);
      conv2(sb, wg, w, lane, bar + B_ST, true);
      PROF_T(44);
      named_bar(3, 256);
      float f[8][4];
      sum_y(sb, threadIdx.x, f);
      mbar_wait(bar + B_PT, 0);
      PROF_T(45);
#pragma unroll
      for (int s = 0; s < 4; s++)
#pragma unroll
        for (int c = 0; c < 4; c++) {
          const uint4 v = lds128(sb + T_PART + s * 16384 + c * 4096 + 16 * threadIdx.x);
          f[0][c] += bf_lo(v.x); f[1][c] += bf_hi(v.x); f[2][c] += bf_lo(v.y); f[3][c] += bf_hi(v.y);
          f[4][c] += bf_lo(v.z); f[5][c] += bf_hi(v.z); f[6][c] += bf_lo(v.w); f[7][c] += bf_hi(v.w);
        }
      __nv_bfloat16* o = p.out + (size_t)(8 * threadIdx.x) * D_ + blockIdx.x * 4;
#pragma unroll
      for (int i = 0; i < 8; i++) *(uint2*)(o + i * D_) = make_uint2(pack_bf16(f[i][0], f[i][1]), pack_bf16(f[i][2], f[i][3]));
      PROF_T(46);
    } else {
#pragma unroll 1
      for (int grp = 0; grp < 4; grp++) {
        mbar_wait(bar + B_CV, grp & 1);
        conv2(sb, wg, w, lane, 0, false);
        named_bar(3, 256);
        if (t == 0) mbar_arrive(bar + B_SG);
        float f[8][4];
        sum_y(sb, threadIdx.x, f);
        __nv_bfloat16* o = g_y5 + (size_t)(8 * threadIdx.x) * 64 + ((int)blockIdx.x - 128) * 16 + grp * 4;
#pragma unroll
        for (int i = 0; i < 8; i++) *(uint2*)(o + i * 64) = make_uint2(pack_bf16(f[i][0], f[i][1]), pack_bf16(f[i][2], f[i][3]));
        __syncwarp();
        if (lane == 0) cnt_add(C_Y5);
        named_bar(3, 256);
      }
      PROF_T(46);
    }
  }
}

typedef CUresult (*PFN_enc)(CUtensorMap*, CUtensorMapDataType, cuuint32_t, void*, const cuuint64_t*, const cuuint64_t*, const cuuint32_t*,
                            const cuuint32_t*, CUtensorMapInterleave, CUtensorMapSwizzle, CUtensorMapL2promotion, CUtensorMapFloatOOBfill);

void enc(PFN_enc fn, CUtensorMap* m, void* ptr, int rank, const cuuint64_t* dims, const cuuint64_t* strides, const cuuint32_t* box, CUtensorMapSwizzle sw) {
  cuuint32_t es[5] = {1, 1, 1, 1, 1};
  fn(m, CU_TENSOR_MAP_DATA_TYPE_BFLOAT16, rank, ptr, dims, strides, box, es, CU_TENSOR_MAP_INTERLEAVE_NONE, sw,
     CU_TENSOR_MAP_L2_PROMOTION_L2_128B, CU_TENSOR_MAP_FLOAT_OOB_FILL_NONE);
}

}

extern "C" void kernel_launch(void* const* d_in, const int* in_sizes, int n_in, void* d_out, int out_size) {
  static Params pr;
  static void* key[3] = {nullptr, nullptr, nullptr};
  if (key[0] != d_in[8] || key[1] != d_in[9] || key[2] != d_in[10]) {
    key[0] = d_in[8]; key[1] = d_in[9]; key[2] = d_in[10];
    void* fnp = nullptr; cudaDriverEntryPointQueryResult st;
    cudaGetDriverEntryPoint("cuTensorMapEncodeTiled", &fnp, cudaEnableDefault, &st);
    PFN_enc fn = (PFN_enc)fnp;
    void *p_xn, *p_part, *p_part2;
    cudaGetSymbolAddress(&p_xn, g_xn); cudaGetSymbolAddress(&p_part, g_part); cudaGetSymbolAddress(&p_part2, g_part2);
    { cuuint64_t d[2] = {D_, L_}, s[1] = {D_ * 2}; cuuint32_t b[2] = {64, 128}; enc(fn, &pr.xn, p_xn, 2, d, s, b, CU_TENSOR_MAP_SWIZZLE_128B); }
    { cuuint64_t d[2] = {F_, D_}, s[1] = {F_ * 2}; cuuint32_t b[2] = {64, 32};
      enc(fn, &pr.gate, d_in[8], 2, d, s, b, CU_TENSOR_MAP_SWIZZLE_128B); enc(fn, &pr.up, d_in[9], 2, d, s, b, CU_TENSOR_MAP_SWIZZLE_128B); }
    { void* wd = d_in[10];
      { cuuint64_t d[3] = {64, F_, 9}, s[2] = {D_ * 2, 128}; cuuint32_t b[3] = {64, 16, 4}; enc(fn, &pr.dn, wd, 3, d, s, b, CU_TENSOR_MAP_SWIZZLE_128B); }
      { cuuint64_t d[2] = {D_, F_}, s[1] = {D_ * 2}; cuuint32_t b[2] = {32, 16}; enc(fn, &pr.dn5, wd, 2, d, s, b, CU_TENSOR_MAP_SWIZZLE_64B); }
      { cuuint64_t d[5] = {64, 2, F_ / 8, 4, 9}, s[4] = {D_ * 2, D_ * 16, D_ * 4, 128}; cuuint32_t b[5] = {64, 2, 4, 2, 4};
        enc(fn, &pr.dp, wd, 5, d, s, b, CU_TENSOR_MAP_SWIZZLE_128B); }
      { cuuint64_t d[4] = {D_, 2, F_ / 8, 4}, s[3] = {D_ * 2, D_ * 16, D_ * 4}; cuuint32_t b[4] = {32, 2, 4, 2};
        enc(fn, &pr.dp5, wd, 4, d, s, b, CU_TENSOR_MAP_SWIZZLE_64B); }
    }
    { cuuint64_t d[3] = {L_, 512, 4}, s[2] = {L_ * 2, (cuuint64_t)L_ * 512 * 2}; cuuint32_t b[3] = {64, 64, 1}; enc(fn, &pr.part, p_part, 3, d, s, b, CU_TENSOR_MAP_SWIZZLE_128B); }
    { cuuint64_t d[3] = {64, L_, 4}, s[2] = {128, (cuuint64_t)L_ * 128}; cuuint32_t b[3] = {32, 64, 1}; enc(fn, &pr.part2, p_part2, 3, d, s, b, CU_TENSOR_MAP_SWIZZLE_64B); }
    cudaFuncSetAttribute(fused_kernel, cudaFuncAttributeMaxDynamicSharedMemorySize, SMEM_BYTES);
  }
  const __nv_bfloat16* const* in = (const __nv_bfloat16* const*)d_in;
  pr.x = in[0]; pr.logA = in[1]; pr.Aim = in[2]; pr.Cre = in[3]; pr.Cim = in[4]; pr.logdt = in[5]; pr.Dsk = in[6];
  pr.out = (__nv_bfloat16*)d_out;
  fused_kernel<<<132, 384, SMEM_BYTES>>>(pr);
}
```

```cpp
#include <cuda_runtime.h>
#include <cuda_bf16.h>
#include <cuda.h>
#include <stdint.h>
#include <stdio.h>
#include <type_traits>
#define CV_BASEOFF 0

namespace {

constexpr int L_ = 2048, D_ = 576, F_ = 4608, NM_ = 128;
constexpr int KP_LEN = 2080;
constexpr int U_LEN = 2176;

__device__ __align__(1024) __nv_bfloat16 g_xn[L_ * D_];
__device__ __align__(1024) __nv_bfloat16 g_u[D_ * U_LEN];
__device__ __align__(1024) uint32_t g_kp[D_ * KP_LEN];
__device__ __align__(1024) unsigned char g_part[32 * 16 * 18432];
__device__ __align__(1024) __nv_bfloat16 g_y[D_ * L_];
__device__ __align__(1024) unsigned int g_cnt[64 * 32];
constexpr int C_LN = 0, C_PART = 16, C_U = 48, C_Y = 49, C_Y5 = 51, C_DONE = 52;

#define PROF_T(idx) do {} while (0)
#define PROF_ACC(idx) do {} while (0)
__device__ __forceinline__ uint32_t smem_u32(const void* p) { return (uint32_t)__cvta_generic_to_shared(p); }
__device__ __forceinline__ void mbar_init(uint32_t bar, uint32_t cnt) { asm volatile("mbarrier.init.shared::cta.b64 [%0], %1;" ::"r"(bar), "r"(cnt)); }
__device__ __forceinline__ void mbar_expect_tx(uint32_t bar, uint32_t bytes) { asm volatile("mbarrier.arrive.expect_tx.shared::cta.b64 _, [%0], %1;" ::"r"(bar), "r"(bytes) : "memory"); }
__device__ __forceinline__ void mbar_arrive(uint32_t bar) { asm volatile("mbarrier.arrive.shared::cta.b64 _, [%0];" ::"r"(bar) : "memory"); }
__device__ __forceinline__ void mbar_arrive_remote(uint32_t bar) { asm volatile("mbarrier.arrive.shared::cluster.b64 _, [%0];" ::"r"(bar) : "memory"); }
__device__ __forceinline__ bool mbar_try_wait(uint32_t bar, uint32_t parity) {
  uint32_t ok;
  asm volatile("{\n.reg .pred p;\nmbarrier.try_wait.parity.shared::cta.b64 p, [%1], %2;\nselp.u32 %0, 1, 0, p;\n}" : "=r"(ok) : "r"(bar), "r"(parity) : "memory");
  return ok;
}
__device__ __forceinline__ bool mbar_test(uint32_t bar, uint32_t parity) {
  uint32_t ok;
  asm volatile("{\n.reg .pred p;\nmbarrier.test_wait.parity.shared::cta.b64 p, [%1], %2;\nselp.u32 %0, 1, 0, p;\n}" : "=r"(ok) : "r"(bar), "r"(parity) : "memory");
  return ok;
}
__device__ __forceinline__ void mbar_wait(uint32_t bar, uint32_t parity) {
  asm volatile("{\n.reg .pred p, q;\n.reg .u32 n;\nmov.u32 n, 0;\nLW:\nmbarrier.try_wait.parity.shared::cta.b64 p, [%0], %1;\n"
               "add.u32 n, n, 1;\nsetp.lt.and.u32 q, n, 65536, !p;\n@q bra LW;\n}" ::"r"(bar), "r"(parity) : "memory");
}
__device__ __forceinline__ bool elect_one() {
  uint32_t ok;
  asm volatile("{\n.reg .pred p;\nelect.sync _|p, 0xffffffff;\nselp.u32 %0, 1, 0, p;\n}" : "=r"(ok));
  return ok;
}
__device__ __forceinline__ void tma_2d(uint32_t dst, const CUtensorMap* map, int c0, int c1, uint32_t bar) {
  asm volatile("cp.async.bulk.tensor.2d.shared::cluster.global.mbarrier::complete_tx::bytes [%0], [%1, {%3, %4}], [%2];"
               ::"r"(dst), "l"(map), "r"(bar), "r"(c0), "r"(c1) : "memory");
}
__device__ __forceinline__ void tma_3d(uint32_t dst, const CUtensorMap* map, int c0, int c1, int c2, uint32_t bar) {
  asm volatile("cp.async.bulk.tensor.3d.shared::cluster.global.mbarrier::complete_tx::bytes [%0], [%1, {%3, %4, %5}], [%2];"
               ::"r"(dst), "l"(map), "r"(bar), "r"(c0), "r"(c1), "r"(c2) : "memory");
}
__device__ __forceinline__ void tma_4d(uint32_t dst, const CUtensorMap* map, int c0, int c1, int c2, int c3, uint32_t bar) {
  asm volatile("cp.async.bulk.tensor.4d.shared::cluster.global.mbarrier::complete_tx::bytes [%0], [%1, {%3, %4, %5, %6}], [%2];"
               ::"r"(dst), "l"(map), "r"(bar), "r"(c0), "r"(c1), "r"(c2), "r"(c3) : "memory");
}
__device__ __forceinline__ void tma_5d(uint32_t dst, const CUtensorMap* map, int c0, int c1, int c2, int c3, int c4, uint32_t bar) {
  asm volatile("cp.async.bulk.tensor.5d.shared::cluster.global.mbarrier::complete_tx::bytes [%0], [%1, {%3, %4, %5, %6, %7}], [%2];"
               ::"r"(dst), "l"(map), "r"(bar), "r"(c0), "r"(c1), "r"(c2), "r"(c3), "r"(c4) : "memory");
}
__device__ __forceinline__ void tma_store_3d(const CUtensorMap* map, uint32_t src, int c0, int c1, int c2) {
  asm volatile("cp.async.bulk.tensor.3d.global.shared::cta.bulk_group [%0, {%2, %3, %4}], [%1];"
               ::"l"(map), "r"(src), "r"(c0), "r"(c1), "r"(c2) : "memory");
}
__device__ __forceinline__ void bulk_g2s(uint32_t dst, const void* src, uint32_t bytes, uint32_t bar) {
  asm volatile("cp.async.bulk.shared::cluster.global.mbarrier::complete_tx::bytes [%0], [%1], %2, [%3];"
               ::"r"(dst), "l"(src), "r"(bytes), "r"(bar) : "memory");
}
__device__ __forceinline__ void prefetch_map(const CUtensorMap* m) { asm volatile("prefetch.tensormap [%0];" ::"l"(m) : "memory"); }
__device__ __forceinline__ uint32_t mapa(uint32_t addr, uint32_t rank) { uint32_t r; asm volatile("mapa.shared::cluster.u32 %0, %1, %2;" : "=r"(r) : "r"(addr), "r"(rank)); return r; }
__device__ __forceinline__ void cluster_sync() { asm volatile("barrier.cluster.arrive.release.aligned;\nbarrier.cluster.wait.acquire.aligned;" ::: "memory"); }
__device__ __forceinline__ void fence_async_smem() { asm volatile("fence.proxy.async.shared::cta;" ::: "memory"); }
__device__ __forceinline__ void wg_fence() { asm volatile("wgmma.fence.sync.aligned;" ::: "memory"); }
__device__ __forceinline__ void wg_commit() { asm volatile("wgmma.commit_group.sync.aligned;" ::: "memory"); }
template <int N> __device__ __forceinline__ void wg_wait() { asm volatile("wgmma.wait_group.sync.aligned %0;" ::"n"(N) : "memory"); }
template <int N> __device__ __forceinline__ void reg_fence(float (&d)[N]) {
#pragma unroll
  for (int i = 0; i < N; i++) asm volatile("" : "+f"(d[i])::"memory");
}
__device__ __forceinline__ void named_bar(int id, int n) { asm volatile("bar.sync %0, %1;" ::"r"(id), "r"(n) : "memory"); }
__device__ __forceinline__ uint64_t mk_desc(uint32_t addr, uint32_t lbo, uint32_t sbo, uint32_t sw) {
  return (uint64_t)((addr & 0x3FFFF) >> 4) | ((uint64_t)(lbo >> 4) << 16) | ((uint64_t)(sbo >> 4) << 32) | ((uint64_t)sw << 62);
}
__device__ __forceinline__ uint32_t pack_bf16(float lo, float hi) {
  uint32_t r; asm("cvt.rn.bf16x2.f32 %0, %1, %2;" : "=r"(r) : "f"(hi), "f"(lo)); return r;
}
__device__ __forceinline__ float bf_lo(uint32_t v) { return __uint_as_float(v << 16); }
__device__ __forceinline__ float bf_hi(uint32_t v) { return __uint_as_float(v & 0xffff0000u); }
__device__ __forceinline__ float bf_round(float x) { return __bfloat162float(__float2bfloat16_rn(x)); }
__device__ __forceinline__ void st_async_v4(uint32_t addr, uint32_t a, uint32_t b, uint32_t c, uint32_t d, uint32_t bar) {
  asm volatile("st.async.weak.shared::cluster.mbarrier::complete_tx::bytes.v4.b32 [%0], {%1, %2, %3, %4}, [%5];"
               ::"r"(addr), "r"(a), "r"(b), "r"(c), "r"(d), "r"(bar) : "memory");
}
__device__ __forceinline__ void stmatrix_x4_t(uint32_t addr, uint32_t a, uint32_t b, uint32_t c, uint32_t d) {
  asm volatile("stmatrix.sync.aligned.m8n8.x4.trans.shared.b16 [%0], {%1, %2, %3, %4};" ::"r"(addr), "r"(a), "r"(b), "r"(c), "r"(d) : "memory");
}
__device__ __forceinline__ void ldmatrix_x4_t(uint32_t addr, uint32_t& a, uint32_t& b, uint32_t& c, uint32_t& d) {
  asm volatile("ldmatrix.sync.aligned.m8n8.x4.trans.shared.b16 {%0, %1, %2, %3}, [%4];" : "=r"(a), "=r"(b), "=r"(c), "=r"(d) : "r"(addr) : "memory");
}
__device__ __forceinline__ uint32_t lds32(uint32_t addr) { uint32_t v; asm volatile("ld.shared.b32 %0, [%1];" : "=r"(v) : "r"(addr) : "memory"); return v; }
__device__ __forceinline__ float geglu(float g, float u) {
  float z = g * fmaf(g * g, 0.0356774081f, 0.7978845608f);
  float t; asm("tanh.approx.f32 %0, %1;" : "=f"(t) : "f"(z));
  return (g * u) * fmaf(t, 0.5f, 0.5f);
}

__device__ __forceinline__ uint4 lds128(uint32_t addr) { uint4 v; asm volatile("ld.shared.v4.b32 {%0,%1,%2,%3}, [%4];" : "=r"(v.x), "=r"(v.y), "=r"(v.z), "=r"(v.w) : "r"(addr) : "memory"); return v; }
__device__ __forceinline__ void sts32(uint32_t addr, uint32_t v) { asm volatile("st.shared.b32 [%0], %1;" ::"r"(addr), "r"(v) : "memory"); }
__device__ __forceinline__ void stmatrix_x4(uint32_t addr, uint32_t a, uint32_t b, uint32_t c, uint32_t d) {
  asm volatile("stmatrix.sync.aligned.m8n8.x4.shared.b16 [%0], {%1, %2, %3, %4};" ::"r"(addr), "r"(a), "r"(b), "r"(c), "r"(d) : "memory");
}
__device__ __forceinline__ void ldmatrix_x4(uint32_t addr, uint32_t (&r)[4]) {
  asm volatile("ldmatrix.sync.aligned.m8n8.x4.shared.b16 {%0, %1, %2, %3}, [%4];" : "=r"(r[0]), "=r"(r[1]), "=r"(r[2]), "=r"(r[3]) : "r"(addr) : "memory");
}
__device__ __forceinline__ void sts128(uint32_t addr, uint4 v) { asm volatile("st.shared.v4.b32 [%0], {%1,%2,%3,%4};" ::"r"(addr), "r"(v.x), "r"(v.y), "r"(v.z), "r"(v.w) : "memory"); }
__device__ __forceinline__ void bulk_s2g(void* dst, uint32_t src, uint32_t bytes) {
  asm volatile("cp.async.bulk.global.shared::cta.bulk_group [%0], [%1], %2;" ::"l"(dst), "r"(src), "r"(bytes) : "memory");
}
__device__ __forceinline__ void tma_store_2d(const CUtensorMap* map, uint32_t src, int c0, int c1) {
  asm volatile("cp.async.bulk.tensor.2d.global.shared::cta.bulk_group [%0, {%2, %3}], [%1];" ::"l"(map), "r"(src), "r"(c0), "r"(c1) : "memory");
}
__device__ __forceinline__ void bulk_commit_wait() {
  asm volatile("cp.async.bulk.commit_group;" ::: "memory");
  asm volatile("cp.async.bulk.wait_group 0;" ::: "memory");
}
__device__ __forceinline__ void named_arrive(int id, int n) { asm volatile("bar.arrive %0, %1;" ::"r"(id), "r"(n) : "memory"); }
__device__ __forceinline__ void fence_async_all() { asm volatile("fence.proxy.async;" ::: "memory"); }
__device__ __forceinline__ void cnt_add(int idx) {
  asm volatile("red.release.gpu.global.add.u32 [%0], 1;" ::"l"(g_cnt + idx * 32) : "memory");
}
__device__ __forceinline__ void cnt_wait(int idx, uint32_t target) {
  const unsigned int* p = g_cnt + idx * 32;
  for (int it = 0; it < (1 << 18); it++) {
    uint32_t v; asm volatile("ld.acquire.gpu.global.u32 %0, [%1];" : "=r"(v) : "l"(p) : "memory");
    if (v >= target) break;
    __nanosleep(20);
  }
}
__device__ __forceinline__ void prefetch_l2(const void* p, uint32_t bytes) { asm volatile("cp.async.bulk.prefetch.L2.global [%0], %1;" ::"l"(p), "r"(bytes) : "memory"); }

template <int TB>
__device__ __forceinline__ void wg_ss128_init(float (&d)[64], uint64_t da, uint64_t db) {
  asm volatile(
    "wgmma.mma_async.sync.aligned.m64n128k16.f32.bf16.bf16 {%0, %1, %2, %3, %4, %5, %6, %7, %8, %9, %10, %11, %12, %13, %14, %15, %16, %17, %18, %19, %20, %21, %22, %23, %24, %25, %26, %27, %28, %29, %30, %31, %32, %33, %34, %35, %36, %37, %38, %39, %40, %41, %42, %43, %44, %45, %46, %47, %48, %49, %50, %51, %52, %53, %54, %55, %56, %57, %58, %59, %60, %61, %62, %63}, %64, %65, 0, 1, 1, 0, %66;"
    : "=f"(d[0]), "=f"(d[1]), "=f"(d[2]), "=f"(d[3]), "=f"(d[4]), "=f"(d[5]), "=f"(d[6]), "=f"(d[7]), "=f"(d[8]), "=f"(d[9]), "=f"(d[10]), "=f"(d[11]), "=f"(d[12]), "=f"(d[13]), "=f"(d[14]), "=f"(d[15]), "=f"(d[16]), "=f"(d[17]), "=f"(d[18]), "=f"(d[19]), "=f"(d[20]), "=f"(d[21]), "=f"(d[22]), "=f"(d[23]), "=f"(d[24]), "=f"(d[25]), "=f"(d[26]), "=f"(d[27]), "=f"(d[28]), "=f"(d[29]), "=f"(d[30]), "=f"(d[31]), "=f"(d[32]), "=f"(d[33]), "=f"(d[34]), "=f"(d[35]), "=f"(d[36]), "=f"(d[37]), "=f"(d[38]), "=f"(d[39]), "=f"(d[40]), "=f"(d[41]), "=f"(d[42]), "=f"(d[43]), "=f"(d[44]), "=f"(d[45]), "=f"(d[46]), "=f"(d[47]), "=f"(d[48]), "=f"(d[49]), "=f"(d[50]), "=f"(d[51]), "=f"(d[52]), "=f"(d[53]), "=f"(d[54]), "=f"(d[55]), "=f"(d[56]), "=f"(d[57]), "=f"(d[58]), "=f"(d[59]), "=f"(d[60]), "=f"(d[61]), "=f"(d[62]), "=f"(d[63])
    : "l"(da), "l"(db), "n"(TB));
}
template <int TB>
__device__ __forceinline__ void wg_ss128(float (&d)[64], uint64_t da, uint64_t db) {
  asm volatile(
    "wgmma.mma_async.sync.aligned.m64n128k16.f32.bf16.bf16 {%0, %1, %2, %3, %4, %5, %6, %7, %8, %9, %10, %11, %12, %13, %14, %15, %16, %17, %18, %19, %20, %21, %22, %23, %24, %25, %26, %27, %28, %29, %30, %31, %32, %33, %34, %35, %36, %37, %38, %39, %40, %41, %42, %43, %44, %45, %46, %47, %48, %49, %50, %51, %52, %53, %54, %55, %56, %57, %58, %59, %60, %61, %62, %63}, %64, %65, 1, 1, 1, 0, %66;"
    : "+f"(d[0]), "+f"(d[1]), "+f"(d[2]), "+f"(d[3]), "+f"(d[4]), "+f"(d[5]), "+f"(d[6]), "+f"(d[7]), "+f"(d[8]), "+f"(d[9]), "+f"(d[10]), "+f"(d[11]), "+f"(d[12]), "+f"(d[13]), "+f"(d[14]), "+f"(d[15]), "+f"(d[16]), "+f"(d[17]), "+f"(d[18]), "+f"(d[19]), "+f"(d[20]), "+f"(d[21]), "+f"(d[22]), "+f"(d[23]), "+f"(d[24]), "+f"(d[25]), "+f"(d[26]), "+f"(d[27]), "+f"(d[28]), "+f"(d[29]), "+f"(d[30]), "+f"(d[31]), "+f"(d[32]), "+f"(d[33]), "+f"(d[34]), "+f"(d[35]), "+f"(d[36]), "+f"(d[37]), "+f"(d[38]), "+f"(d[39]), "+f"(d[40]), "+f"(d[41]), "+f"(d[42]), "+f"(d[43]), "+f"(d[44]), "+f"(d[45]), "+f"(d[46]), "+f"(d[47]), "+f"(d[48]), "+f"(d[49]), "+f"(d[50]), "+f"(d[51]), "+f"(d[52]), "+f"(d[53]), "+f"(d[54]), "+f"(d[55]), "+f"(d[56]), "+f"(d[57]), "+f"(d[58]), "+f"(d[59]), "+f"(d[60]), "+f"(d[61]), "+f"(d[62]), "+f"(d[63])
    : "l"(da), "l"(db), "n"(TB));
}
template <int TB>
__device__ __forceinline__ void wg_ss256(float (&d)[128], uint64_t da, uint64_t db) {
  asm volatile(
    "wgmma.mma_async.sync.aligned.m64n256k16.f32.bf16.bf16 {%0, %1, %2, %3, %4, %5, %6, %7, %8, %9, %10, %11, %12, %13, %14, %15, %16, %17, %18, %19, %20, %21, %22, %23, %24, %25, %26, %27, %28, %29, %30, %31, %32, %33, %34, %35, %36, %37, %38, %39, %40, %41, %42, %43, %44, %45, %46, %47, %48, %49, %50, %51, %52, %53, %54, %55, %56, %57, %58, %59, %60, %61, %62, %63, %64, %65, %66, %67, %68, %69, %70, %71, %72, %73, %74, %75, %76, %77, %78, %79, %80, %81, %82, %83, %84, %85, %86, %87, %88, %89, %90, %91, %92, %93, %94, %95, %96, %97, %98, %99, %100, %101, %102, %103, %104, %105, %106, %107, %108, %109, %110, %111, %112, %113, %114, %115, %116, %117, %118, %119, %120, %121, %122, %123, %124, %125, %126, %127}, %128, %129, 1, 1, 1, 0, %130;"
    : "+f"(d[0]), "+f"(d[1]), "+f"(d[2]), "+f"(d[3]), "+f"(d[4]), "+f"(d[5]), "+f"(d[6]), "+f"(d[7]), "+f"(d[8]), "+f"(d[9]), "+f"(d[10]), "+f"(d[11]), "+f"(d[12]), "+f"(d[13]), "+f"(d[14]), "+f"(d[15]), "+f"(d[16]), "+f"(d[17]), "+f"(d[18]), "+f"(d[19]), "+f"(d[20]), "+f"(d[21]), "+f"(d[22]), "+f"(d[23]), "+f"(d[24]), "+f"(d[25]), "+f"(d[26]), "+f"(d[27]), "+f"(d[28]), "+f"(d[29]), "+f"(d[30]), "+f"(d[31]), "+f"(d[32]), "+f"(d[33]), "+f"(d[34]), "+f"(d[35]), "+f"(d[36]), "+f"(d[37]), "+f"(d[38]), "+f"(d[39]), "+f"(d[40]), "+f"(d[41]), "+f"(d[42]), "+f"(d[43]), "+f"(d[44]), "+f"(d[45]), "+f"(d[46]), "+f"(d[47]), "+f"(d[48]), "+f"(d[49]), "+f"(d[50]), "+f"(d[51]), "+f"(d[52]), "+f"(d[53]), "+f"(d[54]), "+f"(d[55]), "+f"(d[56]), "+f"(d[57]), "+f"(d[58]), "+f"(d[59]), "+f"(d[60]), "+f"(d[61]), "+f"(d[62]), "+f"(d[63]), "+f"(d[64]), "+f"(d[65]), "+f"(d[66]), "+f"(d[67]), "+f"(d[68]), "+f"(d[69]), "+f"(d[70]), "+f"(d[71]), "+f"(d[72]), "+f"(d[73]), "+f"(d[74]), "+f"(d[75]), "+f"(d[76]), "+f"(d[77]), "+f"(d[78]), "+f"(d[79]), "+f"(d[80]), "+f"(d[81]), "+f"(d[82]), "+f"(d[83]), "+f"(d[84]), "+f"(d[85]), "+f"(d[86]), "+f"(d[87]), "+f"(d[88]), "+f"(d[89]), "+f"(d[90]), "+f"(d[91]), "+f"(d[92]), "+f"(d[93]), "+f"(d[94]), "+f"(d[95]), "+f"(d[96]), "+f"(d[97]), "+f"(d[98]), "+f"(d[99]), "+f"(d[100]), "+f"(d[101]), "+f"(d[102]), "+f"(d[103]), "+f"(d[104]), "+f"(d[105]), "+f"(d[106]), "+f"(d[107]), "+f"(d[108]), "+f"(d[109]), "+f"(d[110]), "+f"(d[111]), "+f"(d[112]), "+f"(d[113]), "+f"(d[114]), "+f"(d[115]), "+f"(d[116]), "+f"(d[117]), "+f"(d[118]), "+f"(d[119]), "+f"(d[120]), "+f"(d[121]), "+f"(d[122]), "+f"(d[123]), "+f"(d[124]), "+f"(d[125]), "+f"(d[126]), "+f"(d[127])
    : "l"(da), "l"(db), "n"(TB));
}
template <int TB>
__device__ __forceinline__ void wg_ss32(float (&d)[16], uint64_t da, uint64_t db) {
  asm volatile(
    "wgmma.mma_async.sync.aligned.m64n32k16.f32.bf16.bf16 {%0, %1, %2, %3, %4, %5, %6, %7, %8, %9, %10, %11, %12, %13, %14, %15}, %16, %17, 1, 1, 1, 0, %18;"
    : "+f"(d[0]), "+f"(d[1]), "+f"(d[2]), "+f"(d[3]), "+f"(d[4]), "+f"(d[5]), "+f"(d[6]), "+f"(d[7]), "+f"(d[8]), "+f"(d[9]), "+f"(d[10]), "+f"(d[11]), "+f"(d[12]), "+f"(d[13]), "+f"(d[14]), "+f"(d[15])
    : "l"(da), "l"(db), "n"(TB));
}
template <int TB>
__device__ __forceinline__ void wg_rs256(float (&d)[128], uint32_t a0, uint32_t a1, uint32_t a2, uint32_t a3, uint64_t db) {
  asm volatile(
    "wgmma.mma_async.sync.aligned.m64n256k16.f32.bf16.bf16 {%0, %1, %2, %3, %4, %5, %6, %7, %8, %9, %10, %11, %12, %13, %14, %15, %16, %17, %18, %19, %20, %21, %22, %23, %24, %25, %26, %27, %28, %29, %30, %31, %32, %33, %34, %35, %36, %37, %38, %39, %40, %41, %42, %43, %44, %45, %46, %47, %48, %49, %50, %51, %52, %53, %54, %55, %56, %57, %58, %59, %60, %61, %62, %63, %64, %65, %66, %67, %68, %69, %70, %71, %72, %73, %74, %75, %76, %77, %78, %79, %80, %81, %82, %83, %84, %85, %86, %87, %88, %89, %90, %91, %92, %93, %94, %95, %96, %97, %98, %99, %100, %101, %102, %103, %104, %105, %106, %107, %108, %109, %110, %111, %112, %113, %114, %115, %116, %117, %118, %119, %120, %121, %122, %123, %124, %125, %126, %127}, {%128, %129, %130, %131}, %132, 1, 1, 1, %133;"
    : "+f"(d[0]), "+f"(d[1]), "+f"(d[2]), "+f"(d[3]), "+f"(d[4]), "+f"(d[5]), "+f"(d[6]), "+f"(d[7]), "+f"(d[8]), "+f"(d[9]), "+f"(d[10]), "+f"(d[11]), "+f"(d[12]), "+f"(d[13]), "+f"(d[14]), "+f"(d[15]), "+f"(d[16]), "+f"(d[17]), "+f"(d[18]), "+f"(d[19]), "+f"(d[20]), "+f"(d[21]), "+f"(d[22]), "+f"(d[23]), "+f"(d[24]), "+f"(d[25]), "+f"(d[26]), "+f"(d[27]), "+f"(d[28]), "+f"(d[29]), "+f"(d[30]), "+f"(d[31]), "+f"(d[32]), "+f"(d[33]), "+f"(d[34]), "+f"(d[35]), "+f"(d[36]), "+f"(d[37]), "+f"(d[38]), "+f"(d[39]), "+f"(d[40]), "+f"(d[41]), "+f"(d[42]), "+f"(d[43]), "+f"(d[44]), "+f"(d[45]), "+f"(d[46]), "+f"(d[47]), "+f"(d[48]), "+f"(d[49]), "+f"(d[50]), "+f"(d[51]), "+f"(d[52]), "+f"(d[53]), "+f"(d[54]), "+f"(d[55]), "+f"(d[56]), "+f"(d[57]), "+f"(d[58]), "+f"(d[59]), "+f"(d[60]), "+f"(d[61]), "+f"(d[62]), "+f"(d[63]), "+f"(d[64]), "+f"(d[65]), "+f"(d[66]), "+f"(d[67]), "+f"(d[68]), "+f"(d[69]), "+f"(d[70]), "+f"(d[71]), "+f"(d[72]), "+f"(d[73]), "+f"(d[74]), "+f"(d[75]), "+f"(d[76]), "+f"(d[77]), "+f"(d[78]), "+f"(d[79]), "+f"(d[80]), "+f"(d[81]), "+f"(d[82]), "+f"(d[83]), "+f"(d[84]), "+f"(d[85]), "+f"(d[86]), "+f"(d[87]), "+f"(d[88]), "+f"(d[89]), "+f"(d[90]), "+f"(d[91]), "+f"(d[92]), "+f"(d[93]), "+f"(d[94]), "+f"(d[95]), "+f"(d[96]), "+f"(d[97]), "+f"(d[98]), "+f"(d[99]), "+f"(d[100]), "+f"(d[101]), "+f"(d[102]), "+f"(d[103]), "+f"(d[104]), "+f"(d[105]), "+f"(d[106]), "+f"(d[107]), "+f"(d[108]), "+f"(d[109]), "+f"(d[110]), "+f"(d[111]), "+f"(d[112]), "+f"(d[113]), "+f"(d[114]), "+f"(d[115]), "+f"(d[116]), "+f"(d[117]), "+f"(d[118]), "+f"(d[119]), "+f"(d[120]), "+f"(d[121]), "+f"(d[122]), "+f"(d[123]), "+f"(d[124]), "+f"(d[125]), "+f"(d[126]), "+f"(d[127])
    : "r"(a0), "r"(a1), "r"(a2), "r"(a3), "l"(db), "n"(TB));
}
template <int TB>
__device__ __forceinline__ void wg_rs32(float (&d)[16], uint32_t a0, uint32_t a1, uint32_t a2, uint32_t a3, uint64_t db) {
  asm volatile(
    "wgmma.mma_async.sync.aligned.m64n32k16.f32.bf16.bf16 {%0, %1, %2, %3, %4, %5, %6, %7, %8, %9, %10, %11, %12, %13, %14, %15}, {%16, %17, %18, %19}, %20, 1, 1, 1, %21;"
    : "+f"(d[0]), "+f"(d[1]), "+f"(d[2]), "+f"(d[3]), "+f"(d[4]), "+f"(d[5]), "+f"(d[6]), "+f"(d[7]), "+f"(d[8]), "+f"(d[9]), "+f"(d[10]), "+f"(d[11]), "+f"(d[12]), "+f"(d[13]), "+f"(d[14]), "+f"(d[15])
    : "r"(a0), "r"(a1), "r"(a2), "r"(a3), "l"(db), "n"(TB));
}
template <int TB>
__device__ __forceinline__ void wg_cv128(float (&d)[64], uint32_t a0, uint32_t a1, uint32_t a2, uint32_t a3, uint64_t db) {
  asm volatile(
    "wgmma.mma_async.sync.aligned.m64n128k16.f32.bf16.bf16 {%0, %1, %2, %3, %4, %5, %6, %7, %8, %9, %10, %11, %12, %13, %14, %15, %16, %17, %18, %19, %20, %21, %22, %23, %24, %25, %26, %27, %28, %29, %30, %31, %32, %33, %34, %35, %36, %37, %38, %39, %40, %41, %42, %43, %44, %45, %46, %47, %48, %49, %50, %51, %52, %53, %54, %55, %56, %57, %58, %59, %60, %61, %62, %63}, {%64, %65, %66, %67}, %68, 1, 1, 1, %69;"
    : "+f"(d[0]), "+f"(d[1]), "+f"(d[2]), "+f"(d[3]), "+f"(d[4]), "+f"(d[5]), "+f"(d[6]), "+f"(d[7]), "+f"(d[8]), "+f"(d[9]), "+f"(d[10]), "+f"(d[11]), "+f"(d[12]), "+f"(d[13]), "+f"(d[14]), "+f"(d[15]), "+f"(d[16]), "+f"(d[17]), "+f"(d[18]), "+f"(d[19]), "+f"(d[20]), "+f"(d[21]), "+f"(d[22]), "+f"(d[23]), "+f"(d[24]), "+f"(d[25]), "+f"(d[26]), "+f"(d[27]), "+f"(d[28]), "+f"(d[29]), "+f"(d[30]), "+f"(d[31]), "+f"(d[32]), "+f"(d[33]), "+f"(d[34]), "+f"(d[35]), "+f"(d[36]), "+f"(d[37]), "+f"(d[38]), "+f"(d[39]), "+f"(d[40]), "+f"(d[41]), "+f"(d[42]), "+f"(d[43]), "+f"(d[44]), "+f"(d[45]), "+f"(d[46]), "+f"(d[47]), "+f"(d[48]), "+f"(d[49]), "+f"(d[50]), "+f"(d[51]), "+f"(d[52]), "+f"(d[53]), "+f"(d[54]), "+f"(d[55]), "+f"(d[56]), "+f"(d[57]), "+f"(d[58]), "+f"(d[59]), "+f"(d[60]), "+f"(d[61]), "+f"(d[62]), "+f"(d[63])
    : "r"(a0), "r"(a1), "r"(a2), "r"(a3), "l"(db), "n"(TB));
}
template <int TB>
__device__ __forceinline__ void wg_cv96(float (&d)[48], uint32_t a0, uint32_t a1, uint32_t a2, uint32_t a3, uint64_t db) {
  asm volatile(
    "wgmma.mma_async.sync.aligned.m64n96k16.f32.bf16.bf16 {%0, %1, %2, %3, %4, %5, %6, %7, %8, %9, %10, %11, %12, %13, %14, %15, %16, %17, %18, %19, %20, %21, %22, %23, %24, %25, %26, %27, %28, %29, %30, %31, %32, %33, %34, %35, %36, %37, %38, %39, %40, %41, %42, %43, %44, %45, %46, %47}, {%48, %49, %50, %51}, %52, 1, 1, 1, %53;"
    : "+f"(d[0]), "+f"(d[1]), "+f"(d[2]), "+f"(d[3]), "+f"(d[4]), "+f"(d[5]), "+f"(d[6]), "+f"(d[7]), "+f"(d[8]), "+f"(d[9]), "+f"(d[10]), "+f"(d[11]), "+f"(d[12]), "+f"(d[13]), "+f"(d[14]), "+f"(d[15]), "+f"(d[16]), "+f"(d[17]), "+f"(d[18]), "+f"(d[19]), "+f"(d[20]), "+f"(d[21]), "+f"(d[22]), "+f"(d[23]), "+f"(d[24]), "+f"(d[25]), "+f"(d[26]), "+f"(d[27]), "+f"(d[28]), "+f"(d[29]), "+f"(d[30]), "+f"(d[31]), "+f"(d[32]), "+f"(d[33]), "+f"(d[34]), "+f"(d[35]), "+f"(d[36]), "+f"(d[37]), "+f"(d[38]), "+f"(d[39]), "+f"(d[40]), "+f"(d[41]), "+f"(d[42]), "+f"(d[43]), "+f"(d[44]), "+f"(d[45]), "+f"(d[46]), "+f"(d[47])
    : "r"(a0), "r"(a1), "r"(a2), "r"(a3), "l"(db), "n"(TB));
}
template <int TB>
__device__ __forceinline__ void wg_cv64(float (&d)[32], uint32_t a0, uint32_t a1, uint32_t a2, uint32_t a3, uint64_t db) {
  asm volatile(
    "wgmma.mma_async.sync.aligned.m64n64k16.f32.bf16.bf16 {%0, %1, %2, %3, %4, %5, %6, %7, %8, %9, %10, %11, %12, %13, %14, %15, %16, %17, %18, %19, %20, %21, %22, %23, %24, %25, %26, %27, %28, %29, %30, %31}, {%32, %33, %34, %35}, %36, 1, 1, 1, %37;"
    : "+f"(d[0]), "+f"(d[1]), "+f"(d[2]), "+f"(d[3]), "+f"(d[4]), "+f"(d[5]), "+f"(d[6]), "+f"(d[7]), "+f"(d[8]), "+f"(d[9]), "+f"(d[10]), "+f"(d[11]), "+f"(d[12]), "+f"(d[13]), "+f"(d[14]), "+f"(d[15]), "+f"(d[16]), "+f"(d[17]), "+f"(d[18]), "+f"(d[19]), "+f"(d[20]), "+f"(d[21]), "+f"(d[22]), "+f"(d[23]), "+f"(d[24]), "+f"(d[25]), "+f"(d[26]), "+f"(d[27]), "+f"(d[28]), "+f"(d[29]), "+f"(d[30]), "+f"(d[31])
    : "r"(a0), "r"(a1), "r"(a2), "r"(a3), "l"(db), "n"(TB));
}
template <int TB>
__device__ __forceinline__ void wg_cv128_init(float (&d)[64], uint32_t a0, uint32_t a1, uint32_t a2, uint32_t a3, uint64_t db) {
  asm volatile(
    "wgmma.mma_async.sync.aligned.m64n128k16.f32.bf16.bf16 {%0, %1, %2, %3, %4, %5, %6, %7, %8, %9, %10, %11, %12, %13, %14, %15, %16, %17, %18, %19, %20, %21, %22, %23, %24, %25, %26, %27, %28, %29, %30, %31, %32, %33, %34, %35, %36, %37, %38, %39, %40, %41, %42, %43, %44, %45, %46, %47, %48, %49, %50, %51, %52, %53, %54, %55, %56, %57, %58, %59, %60, %61, %62, %63}, {%64, %65, %66, %67}, %68, 0, 1, 1, %69;"
    : "=f"(d[0]), "=f"(d[1]), "=f"(d[2]), "=f"(d[3]), "=f"(d[4]), "=f"(d[5]), "=f"(d[6]), "=f"(d[7]), "=f"(d[8]), "=f"(d[9]), "=f"(d[10]), "=f"(d[11]), "=f"(d[12]), "=f"(d[13]), "=f"(d[14]), "=f"(d[15]), "=f"(d[16]), "=f"(d[17]), "=f"(d[18]), "=f"(d[19]), "=f"(d[20]), "=f"(d[21]), "=f"(d[22]), "=f"(d[23]), "=f"(d[24]), "=f"(d[25]), "=f"(d[26]), "=f"(d[27]), "=f"(d[28]), "=f"(d[29]), "=f"(d[30]), "=f"(d[31]), "=f"(d[32]), "=f"(d[33]), "=f"(d[34]), "=f"(d[35]), "=f"(d[36]), "=f"(d[37]), "=f"(d[38]), "=f"(d[39]), "=f"(d[40]), "=f"(d[41]), "=f"(d[42]), "=f"(d[43]), "=f"(d[44]), "=f"(d[45]), "=f"(d[46]), "=f"(d[47]), "=f"(d[48]), "=f"(d[49]), "=f"(d[50]), "=f"(d[51]), "=f"(d[52]), "=f"(d[53]), "=f"(d[54]), "=f"(d[55]), "=f"(d[56]), "=f"(d[57]), "=f"(d[58]), "=f"(d[59]), "=f"(d[60]), "=f"(d[61]), "=f"(d[62]), "=f"(d[63])
    : "r"(a0), "r"(a1), "r"(a2), "r"(a3), "l"(db), "n"(TB));
}

constexpr int NST = 7, SLOT = 9216;
constexpr uint32_t SM_XN = 0, SM_HIN = 147456, SM_RING = 163840, SM_BAR = SM_RING + NST * SLOT;
constexpr uint32_t SMEM_BYTES = SM_BAR + 320;
constexpr uint32_t B_FULL = 0, B_EMPTY = 56, B_XN = 112, B_HF = 184, B_HE = 200, B_CV = 216, B_PT = 224, B_YT = 232, B_SG = 240, B_X = 248;
constexpr uint32_t PR_LN = 81920, PR_PAR = 102400, PR_RED = 110592;
constexpr uint32_t T_U = 81920, T_KP = 99328, T_YT = 81920, T_PART = SM_HIN;
constexpr uint32_t U_BYTES = U_LEN * 2, KP_BYTES = KP_LEN * 4, IMG = 18432;

struct Params {
  CUtensorMap xn, gate, up, dn, dn5, dp, dp5, x, x5, y, y5, out, out5;
  const __nv_bfloat16 *xp, *logA, *Aim, *Cre, *Cim, *logdt, *Dsk;
};

__device__ __forceinline__ float us2f(uint32_t v) { return __uint_as_float(v << 16); }
struct KgIn { uint32_t la, ai, cr, ci, ldt; };
__device__ __forceinline__ void kgen_load(const Params& p, int ch0, int tid, KgIn& in) {
  const int e = ch0 * (NM_ / 2) + tid;
  in.la = __ldg((const uint32_t*)p.logA + e); in.ai = __ldg((const uint32_t*)p.Aim + e);
  in.cr = __ldg((const uint32_t*)p.Cre + e); in.ci = __ldg((const uint32_t*)p.Cim + e);
  in.ldt = __ldg((const unsigned short*)p.logdt + ch0 + (tid >> 6)) | ((uint32_t)__ldg((const unsigned short*)p.Dsk + ch0 + (tid >> 6)) << 16);
}
__device__ __forceinline__ void kgen4(unsigned char* sm, unsigned short* kd4, int tid, KgIn in) {
  float4* s_par = (float4*)(sm + PR_PAR);
  float* s_red = (float*)(sm + PR_RED);
  const int warp = tid >> 5, lane = tid & 31;
  const float dt = bf_round(expf(bf_lo(in.ldt)));
  float v = 0.f;
#pragma unroll 1
  for (int r = 0; r < 2; r++) {
    const float are = -bf_round(expf(bf_lo(in.la))) * dt * 1.4426950408889634f;
    float w = bf_lo(in.ai) * dt * 0.15915494309189535f;
    const float cr = 2.f * bf_lo(in.cr) * dt, ci = 2.f * bf_lo(in.ci) * dt;
    float we = 2048.f * w; we = (we - rintf(we)) * 6.283185307179586f;
    w -= rintf(w);
    s_par[2 * tid + r] = make_float4(are, w * 6.283185307179586f, cr, ci);
    float m; asm("ex2.approx.ftz.f32 %0, %1;" : "=f"(m) : "f"(are * 2048.f));
    v = fmaf(m, cr * __cosf(we) - ci * __sinf(we), v);
    in.la >>= 16; in.ai >>= 16; in.cr >>= 16; in.ci >>= 16;
  }
#pragma unroll
  for (int o = 16; o; o >>= 1) v += __shfl_xor_sync(0xffffffffu, v, o);
  s_red[2560 + warp] = v;
  __syncwarp();
  PROF_T(50);
  const int g = lane >> 2, q = lane & 3;
  float acc[5][4];
#pragma unroll
  for (int t = 0; t < 5; t++) { acc[t][0] = acc[t][1] = acc[t][2] = acc[t][3] = 0.f; }
  const float j1 = (float)g, j2 = (float)(g + 8);
#pragma unroll 2
  for (int ks = 0; ks < 16; ks++) {
    const float4 pr = s_par[warp * 64 + ks * 4 + q];
    float r1, i1, r2, i2;
    {
      float m1, m2;
      asm("ex2.approx.ftz.f32 %0, %1;" : "=f"(m1) : "f"(pr.x * j1));
      asm("ex2.approx.ftz.f32 %0, %1;" : "=f"(m2) : "f"(pr.x * j2));
      const float t1 = pr.y * j1, t2 = pr.y * j2;
      r1 = m1 * __cosf(t1); i1 = m1 * __sinf(t1); r2 = m2 * __cosf(t2); i2 = m2 * __sinf(t2);
    }
    float ar1[4], ai1[4], ar2[4], ai2[4];
#pragma unroll
    for (int s = 0; s < 4; s++) {
      ar1[s] = r1; ai1[s] = i1; ar2[s] = r2; ai2[s] = i2;
      float nr = fmaf(r1, r1, -i1 * i1); i1 = (r1 * i1) * 2.f; r1 = nr;
      nr = fmaf(r2, r2, -i2 * i2); i2 = (r2 * i2) * 2.f; r2 = nr;
    }
    auto mma = [&](float (&d)[4], int s, float er, float ei) {
      const float b0 = fmaf(pr.z, er, -(pr.w * ei)), b1 = fmaf(-pr.z, ei, -(pr.w * er));
      asm("mma.sync.aligned.m16n8k8.row.col.f32.tf32.tf32.f32 {%0,%1,%2,%3}, {%4,%5,%6,%7}, {%8,%9}, {%0,%1,%2,%3};"
          : "+f"(d[0]), "+f"(d[1]), "+f"(d[2]), "+f"(d[3])
          : "r"(__float_as_uint(ar1[s])), "r"(__float_as_uint(ar2[s])), "r"(__float_as_uint(ai1[s])), "r"(__float_as_uint(ai2[s])),
            "r"(__float_as_uint(b0)), "r"(__float_as_uint(b1)));
    };
    mma(acc[0], 0, r1, i1);
    mma(acc[1], 0, r2, i2);
#pragma unroll
    for (int s = 1; s < 4; s++) {
      float nr = fmaf(r2, r2, -i2 * i2); i2 = (r2 * i2) * 2.f; r2 = nr;
      mma(acc[1 + s], s, r2, i2);
    }
  }
  PROF_T(51);
  float* red = s_red + (warp >> 1) * 640 + lane;
  if (warp & 1) {
#pragma unroll
    for (int t = 0; t < 5; t++)
#pragma unroll
      for (int e = 0; e < 4; e++) red[(4 * t + e) * 32] = acc[t][e];
  }
  named_bar(3, 256);
  if (!(warp & 1)) {
    unsigned short* kd = kd4 + (warp >> 1) * 648;
    if (lane == 0) {
      acc[0][0] += bf_hi(in.ldt);
      kd[640] = (unsigned short)pack_bf16(v + s_red[2561 + warp], 0.f);
    }
#pragma unroll
    for (int t = 0; t < 5; t++)
#pragma unroll
      for (int e = 0; e < 4; e++)
        kd[t * 128 + 32 * q + 16 * (e & 1) + 8 * (e >> 1) + g] = (unsigned short)pack_bf16(acc[t][e] + red[(4 * t + e) * 32], 0.f);
  }
  PROF_T(52);
}
__device__ __forceinline__ int kd_index(int l, int sh) {
  const int m = sh ? 1 : 0;
  return ((l + ((1 << sh) >> 1) - m + ((l >> sh) & m)) >> sh) + 128 * sh;
}
template <int NT>
__device__ __forceinline__ void kexpand(const unsigned short* kd0, int ch0, int nch, int tid) {
#pragma unroll 1
  for (int it = tid; it < KP_LEN / 4; it += NT) {
    const int i0 = it * 4 - 16;
    const bool ok = i0 >= 0 && i0 < L_;
    const int l0 = ok ? i0 : 4;
    const int sh = max(0, 24 - __clz(l0 | 1)), shp = max(0, 24 - __clz((l0 - 1) | 1));
    const int xp = kd_index(max(l0 - 1, 0), shp), x0 = kd_index(l0, sh), x1 = kd_index(l0 + 1, sh), x2 = kd_index(l0 + 2, sh), x3 = kd_index(l0 + 3, sh);
    const uint32_t mk = ok ? 0xffffffffu : 0u, mp = i0 > 0 ? mk : 0xffffu & mk;
    const unsigned short* kd = kd0;
    uint4* dst = (uint4*)(g_kp + (size_t)ch0 * KP_LEN) + it;
#pragma unroll 2
    for (int c = 0; c < nch; c++) {
      const uint32_t vp = kd[xp], v0 = kd[x0], v1 = kd[x1], v2 = kd[x2], v3 = kd[x3];
      *dst = make_uint4((v0 | (vp << 16)) & mp, (v1 | (v0 << 16)) & mk, (v2 | (v1 << 16)) & mk, (v3 | (v2 << 16)) & mk);
      kd += 648; dst += KP_LEN / 4;
    }
  }
  fence_async_all();
}

template <int NR>
__device__ __forceinline__ void conv_mma(float (&d)[NR], const uint32_t* a, uint64_t db) {
  if constexpr (NR == 64) wg_cv128<0>(d, a[0], a[1], a[2], a[3], db);
  else if constexpr (NR == 48) wg_cv96<0>(d, a[0], a[1], a[2], a[3], db);
  else if constexpr (NR == 32) wg_cv64<0>(d, a[0], a[1], a[2], a[3], db);
  else wg_rs32<0>(d, a[0], a[1], a[2], a[3], db);
}
__device__ __forceinline__ void conv_load(uint32_t (&a)[8], uint32_t o) {
#pragma unroll
  for (int c = 0; c < 2; c++) {
    a[4 * c + 0] = lds32(o + c * KP_BYTES); a[4 * c + 1] = lds32(o + c * KP_BYTES + 512);
    a[4 * c + 2] = lds32(o + c * KP_BYTES - 32); a[4 * c + 3] = lds32(o + c * KP_BYTES + 480);
  }
}
template <int NR>
__device__ __forceinline__ void conv_phase(float (&dA)[NR], float (&dB)[NR], uint32_t (&a0)[8], uint32_t (&a1)[8], uint32_t kp, uint64_t dU) {
#pragma unroll 1
  for (int i = 0; i < 4; i++) {
    wg_fence();
    conv_mma<NR>(dA, a0, dU); conv_mma<NR>(dB, a0 + 4, dU + (U_BYTES >> 4));
    wg_commit();
    wg_wait<1>();
    conv_load(a1, kp + 64);
    wg_fence();
    conv_mma<NR>(dA, a1, dU - 2); conv_mma<NR>(dB, a1 + 4, dU - 2 + (U_BYTES >> 4));
    wg_commit();
    wg_wait<1>();
    kp += (i == 3) ? 64 * 26 : 128;
    dU -= 4;
    conv_load(a0, kp);
  }
  wg_wait<0>();
  reg_fence(dA); reg_fence(dB);
}
template <int NR>
__device__ __forceinline__ void upper_copy(float (&dst)[NR - 16], const float (&src)[NR]) {
#pragma unroll
  for (int i = 0; i < NR - 16; i++) asm volatile("mov.b32 %0, %1;" : "=f"(dst[i]) : "f"(src[i + 16]));
}
__device__ __forceinline__ void conv2(uint32_t sb, int wg, int w, int lane, int ch, int cnt) {
  const int g = lane >> 2, q = lane & 3;
  float dA[64], dB[64];
  uint32_t a0[8], a1[8];
  const uint32_t kp = sb + T_KP + 2 * wg * KP_BYTES + 4 * (16 + 256 * (w >> 1) + 8 * (w & 1) + g - 2 * q);
  const uint64_t dU = mk_desc(sb + T_U + 2 * wg * U_BYTES + 256, 16, 256, 3);
#pragma unroll
  for (int i = 0; i < 64; i++) { dA[i] = 0.f; dB[i] = 0.f; }
  conv_load(a0, kp);
  conv_phase<64>(dA, dB, a0, a1, kp, dU);
  float eA[48], eB[48];
  upper_copy<64>(eA, dA); upper_copy<64>(eB, dB);
  conv_phase<48>(eA, eB, a0, a1, kp + 2048, dU);
  float fA[32], fB[32];
  upper_copy<48>(fA, eA); upper_copy<48>(fB, eB);
  conv_phase<32>(fA, fB, a0, a1, kp + 4096, dU);
  float gA[16], gB[16];
  upper_copy<32>(gA, fA); upper_copy<32>(gB, fB);
  conv_phase<16>(gA, gB, a0, a1, kp + 6144, dU);
#pragma unroll
  for (int i = 0; i < 16; i++) {
    dA[16 + i] = eA[i]; dA[32 + i] = fA[i]; dA[48 + i] = gA[i];
    dB[16 + i] = eB[i]; dB[32 + i] = fB[i]; dB[48 + i] = gB[i];
  }
  float z[2][16][2];
#pragma unroll
  for (int m = 0; m < 16; m++)
#pragma unroll
    for (int e = 0; e < 2; e++) {
      z[0][m][e] = m ? dA[4 * m + e] + dA[4 * m - 2 + e] : dA[e];
      z[1][m][e] = m ? dB[4 * m + e] + dB[4 * m - 2 + e] : dB[e];
    }
  named_bar(1 + wg, 128);
  const uint32_t xb = sb + T_KP + 2 * wg * KP_BYTES;
  const uint32_t xw = xb + (w * 32 + lane) * 16, xr = xb + ((w ^ 2) * 32 + lane) * 16;
  float k[2][8][2];
  if (w < 2) {
#pragma unroll
    for (int c = 0; c < 2; c++)
#pragma unroll
      for (int m = 0; m < 8; m += 2) {
        sts128(xw + (4 * c + (m >> 1)) * 2048, make_uint4(__float_as_uint(z[c][8 + m][0]), __float_as_uint(z[c][8 + m][1]), __float_as_uint(z[c][9 + m][0]), __float_as_uint(z[c][9 + m][1])));
        k[c][m][0] = z[c][m][0]; k[c][m][1] = z[c][m][1]; k[c][m + 1][0] = z[c][m + 1][0]; k[c][m + 1][1] = z[c][m + 1][1];
      }
  } else {
#pragma unroll
    for (int c = 0; c < 2; c++)
#pragma unroll
      for (int m = 0; m < 8; m += 2) {
        sts128(xw + (4 * c + (m >> 1)) * 2048, m ? make_uint4(__float_as_uint(z[c][m - 2][0]), __float_as_uint(z[c][m - 2][1]), __float_as_uint(z[c][m - 1][0]), __float_as_uint(z[c][m - 1][1])) : make_uint4(0u, 0u, 0u, 0u));
        k[c][m][0] = z[c][6 + m][0]; k[c][m][1] = z[c][6 + m][1]; k[c][m + 1][0] = z[c][7 + m][0]; k[c][m + 1][1] = z[c][7 + m][1];
      }
  }
  named_bar(1 + wg, 128);
  const uint32_t yb = sb + T_U + 2 * wg * U_BYTES;
#pragma unroll
  for (int c = 0; c < 2; c++)
#pragma unroll
    for (int m = 0; m < 8; m += 4) {
      const uint4 u = lds128(xr + (4 * c + (m >> 1)) * 2048), v = lds128(xr + (4 * c + (m >> 1) + 1) * 2048);
      stmatrix_x4_t(yb + c * 4096 + (64 * (w >> 1) + 8 * m + lane) * 32 + 16 * (w & 1),
                    pack_bf16(k[c][m][0] + __uint_as_float(u.x), k[c][m][1] + __uint_as_float(u.y)), pack_bf16(k[c][m + 1][0] + __uint_as_float(u.z), k[c][m + 1][1] + __uint_as_float(u.w)),
                    pack_bf16(k[c][m + 2][0] + __uint_as_float(v.x), k[c][m + 2][1] + __uint_as_float(v.y)), pack_bf16(k[c][m + 3][0] + __uint_as_float(v.z), k[c][m + 3][1] + __uint_as_float(v.w)));
    }
  fence_async_smem();
  named_bar(1 + wg, 128);
  if (w == 0 && lane == 0) {
    bulk_s2g(g_y + (size_t)ch * L_, yb, 8192);
    bulk_commit_wait();
    fence_async_all();
    cnt_add(cnt);
  }
  __syncwarp();
}

__global__ void __cluster_dims__(2, 1, 1) __launch_bounds__(384, 1) fused_kernel(const __grid_constant__ Params p) {
  extern __shared__ __align__(1024) unsigned char smem_raw[];
  const uint32_t sb = smem_u32(smem_raw);
  const uint32_t bar = sb + SM_BAR;
  const int j = blockIdx.x & 1, pair = blockIdx.x >> 1, mt = pair & 15, sp = pair >> 4;
  const bool spare = pair >= 64;
  const int wg = __shfl_sync(0xffffffffu, threadIdx.x >> 7, 0);
  const int row0 = mt * 128 + (2 * sp + j) * 16;
  const int f0 = sp * 1152;
  PROF_T(0);
  KgIn kin;
  if (wg < 2) kgen_load(p, spare ? 512 + ((int)blockIdx.x - 128) * 16 : blockIdx.x * 4, threadIdx.x, kin);
  if (threadIdx.x == 256) {
    mbar_init(bar + B_X, 1);
    if (!spare) {
      mbar_expect_tx(bar + B_X, 16 * D_ * 2);
      bulk_g2s(sb + PR_LN, p.xp + (size_t)row0 * D_, 16 * D_ * 2, bar + B_X);
    }
#pragma unroll 1
    for (int i = 0; i < 30; i++) mbar_init(bar + 8 * i, (i >= 7 && i < 14) ? 8 : 1);
    mbar_init(bar + B_SG, 2);
    mbar_expect_tx(bar + B_HF, 8192); mbar_expect_tx(bar + B_HF + 8, 8192);
    asm volatile("fence.mbarrier_init.release.cluster;" ::: "memory");
    if (!spare) {
#pragma unroll 1
      for (int u = 0; u < NST; u++) {
        const uint32_t dst = sb + SM_RING + u * SLOT, fb = bar + B_FULL + 8 * u;
        mbar_expect_tx(fb, 8192);
        tma_2d(dst, &p.gate, f0 + 64 * j, 32 * u, fb);
        tma_2d(dst + 4096, &p.up, f0 + 64 * j, 32 * u, fb);
      }
    }
  }
  __syncthreads();
  asm volatile("barrier.cluster.arrive.relaxed.aligned;" ::: "memory");

  if (wg == 2) {
    const int t = threadIdx.x & 127, w = t >> 5, lane = t & 31;
    const bool el = elect_one();
    if (!spare) {
      const uint32_t ra = sb + PR_LN + (t >> 3) * (D_ * 2) + (t & 7) * 16;
      PROF_T(60);
      mbar_wait(bar + B_X, 0);
      PROF_T(61);
      const float x0 = bf_lo(lds32(sb + PR_LN + (t >> 3) * (D_ * 2)));
      float s = 0.f, q = 0.f;
#pragma unroll 1
      for (int i = 0; i < 9; i++) {
        const uint4 v = lds128(ra + i * 128);
        const uint32_t u[4] = {v.x, v.y, v.z, v.w};
#pragma unroll
        for (int k = 0; k < 4; k++) {
          const float a = bf_lo(u[k]) - x0, b = bf_hi(u[k]) - x0;
          s += a + b; q = fmaf(a, a, q); q = fmaf(b, b, q);
        }
      }
#pragma unroll
      for (int o = 4; o; o >>= 1) { s += __shfl_xor_sync(0xffffffffu, s, o); q += __shfl_xor_sync(0xffffffffu, q, o); }
      s *= (1.0f / D_);
      const float mb = bf_round(s + x0);
      const float var = fmaxf(fmaf(-s, s, q * (1.0f / D_)), 0.f);
      const float rinv = 1.0f / bf_round(sqrtf(bf_round(bf_round(var) + 1e-5f)));
#pragma unroll 1
      for (int i = 0; i < 9; i++) {
        const uint4 v = lds128(ra + i * 128);
        uint32_t u[4] = {v.x, v.y, v.z, v.w};
#pragma unroll
        for (int k = 0; k < 4; k++) {
          const uint32_t d = pack_bf16(bf_lo(u[k]) - mb, bf_hi(u[k]) - mb);
          u[k] = pack_bf16(bf_lo(d) * rinv, bf_hi(d) * rinv);
        }
        sts128(ra + i * 128, make_uint4(u[0], u[1], u[2], u[3]));
      }
      fence_async_smem();
      named_bar(5, 128);
      PROF_T(62);
      if (w == 0) {
        if (el) {
          bulk_s2g(g_xn + (size_t)row0 * D_, sb + PR_LN, 16 * D_ * 2);
          bulk_commit_wait();
          fence_async_all();
          cnt_add(C_LN + mt);
        }
        __syncwarp();
        PROF_T(63);
      } else {
        const uint32_t* s_ln = (const uint32_t*)(smem_raw + PR_LN);
        const int sw = (row0 >> 6) & 1;
#pragma unroll 1
        for (int it = t - 32; it < 576; it += 96) {
          const int cp = it >> 1, hf = it & 1;
          uint32_t lo[4], hi[4];
#pragma unroll
          for (int r = 0; r < 4; r++) {
            const uint32_t a = s_ln[(8 * hf + 2 * r) * 288 + cp], b = s_ln[(8 * hf + 2 * r + 1) * 288 + cp];
            lo[r] = __byte_perm(a, b, 0x5410); hi[r] = __byte_perm(a, b, 0x7632);
          }
          uint4* d = (uint4*)(g_u + (size_t)(2 * cp) * U_LEN + 128 + row0) + (hf ^ sw);
          d[0] = make_uint4(lo[0], lo[1], lo[2], lo[3]);
          d[U_LEN / 8] = make_uint4(hi[0], hi[1], hi[2], hi[3]);
        }
      }
    }
    asm volatile("barrier.cluster.wait.aligned;" ::: "memory");
    asm volatile("setmaxnreg.dec.sync.aligned.u32 24;");
    if (w == 0) {
      if (!spare) {
        cnt_wait(C_LN + mt, 8);
        PROF_T(67);
        fence_async_all();
#pragma unroll 1
        for (int kb = 0; kb < 9; kb++) {
          if (kb == 5) named_bar(4, 384);
          if (el) {
            mbar_expect_tx(bar + B_XN + 8 * kb, 16384);
            tma_2d(sb + SM_XN + kb * 16384, &p.xn, kb * 64, mt * 128, bar + B_XN + 8 * kb);
          }
        }
        PROF_T(69);
        uint32_t slot = 0, ph = 0;
#pragma unroll 1
        for (int c = 0; c <= 9; c++) {
          const int fc = f0 + c * 128;
          if (c < 9) {
#pragma unroll 1
            for (int u = c ? 0 : NST; u < 18; u++) {
              mbar_wait(bar + B_EMPTY + 8 * slot, ph);
              if (el) {
                const uint32_t dst = sb + SM_RING + slot * SLOT, fb = bar + B_FULL + 8 * slot;
                mbar_expect_tx(fb, 8192);
                tma_2d(dst, &p.gate, fc + 64 * j, 32 * u, fb);
                tma_2d(dst + 4096, &p.up, fc + 64 * j, 32 * u, fb);
              }
              if (++slot == NST) { slot = 0; ph ^= 1; }
            }
          }
          const int fp = (fc - 128 + 64 * (1 - j)) >> 3, fo = fc + 64 * j;
#pragma unroll 1
          for (int i = 0; i < 8; i++) {
            const bool isP = (0x17 >> i) & 1;
            const int u = (0x32130210 >> (4 * i)) & 3;
            if (isP ? (c == 0) : (c == 9)) continue;
            mbar_wait(bar + B_EMPTY + 8 * slot, ph);
            if (el) {
              const uint32_t dst = sb + SM_RING + slot * SLOT, fb = bar + B_FULL + 8 * slot;
              mbar_expect_tx(fb, 9216);
              if (isP) {
                tma_5d(dst, &p.dp, 0, 0, fp + 4 * (u >> 1), 2 * (u & 1), 4 * j, fb);
                tma_4d(dst + 8192, &p.dp5, 512 + 32 * j, 0, fp + 4 * (u >> 1), 2 * (u & 1), fb);
              } else {
                tma_3d(dst, &p.dn, 0, fo + 16 * u, 4 * j, fb);
                tma_2d(dst + 8192, &p.dn5, 512 + 32 * j, fo + 16 * u, fb);
              }
            }
            if (++slot == NST) { slot = 0; ph ^= 1; }
          }
        }
        const int ch0 = blockIdx.x * 4;
        named_bar(7, 128);
        cnt_wait(C_U, 384);
        fence_async_all();
        if (el) {
          mbar_expect_tx(bar + B_CV, 4 * U_BYTES + 4 * KP_BYTES);
          bulk_g2s(sb + T_KP, g_kp + (size_t)ch0 * KP_LEN, 4 * KP_BYTES, bar + B_CV);
          bulk_g2s(sb + T_U, g_u + (size_t)ch0 * U_LEN, 4 * U_BYTES, bar + B_CV);
        }
        unsigned char* img = g_part + (size_t)(2 * mt + j) * 16 * IMG;
        mbar_wait(bar + B_SG, 0);
        if (lane < 15) {
          const int qi = lane / 5, pc = lane - 5 * qi, r = (sp + 1 + qi) & 3;
          bulk_s2g(img + (r * 4 + sp) * IMG + pc * 4096, sb + pc * 16384 + (r >> 1) * 8192 + (r & 1) * (pc < 4 ? 4096 : 2048), pc < 4 ? 4096 : 2048);
          bulk_commit_wait();
          fence_async_all();
        } else if (lane == 15) {
          mbar_expect_tx(bar + B_PT, 4 * IMG);
#pragma unroll 1
          for (int i = 0; i < 4; i++) tma_2d(sb + T_PART + 3 * IMG + i * 4096, &p.x, 256 * j + 64 * i, mt * 128 + 32 * sp, bar + B_PT);
          tma_2d(sb + T_PART + 3 * IMG + 16384, &p.x5, 512 + 32 * j, mt * 128 + 32 * sp, bar + B_PT);
        }
        __syncwarp();
        if (el) cnt_add(C_PART + 2 * mt + j);
        cnt_wait(C_PART + 2 * mt + j, 4);
        fence_async_all();
        if (lane < 3) bulk_g2s(sb + T_PART + lane * IMG, img + (sp * 4 + ((sp + 1 + lane) & 3)) * IMG, IMG, bar + B_PT);
        cnt_wait(C_Y5, 32);
        cnt_wait(C_Y + (ch0 >> 8), 128);
        cnt_wait(C_Y + j, 128);
        fence_async_all();
        if (el) {
          mbar_expect_tx(bar + B_YT, IMG);
          tma_2d(sb + T_YT, &p.y, mt * 128 + 32 * sp, 256 * j, bar + B_YT);
          tma_2d(sb + T_YT + 16384, &p.y5, mt * 128 + 32 * sp, 512 + 32 * j, bar + B_YT);
        }
        cnt_wait(C_Y + (j ^ 1), 128);
      } else {
        named_bar(4, 384);
        cnt_wait(C_U, 384);
        fence_async_all();
#pragma unroll 1
        for (int grp = 0; grp < 4; grp++) {
          const int ch0 = 512 + ((int)blockIdx.x - 128) * 16 + grp * 4;
          if (grp) mbar_wait(bar + B_SG, (grp - 1) & 1);
          if (el) {
            mbar_expect_tx(bar + B_CV, 4 * U_BYTES + 4 * KP_BYTES);
            bulk_g2s(sb + T_KP, g_kp + (size_t)ch0 * KP_LEN, 4 * KP_BYTES, bar + B_CV);
            bulk_g2s(sb + T_U, g_u + (size_t)ch0 * U_LEN, 4 * U_BYTES, bar + B_CV);
          }
        }
      }
      unsigned int old = 0;
      if (el) old = atomicAdd(g_cnt + C_DONE * 32, 1u) + 1;
      if (__any_sync(0xffffffffu, old == gridDim.x)) { g_cnt[lane * 32] = 0u; g_cnt[(lane + 32) * 32] = 0u; }
    } else {
      if (!spare) {
        __syncwarp();
        if (lane == 0) { fence_async_all(); cnt_add(C_U); }
      }
      named_bar(4, 384);
      if (!spare) {
        kexpand<96>((const unsigned short*)(smem_raw + SM_HIN), blockIdx.x * 4, 4, t - 32);
        named_arrive(7, 128);
        named_bar(8, 96);
        if (t == 32) { mbar_arrive_remote(mapa(bar + B_HE, j ^ 1)); mbar_arrive_remote(mapa(bar + B_HE + 8, j ^ 1)); }
      }
    }
  } else {
    const int t = threadIdx.x & 127, w = t >> 5, lane = t & 31;
    if (!spare) kgen4(smem_raw, (unsigned short*)(smem_raw + SM_HIN), threadIdx.x, kin);
    else {
      const int c0 = 512 + ((int)blockIdx.x - 128) * 16;
#pragma unroll 1
      for (int grp = 0; grp < 4; grp++) {
        if (grp) kgen_load(p, c0 + grp * 4, threadIdx.x, kin);
        kgen4(smem_raw, (unsigned short*)(smem_raw + SM_HIN) + grp * 4 * 648, threadIdx.x, kin);
        named_bar(3, 256);
      }
      kexpand<256>((const unsigned short*)(smem_raw + SM_HIN), c0, 16, threadIdx.x);
    }
    named_arrive(4, 384);
    PROF_T(41);
    asm volatile("barrier.cluster.wait.aligned;" ::: "memory");
    asm volatile("setmaxnreg.inc.sync.aligned.u32 240;");
    if (!spare) {
      const bool leader = (t == 0);
      float O1[128], O2[16];
#pragma unroll
      for (int i = 0; i < 128; i++) O1[i] = 0.f;
#pragma unroll
      for (int i = 0; i < 16; i++) O2[i] = 0.f;
      reg_fence(O1); reg_fence(O2);
      uint32_t slot = 0, ph = 0, prev = 0;
      const uint32_t hin = sb + SM_HIN + wg * 8192;
      const uint32_t r_hin = mapa(hin + (16 * w + (lane >> 2)) * 128 + (((lane & 3) ^ (lane >> 2)) << 4), j ^ 1);
      const uint32_t r_hf = mapa(bar + B_HF + 8 * wg, j ^ 1), r_he = mapa(bar + B_HE + 8 * wg, j ^ 1);
      const uint64_t dA0 = mk_desc(sb + SM_XN + wg * 8192, 16, 1024, 1);
      const uint64_t dH0 = mk_desc(hin, 16, 1024, 1);
      const uint64_t dG0 = mk_desc(sb + SM_RING, 4096, 1024, 1);
      const uint64_t dW0 = mk_desc(sb + SM_RING, 2048, 1024, 1);
      const uint64_t dX0 = mk_desc(sb + SM_RING + 8192, 512, 512, 2);
      auto adv = [&]() { prev = slot; if (++slot == NST) { slot = 0; ph ^= 1; } };
      auto release = [&](uint32_t s) { if (lane == 0) mbar_arrive(bar + B_EMPTY + 8 * s); };
      auto acquire = [&]() -> bool {
        if (__all_sync(0xffffffffu, mbar_test(bar + B_FULL + 8 * slot, ph))) return true;
        wg_wait<0>();
        release(prev);
        mbar_wait(bar + B_FULL + 8 * slot, ph);
        return false;
      };
      auto peer_begin = [&](int cp) {
        mbar_wait(bar + B_HF + 8 * wg, cp & 1);
        if (leader && cp < 8) mbar_expect_tx(bar + B_HF + 8 * wg, 8192);
        fence_async_smem();
      };
      auto peer_unit = [&](int u) {
        wg_fence();
        wg_ss256<1>(O1, dH0 + 2 * u, dW0 + (uint64_t)(slot * (SLOT >> 4)));
        wg_ss32<1>(O2, dH0 + 2 * u, dX0 + (uint64_t)(slot * (SLOT >> 4)));
        wg_commit();
      };
      auto chunk = [&](auto first_c, const int c) {
        constexpr bool FIRST = decltype(first_c)::value;
        float S[64];
        {
          if (FIRST) mbar_wait(bar + B_XN, 0);
          mbar_wait(bar + B_FULL + 8 * slot, ph);
          if (FIRST) PROF_T(42);
          const uint64_t db = dG0 + (uint64_t)(slot * (SLOT >> 4));
          wg_fence();
          wg_ss128_init<1>(S, dA0, db);
          wg_ss128<1>(S, dA0 + 2, db + 128);
          wg_commit();
          adv();
        }
#pragma unroll 1
        for (int u = 1; u < 18; u++) {
          if (FIRST && !(u & 1)) mbar_wait(bar + B_XN + 8 * (u >> 1), 0);
          const bool rel = acquire();
          const uint64_t da = dA0 + (uint64_t)((u >> 1) * 1024 + (u & 1) * 4);
          const uint64_t db = dG0 + (uint64_t)(slot * (SLOT >> 4));
          wg_fence();
          wg_ss128<1>(S, da, db);
          wg_ss128<1>(S, da + 2, db + 128);
          wg_commit();
          wg_wait<1>();
          if (rel) release(prev);
          adv();
        }
        uint32_t H[16];
        if constexpr (!FIRST) peer_begin(c - 1);
        else { wg_wait<0>(); release(prev); }
        auto P = [&](int u) { if constexpr (!FIRST) { const bool rel = acquire(); peer_unit(u); wg_wait<1>(); if (rel) release(prev); adv(); } };
        auto E = [&](int u) {
#pragma unroll
          for (int i = 8 * u; i < 8 * u + 8; i++) asm volatile("" : "+f"(S[i]), "+f"(S[32 + i])::"memory");
#pragma unroll
          for (int g = 2 * u; g < 2 * u + 2; g++) {
            H[2 * g] = pack_bf16(geglu(S[4 * g], S[32 + 4 * g]), geglu(S[4 * g + 1], S[33 + 4 * g]));
            H[2 * g + 1] = pack_bf16(geglu(S[4 * g + 2], S[34 + 4 * g]), geglu(S[4 * g + 3], S[35 + 4 * g]));
          }
#pragma unroll
          for (int i = 4 * u; i < 4 * u + 4; i++) asm volatile("" : "+r"(H[i])::"memory");
        };
        auto O = [&](int u) {
          bool rel;
          if (FIRST && u == 0) { mbar_wait(bar + B_FULL + 8 * slot, ph); rel = false; } else rel = acquire();
          wg_fence();
          wg_rs256<1>(O1, H[4 * u], H[4 * u + 1], H[4 * u + 2], H[4 * u + 3], dW0 + (uint64_t)(slot * (SLOT >> 4)));
          wg_rs32<1>(O2, H[4 * u], H[4 * u + 1], H[4 * u + 2], H[4 * u + 3], dX0 + (uint64_t)(slot * (SLOT >> 4)));
          wg_commit();
          if (u == 3) {
            mbar_wait(bar + B_HE + 8 * wg, c & 1);
            st_async_v4(r_hin, H[0], H[2], H[4], H[6], r_hf);
            st_async_v4(r_hin ^ 64, H[8], H[10], H[12], H[14], r_hf);
            st_async_v4(r_hin + 1024, H[1], H[3], H[5], H[7], r_hf);
            st_async_v4((r_hin ^ 64) + 1024, H[9], H[11], H[13], H[15], r_hf);
            named_bar(3, 256);
          }
          wg_wait<1>();
          if (rel) release(prev);
          if (u == 1) { if constexpr (!FIRST) { if (leader) mbar_arrive_remote(r_he); } }
          if (u == 3) { wg_wait<0>(); release(slot); }
          adv();
        };
        P(0); E(0); P(1); E(1); P(2); O(0); E(2); P(3); O(1); E(3); O(2); O(3);
        PROF_T(4 + 4 * c);
      };
      chunk(std::true_type{}, 0);
#pragma unroll 1
      for (int c = 1; c < 9; c++) chunk(std::false_type{}, c);
      peer_begin(8);
#pragma unroll 1
      for (int u = 0; u < 4; u++) { mbar_wait(bar + B_FULL + 8 * slot, ph); peer_unit(u); adv(); }
      wg_wait<0>();
      reg_fence(O1); reg_fence(O2);
      PROF_T(40);
      const int mi = lane >> 3, li = lane & 7;
      {
        const int row = 16 * w + 8 * (mi & 1) + li;
        const uint32_t stg = sb + SM_XN + wg * 8192 + row * 128;
#pragma unroll
        for (int g = 0; g < 32; g += 2)
          stmatrix_x4(stg + (g >> 3) * 16384 + ((((g & 7) + (mi >> 1)) ^ li) << 4), pack_bf16(O1[4 * g], O1[4 * g + 1]), pack_bf16(O1[4 * g + 2], O1[4 * g + 3]),
                      pack_bf16(O1[4 * g + 4], O1[4 * g + 5]), pack_bf16(O1[4 * g + 6], O1[4 * g + 7]));
#pragma unroll
        for (int g = 0; g < 4; g += 2)
          stmatrix_x4(stg + 65536 - row * 64 + (((g + (mi >> 1)) ^ (li >> 1)) << 4), pack_bf16(O2[4 * g], O2[4 * g + 1]), pack_bf16(O2[4 * g + 2], O2[4 * g + 3]),
                      pack_bf16(O2[4 * g + 4], O2[4 * g + 5]), pack_bf16(O2[4 * g + 6], O2[4 * g + 7]));
        fence_async_smem();
        named_bar(1 + wg, 128);
        if (leader) mbar_arrive(bar + B_SG);
      }
      mbar_wait(bar + B_CV, 0);
      PROF_T(43);
      conv2(sb, wg, w, lane, blockIdx.x * 4 + 2 * wg, C_Y + (blockIdx.x >> 6));
      PROF_T(44);
      const int w8 = threadIdx.x >> 5, row = 16 * (w8 & 1) + 8 * (mi & 1) + li;
      const uint32_t own = sb + SM_XN + (sp >> 1) * 8192;
      const int nblk = w8 < 4 ? 5 : 4;
      named_bar(3, 256);
      mbar_wait(bar + B_PT, 0);
#pragma unroll 1
      for (int k = 0; k < nblk; k++) {
        const uint32_t o = k < 4 ? row * 128 + (((2 * k + (mi >> 1)) ^ li) << 4) : row * 64 + (((2 * (w8 >> 1) + (mi >> 1)) ^ (li >> 1)) << 4);
        const uint32_t oa = own + o + (k < 4 ? (w8 >> 1) * 16384 + (sp & 1) * 4096 : 65536 + (sp & 1) * 2048);
        const uint32_t pa = sb + T_PART + o + (k < 4 ? (w8 >> 1) * 4096 : 16384);
        uint32_t r[4];
        float f[8];
        ldmatrix_x4(oa, r);
#pragma unroll
        for (int i = 0; i < 4; i++) { f[2 * i] = bf_lo(r[i]); f[2 * i + 1] = bf_hi(r[i]); }
#pragma unroll
        for (int s = 0; s < 4; s++) {
          ldmatrix_x4(pa + s * IMG, r);
#pragma unroll
          for (int i = 0; i < 4; i++) { f[2 * i] += bf_lo(r[i]); f[2 * i + 1] += bf_hi(r[i]); }
        }
        stmatrix_x4(oa, pack_bf16(f[0], f[1]), pack_bf16(f[2], f[3]), pack_bf16(f[4], f[5]), pack_bf16(f[6], f[7]));
      }
      __syncwarp();
      mbar_wait(bar + B_YT, 0);
      PROF_T(45);
#pragma unroll 1
      for (int k = 0; k < nblk; k++) {
        const uint32_t o = k < 4 ? row * 128 + (((2 * k + (mi >> 1)) ^ li) << 4) : row * 64 + (((2 * (w8 >> 1) + (mi >> 1)) ^ (li >> 1)) << 4);
        const uint32_t oa = own + o + (k < 4 ? (w8 >> 1) * 16384 + (sp & 1) * 4096 : 65536 + (sp & 1) * 2048);
        const int chl = (k < 4 ? 64 * (w8 >> 1) + 16 * k : 256 + 16 * (w8 >> 1)) + 8 * (mi >> 1) + li;
        uint32_t r[4], y0, y1, y2, y3;
        ldmatrix_x4(oa, r);
        ldmatrix_x4_t(sb + T_YT + chl * 64 + (((2 * (w8 & 1) + (mi & 1)) ^ (li >> 1)) << 4), y0, y1, y2, y3);
        stmatrix_x4(oa, pack_bf16(bf_lo(r[0]) + bf_lo(y0), bf_hi(r[0]) + bf_hi(y0)), pack_bf16(bf_lo(r[1]) + bf_lo(y1), bf_hi(r[1]) + bf_hi(y1)),
                    pack_bf16(bf_lo(r[2]) + bf_lo(y2), bf_hi(r[2]) + bf_hi(y2)), pack_bf16(bf_lo(r[3]) + bf_lo(y3), bf_hi(r[3]) + bf_hi(y3)));
      }
      fence_async_smem();
      named_bar(3, 256);
      if (threadIdx.x < 5) {
        if (threadIdx.x < 4) tma_store_2d(&p.out, own + threadIdx.x * 16384 + (sp & 1) * 4096, 256 * j + 64 * threadIdx.x, mt * 128 + 32 * sp);
        else tma_store_2d(&p.out5, own + 65536 + (sp & 1) * 2048, 512 + 32 * j, mt * 128 + 32 * sp);
        asm volatile("cp.async.bulk.commit_group;" ::: "memory");
        asm volatile("cp.async.bulk.wait_group.read 0;" ::: "memory");
      }
      PROF_T(46);
    } else {
#pragma unroll 1
      for (int grp = 0; grp < 4; grp++) {
        mbar_wait(bar + B_CV, grp & 1);
        conv2(sb, wg, w, lane, 512 + ((int)blockIdx.x - 128) * 16 + grp * 4 + 2 * wg, C_Y5);
        if (t == 0) mbar_arrive(bar + B_SG);
      }
      PROF_T(46);
    }
  }
}

typedef CUresult (*PFN_enc)(CUtensorMap*, CUtensorMapDataType, cuuint32_t, void*, const cuuint64_t*, const cuuint64_t*, const cuuint32_t*,
                            const cuuint32_t*, CUtensorMapInterleave, CUtensorMapSwizzle, CUtensorMapL2promotion, CUtensorMapFloatOOBfill);

void enc(PFN_enc fn, CUtensorMap* m, void* ptr, int rank, const cuuint64_t* dims, const cuuint64_t* strides, const cuuint32_t* box, CUtensorMapSwizzle sw) {
  cuuint32_t es[5] = {1, 1, 1, 1, 1};
  fn(m, CU_TENSOR_MAP_DATA_TYPE_BFLOAT16, rank, ptr, dims, strides, box, es, CU_TENSOR_MAP_INTERLEAVE_NONE, sw,
     CU_TENSOR_MAP_L2_PROMOTION_L2_128B, CU_TENSOR_MAP_FLOAT_OOB_FILL_NONE);
}

}

extern "C" void kernel_launch(void* const* d_in, const int* in_sizes, int n_in, void* d_out, int out_size) {
  static Params pr;
  static void* key[5] = {nullptr, nullptr, nullptr, nullptr, nullptr};
  if (key[0] != d_in[8] || key[1] != d_in[9] || key[2] != d_in[10] || key[3] != d_in[0] || key[4] != d_out) {
    key[0] = d_in[8]; key[1] = d_in[9]; key[2] = d_in[10]; key[3] = d_in[0]; key[4] = d_out;
    void* fnp = nullptr; cudaDriverEntryPointQueryResult st;
    cudaGetDriverEntryPoint("cuTensorMapEncodeTiled", &fnp, cudaEnableDefault, &st);
    PFN_enc fn = (PFN_enc)fnp;
    void *p_xn, *p_y;
    cudaGetSymbolAddress(&p_xn, g_xn); cudaGetSymbolAddress(&p_y, g_y);
    { cuuint64_t d[2] = {D_, L_}, s[1] = {D_ * 2};
      { cuuint32_t b[2] = {64, 128}; enc(fn, &pr.xn, p_xn, 2, d, s, b, CU_TENSOR_MAP_SWIZZLE_128B); }
      { cuuint32_t b[2] = {64, 32}; enc(fn, &pr.x, d_in[0], 2, d, s, b, CU_TENSOR_MAP_SWIZZLE_128B); enc(fn, &pr.out, d_out, 2, d, s, b, CU_TENSOR_MAP_SWIZZLE_128B); }
      { cuuint32_t b[2] = {32, 32}; enc(fn, &pr.x5, d_in[0], 2, d, s, b, CU_TENSOR_MAP_SWIZZLE_64B); enc(fn, &pr.out5, d_out, 2, d, s, b, CU_TENSOR_MAP_SWIZZLE_64B); } }
    { cuuint64_t d[2] = {F_, D_}, s[1] = {F_ * 2}; cuuint32_t b[2] = {64, 32};
      enc(fn, &pr.gate, d_in[8], 2, d, s, b, CU_TENSOR_MAP_SWIZZLE_128B); enc(fn, &pr.up, d_in[9], 2, d, s, b, CU_TENSOR_MAP_SWIZZLE_128B); }
    { void* wd = d_in[10];
      { cuuint64_t d[3] = {64, F_, 9}, s[2] = {D_ * 2, 128}; cuuint32_t b[3] = {64, 16, 4}; enc(fn, &pr.dn, wd, 3, d, s, b, CU_TENSOR_MAP_SWIZZLE_128B); }
      { cuuint64_t d[2] = {D_, F_}, s[1] = {D_ * 2}; cuuint32_t b[2] = {32, 16}; enc(fn, &pr.dn5, wd, 2, d, s, b, CU_TENSOR_MAP_SWIZZLE_64B); }
      { cuuint64_t d[5] = {64, 2, F_ / 8, 4, 9}, s[4] = {D_ * 2, D_ * 16, D_ * 4, 128}; cuuint32_t b[5] = {64, 2, 4, 2, 4};
        enc(fn, &pr.dp, wd, 5, d, s, b, CU_TENSOR_MAP_SWIZZLE_128B); }
      { cuuint64_t d[4] = {D_, 2, F_ / 8, 4}, s[3] = {D_ * 2, D_ * 16, D_ * 4}; cuuint32_t b[4] = {32, 2, 4, 2};
        enc(fn, &pr.dp5, wd, 4, d, s, b, CU_TENSOR_MAP_SWIZZLE_64B); }
    }
    { cuuint64_t d[2] = {L_, D_}, s[1] = {L_ * 2};
      { cuuint32_t b[2] = {32, 256}; enc(fn, &pr.y, p_y, 2, d, s, b, CU_TENSOR_MAP_SWIZZLE_64B); }
      { cuuint32_t b[2] = {32, 32}; enc(fn, &pr.y5, p_y, 2, d, s, b, CU_TENSOR_MAP_SWIZZLE_64B); } }
    cudaFuncSetAttribute(fused_kernel, cudaFuncAttributeMaxDynamicSharedMemorySize, SMEM_BYTES);
  }
  const __nv_bfloat16* const* in = (const __nv_bfloat16* const*)d_in;
  pr.xp = in[0]; pr.logA = in[1]; pr.Aim = in[2]; pr.Cre = in[3]; pr.Cim = in[4]; pr.logdt = in[5]; pr.Dsk = in[6];
  fused_kernel<<<132, 384, SMEM_BYTES>>>(pr);
}
```

```cpp
#include <cuda_runtime.h>
#include <cuda_bf16.h>
#include <cuda.h>
#include <stdint.h>
#include <stdio.h>
#include <type_traits>
#define CV_BASEOFF 0

namespace {

constexpr int L_ = 2048, D_ = 576, F_ = 4608, NM_ = 128;
constexpr int KP_LEN = 2080;
constexpr int U_LEN = 2176;

__device__ __align__(1024) __nv_bfloat16 g_xn[L_ * D_];
__device__ __align__(1024) __nv_bfloat16 g_u[D_ * U_LEN];
__device__ __align__(1024) uint32_t g_kp[D_ * KP_LEN];
__device__ __align__(1024) unsigned char g_part[32 * 16 * 18432];
__device__ __align__(1024) __nv_bfloat16 g_y[D_ * L_];
__device__ __align__(1024) unsigned int g_cnt[64 * 32];
constexpr int C_LN = 0, C_PART = 16, C_U = 48, C_Y = 49, C_Y5 = 51, C_DONE = 52;

#define PROF_T(idx) do {} while (0)
#define PROF_G(idx) do {} while (0)
#define PROF_DUMP() do {} while (0)
__device__ __forceinline__ uint32_t smem_u32(const void* p) { return (uint32_t)__cvta_generic_to_shared(p); }
__device__ __forceinline__ void mbar_init(uint32_t bar, uint32_t cnt) { asm volatile("mbarrier.init.shared::cta.b64 [%0], %1;" ::"r"(bar), "r"(cnt)); }
__device__ __forceinline__ void mbar_expect_tx(uint32_t bar, uint32_t bytes) { asm volatile("mbarrier.arrive.expect_tx.shared::cta.b64 _, [%0], %1;" ::"r"(bar), "r"(bytes) : "memory"); }
__device__ __forceinline__ void mbar_arrive(uint32_t bar) { asm volatile("mbarrier.arrive.shared::cta.b64 _, [%0];" ::"r"(bar) : "memory"); }
__device__ __forceinline__ void mbar_arrive_remote(uint32_t bar) { asm volatile("mbarrier.arrive.shared::cluster.b64 _, [%0];" ::"r"(bar) : "memory"); }
__device__ __forceinline__ bool mbar_try_wait(uint32_t bar, uint32_t parity) {
  uint32_t ok;
  asm volatile("{\n.reg .pred p;\nmbarrier.try_wait.parity.shared::cta.b64 p, [%1], %2;\nselp.u32 %0, 1, 0, p;\n}" : "=r"(ok) : "r"(bar), "r"(parity) : "memory");
  return ok;
}
__device__ __forceinline__ bool mbar_test(uint32_t bar, uint32_t parity) {
  uint32_t ok;
  asm volatile("{\n.reg .pred p;\nmbarrier.test_wait.parity.shared::cta.b64 p, [%1], %2;\nselp.u32 %0, 1, 0, p;\n}" : "=r"(ok) : "r"(bar), "r"(parity) : "memory");
  return ok;
}
__device__ __forceinline__ void mbar_wait(uint32_t bar, uint32_t parity) {
  asm volatile("{\n.reg .pred p, q;\n.reg .u32 n;\nmov.u32 n, 0;\nLW:\nmbarrier.try_wait.parity.shared::cta.b64 p, [%0], %1;\n"
               "add.u32 n, n, 1;\nsetp.lt.and.u32 q, n, 65536, !p;\n@q bra LW;\n}" ::"r"(bar), "r"(parity) : "memory");
}
__device__ __forceinline__ bool elect_one() {
  uint32_t ok;
  asm volatile("{\n.reg .pred p;\nelect.sync _|p, 0xffffffff;\nselp.u32 %0, 1, 0, p;\n}" : "=r"(ok));
  return ok;
}
__device__ __forceinline__ void tma_2d(uint32_t dst, const CUtensorMap* map, int c0, int c1, uint32_t bar) {
  asm volatile("cp.async.bulk.tensor.2d.shared::cluster.global.mbarrier::complete_tx::bytes [%0], [%1, {%3, %4}], [%2];"
               ::"r"(dst), "l"(map), "r"(bar), "r"(c0), "r"(c1) : "memory");
}
__device__ __forceinline__ void tma_3d(uint32_t dst, const CUtensorMap* map, int c0, int c1, int c2, uint32_t bar) {
  asm volatile("cp.async.bulk.tensor.3d.shared::cluster.global.mbarrier::complete_tx::bytes [%0], [%1, {%3, %4, %5}], [%2];"
               ::"r"(dst), "l"(map), "r"(bar), "r"(c0), "r"(c1), "r"(c2) : "memory");
}
__device__ __forceinline__ void tma_4d(uint32_t dst, const CUtensorMap* map, int c0, int c1, int c2, int c3, uint32_t bar) {
  asm volatile("cp.async.bulk.tensor.4d.shared::cluster.global.mbarrier::complete_tx::bytes [%0], [%1, {%3, %4, %5, %6}], [%2];"
               ::"r"(dst), "l"(map), "r"(bar), "r"(c0), "r"(c1), "r"(c2), "r"(c3) : "memory");
}
__device__ __forceinline__ void tma_5d(uint32_t dst, const CUtensorMap* map, int c0, int c1, int c2, int c3, int c4, uint32_t bar) {
  asm volatile("cp.async.bulk.tensor.5d.shared::cluster.global.mbarrier::complete_tx::bytes [%0], [%1, {%3, %4, %5, %6, %7}], [%2];"
               ::"r"(dst), "l"(map), "r"(bar), "r"(c0), "r"(c1), "r"(c2), "r"(c3), "r"(c4) : "memory");
}
__device__ __forceinline__ void tma_store_3d(const CUtensorMap* map, uint32_t src, int c0, int c1, int c2) {
  asm volatile("cp.async.bulk.tensor.3d.global.shared::cta.bulk_group [%0, {%2, %3, %4}], [%1];"
               ::"l"(map), "r"(src), "r"(c0), "r"(c1), "r"(c2) : "memory");
}
__device__ __forceinline__ void bulk_g2s(uint32_t dst, const void* src, uint32_t bytes, uint32_t bar) {
  asm volatile("cp.async.bulk.shared::cluster.global.mbarrier::complete_tx::bytes [%0], [%1], %2, [%3];"
               ::"r"(dst), "l"(src), "r"(bytes), "r"(bar) : "memory");
}
__device__ __forceinline__ void prefetch_map(const CUtensorMap* m) { asm volatile("prefetch.tensormap [%0];" ::"l"(m) : "memory"); }
__device__ __forceinline__ uint32_t mapa(uint32_t addr, uint32_t rank) { uint32_t r; asm volatile("mapa.shared::cluster.u32 %0, %1, %2;" : "=r"(r) : "r"(addr), "r"(rank)); return r; }
__device__ __forceinline__ void cluster_sync() { asm volatile("barrier.cluster.arrive.release.aligned;\nbarrier.cluster.wait.acquire.aligned;" ::: "memory"); }
__device__ __forceinline__ void fence_async_smem() { asm volatile("fence.proxy.async.shared::cta;" ::: "memory"); }
__device__ __forceinline__ void wg_fence() { asm volatile("wgmma.fence.sync.aligned;" ::: "memory"); }
__device__ __forceinline__ void wg_commit() { asm volatile("wgmma.commit_group.sync.aligned;" ::: "memory"); }
template <int N> __device__ __forceinline__ void wg_wait() { asm volatile("wgmma.wait_group.sync.aligned %0;" ::"n"(N) : "memory"); }
template <int N> __device__ __forceinline__ void reg_fence(float (&d)[N]) {
#pragma unroll
  for (int i = 0; i < N; i++) asm volatile("" : "+f"(d[i])::"memory");
}
__device__ __forceinline__ void named_bar(int id, int n) { asm volatile("bar.sync %0, %1;" ::"r"(id), "r"(n) : "memory"); }
__device__ __forceinline__ uint64_t mk_desc(uint32_t addr, uint32_t lbo, uint32_t sbo, uint32_t sw) {
  return (uint64_t)((addr & 0x3FFFF) >> 4) | ((uint64_t)(lbo >> 4) << 16) | ((uint64_t)(sbo >> 4) << 32) | ((uint64_t)sw << 62);
}
__device__ __forceinline__ uint32_t pack_bf16(float lo, float hi) {
  uint32_t r; asm("cvt.rn.bf16x2.f32 %0, %1, %2;" : "=r"(r) : "f"(hi), "f"(lo)); return r;
}
__device__ __forceinline__ float bf_lo(uint32_t v) { return __uint_as_float(v << 16); }
__device__ __forceinline__ float bf_hi(uint32_t v) { return __uint_as_float(v & 0xffff0000u); }
__device__ __forceinline__ float bf_round(float x) { return __bfloat162float(__float2bfloat16_rn(x)); }
__device__ __forceinline__ void st_async_v4(uint32_t addr, uint32_t a, uint32_t b, uint32_t c, uint32_t d, uint32_t bar) {
  asm volatile("st.async.weak.shared::cluster.mbarrier::complete_tx::bytes.v4.b32 [%0], {%1, %2, %3, %4}, [%5];"
               ::"r"(addr), "r"(a), "r"(b), "r"(c), "r"(d), "r"(bar) : "memory");
}
__device__ __forceinline__ void stmatrix_x4_t(uint32_t addr, uint32_t a, uint32_t b, uint32_t c, uint32_t d) {
  asm volatile("stmatrix.sync.aligned.m8n8.x4.trans.shared.b16 [%0], {%1, %2, %3, %4};" ::"r"(addr), "r"(a), "r"(b), "r"(c), "r"(d) : "memory");
}
__device__ __forceinline__ void ldmatrix_x4_t(uint32_t addr, uint32_t& a, uint32_t& b, uint32_t& c, uint32_t& d) {
  asm volatile("ldmatrix.sync.aligned.m8n8.x4.trans.shared.b16 {%0, %1, %2, %3}, [%4];" : "=r"(a), "=r"(b), "=r"(c), "=r"(d) : "r"(addr) : "memory");
}
__device__ __forceinline__ uint32_t lds32(uint32_t addr) { uint32_t v; asm volatile("ld.shared.b32 %0, [%1];" : "=r"(v) : "r"(addr) : "memory"); return v; }
__device__ __forceinline__ float geglu(float g, float u) {
  float z = g * fmaf(g * g, 0.0356774081f, 0.7978845608f);
  float t; asm("tanh.approx.f32 %0, %1;" : "=f"(t) : "f"(z));
  return (g * u) * fmaf(t, 0.5f, 0.5f);
}

__device__ __forceinline__ uint4 lds128(uint32_t addr) { uint4 v; asm volatile("ld.shared.v4.b32 {%0,%1,%2,%3}, [%4];" : "=r"(v.x), "=r"(v.y), "=r"(v.z), "=r"(v.w) : "r"(addr) : "memory"); return v; }
__device__ __forceinline__ void sts32(uint32_t addr, uint32_t v) { asm volatile("st.shared.b32 [%0], %1;" ::"r"(addr), "r"(v) : "memory"); }
__device__ __forceinline__ void stmatrix_x4(uint32_t addr, uint32_t a, uint32_t b, uint32_t c, uint32_t d) {
  asm volatile("stmatrix.sync.aligned.m8n8.x4.shared.b16 [%0], {%1, %2, %3, %4};" ::"r"(addr), "r"(a), "r"(b), "r"(c), "r"(d) : "memory");
}
__device__ __forceinline__ void ldmatrix_x4(uint32_t addr, uint32_t (&r)[4]) {
  asm volatile("ldmatrix.sync.aligned.m8n8.x4.shared.b16 {%0, %1, %2, %3}, [%4];" : "=r"(r[0]), "=r"(r[1]), "=r"(r[2]), "=r"(r[3]) : "r"(addr) : "memory");
}
__device__ __forceinline__ void sts128(uint32_t addr, uint4 v) { asm volatile("st.shared.v4.b32 [%0], {%1,%2,%3,%4};" ::"r"(addr), "r"(v.x), "r"(v.y), "r"(v.z), "r"(v.w) : "memory"); }
__device__ __forceinline__ void bulk_s2g(void* dst, uint32_t src, uint32_t bytes) {
  asm volatile("cp.async.bulk.global.shared::cta.bulk_group [%0], [%1], %2;" ::"l"(dst), "r"(src), "r"(bytes) : "memory");
}
__device__ __forceinline__ void tma_store_2d(const CUtensorMap* map, uint32_t src, int c0, int c1) {
  asm volatile("cp.async.bulk.tensor.2d.global.shared::cta.bulk_group [%0, {%2, %3}], [%1];" ::"l"(map), "r"(src), "r"(c0), "r"(c1) : "memory");
}
__device__ __forceinline__ void bulk_commit_wait() {
  asm volatile("cp.async.bulk.commit_group;" ::: "memory");
  asm volatile("cp.async.bulk.wait_group 0;" ::: "memory");
}
__device__ __forceinline__ void named_arrive(int id, int n) { asm volatile("bar.arrive %0, %1;" ::"r"(id), "r"(n) : "memory"); }
__device__ __forceinline__ void fence_async_all() { asm volatile("fence.proxy.async.global;" ::: "memory"); }
__device__ __forceinline__ void cnt_add(int idx) {
  asm volatile("red.release.gpu.global.add.u32 [%0], 1;" ::"l"(g_cnt + idx * 32) : "memory");
}
__device__ __forceinline__ void cnt_add_done(int idx) {
  asm volatile("red.relaxed.gpu.global.add.u32 [%0], 1;" ::"l"(g_cnt + idx * 32) : "memory");
}
__device__ __forceinline__ void cnt_wait(int idx, uint32_t target) {
  const unsigned int* p = g_cnt + idx * 32;
#pragma unroll 1
  for (int it = 0; it < (1 << 18); it++) {
    uint32_t v; asm volatile("ld.acquire.gpu.global.u32 %0, [%1];" : "=r"(v) : "l"(p) : "memory");
    if (v >= target) break;
    __nanosleep(20);
  }
}
__device__ __forceinline__ void prefetch_l2(const void* p, uint32_t bytes) { asm volatile("cp.async.bulk.prefetch.L2.global [%0], %1;" ::"l"(p), "r"(bytes) : "memory"); }

template <int TB>
__device__ __forceinline__ void wg_ss128_init(float (&d)[64], uint64_t da, uint64_t db) {
  asm volatile(
    "wgmma.mma_async.sync.aligned.m64n128k16.f32.bf16.bf16 {%0, %1, %2, %3, %4, %5, %6, %7, %8, %9, %10, %11, %12, %13, %14, %15, %16, %17, %18, %19, %20, %21, %22, %23, %24, %25, %26, %27, %28, %29, %30, %31, %32, %33, %34, %35, %36, %37, %38, %39, %40, %41, %42, %43, %44, %45, %46, %47, %48, %49, %50, %51, %52, %53, %54, %55, %56, %57, %58, %59, %60, %61, %62, %63}, %64, %65, 0, 1, 1, 0, %66;"
    : "=f"(d[0]), "=f"(d[1]), "=f"(d[2]), "=f"(d[3]), "=f"(d[4]), "=f"(d[5]), "=f"(d[6]), "=f"(d[7]), "=f"(d[8]), "=f"(d[9]), "=f"(d[10]), "=f"(d[11]), "=f"(d[12]), "=f"(d[13]), "=f"(d[14]), "=f"(d[15]), "=f"(d[16]), "=f"(d[17]), "=f"(d[18]), "=f"(d[19]), "=f"(d[20]), "=f"(d[21]), "=f"(d[22]), "=f"(d[23]), "=f"(d[24]), "=f"(d[25]), "=f"(d[26]), "=f"(d[27]), "=f"(d[28]), "=f"(d[29]), "=f"(d[30]), "=f"(d[31]), "=f"(d[32]), "=f"(d[33]), "=f"(d[34]), "=f"(d[35]), "=f"(d[36]), "=f"(d[37]), "=f"(d[38]), "=f"(d[39]), "=f"(d[40]), "=f"(d[41]), "=f"(d[42]), "=f"(d[43]), "=f"(d[44]), "=f"(d[45]), "=f"(d[46]), "=f"(d[47]), "=f"(d[48]), "=f"(d[49]), "=f"(d[50]), "=f"(d[51]), "=f"(d[52]), "=f"(d[53]), "=f"(d[54]), "=f"(d[55]), "=f"(d[56]), "=f"(d[57]), "=f"(d[58]), "=f"(d[59]), "=f"(d[60]), "=f"(d[61]), "=f"(d[62]), "=f"(d[63])
    : "l"(da), "l"(db), "n"(TB));
}
template <int TB>
__device__ __forceinline__ void wg_ss128(float (&d)[64], uint64_t da, uint64_t db) {
  asm volatile(
    "wgmma.mma_async.sync.aligned.m64n128k16.f32.bf16.bf16 {%0, %1, %2, %3, %4, %5, %6, %7, %8, %9, %10, %11, %12, %13, %14, %15, %16, %17, %18, %19, %20, %21, %22, %23, %24, %25, %26, %27, %28, %29, %30, %31, %32, %33, %34, %35, %36, %37, %38, %39, %40, %41, %42, %43, %44, %45, %46, %47, %48, %49, %50, %51, %52, %53, %54, %55, %56, %57, %58, %59, %60, %61, %62, %63}, %64, %65, 1, 1, 1, 0, %66;"
    : "+f"(d[0]), "+f"(d[1]), "+f"(d[2]), "+f"(d[3]), "+f"(d[4]), "+f"(d[5]), "+f"(d[6]), "+f"(d[7]), "+f"(d[8]), "+f"(d[9]), "+f"(d[10]), "+f"(d[11]), "+f"(d[12]), "+f"(d[13]), "+f"(d[14]), "+f"(d[15]), "+f"(d[16]), "+f"(d[17]), "+f"(d[18]), "+f"(d[19]), "+f"(d[20]), "+f"(d[21]), "+f"(d[22]), "+f"(d[23]), "+f"(d[24]), "+f"(d[25]), "+f"(d[26]), "+f"(d[27]), "+f"(d[28]), "+f"(d[29]), "+f"(d[30]), "+f"(d[31]), "+f"(d[32]), "+f"(d[33]), "+f"(d[34]), "+f"(d[35]), "+f"(d[36]), "+f"(d[37]), "+f"(d[38]), "+f"(d[39]), "+f"(d[40]), "+f"(d[41]), "+f"(d[42]), "+f"(d[43]), "+f"(d[44]), "+f"(d[45]), "+f"(d[46]), "+f"(d[47]), "+f"(d[48]), "+f"(d[49]), "+f"(d[50]), "+f"(d[51]), "+f"(d[52]), "+f"(d[53]), "+f"(d[54]), "+f"(d[55]), "+f"(d[56]), "+f"(d[57]), "+f"(d[58]), "+f"(d[59]), "+f"(d[60]), "+f"(d[61]), "+f"(d[62]), "+f"(d[63])
    : "l"(da), "l"(db), "n"(TB));
}
template <int TB>
__device__ __forceinline__ void wg_ss256(float (&d)[128], uint64_t da, uint64_t db) {
  asm volatile(
    "wgmma.mma_async.sync.aligned.m64n256k16.f32.bf16.bf16 {%0, %1, %2, %3, %4, %5, %6, %7, %8, %9, %10, %11, %12, %13, %14, %15, %16, %17, %18, %19, %20, %21, %22, %23, %24, %25, %26, %27, %28, %29, %30, %31, %32, %33, %34, %35, %36, %37, %38, %39, %40, %41, %42, %43, %44, %45, %46, %47, %48, %49, %50, %51, %52, %53, %54, %55, %56, %57, %58, %59, %60, %61, %62, %63, %64, %65, %66, %67, %68, %69, %70, %71, %72, %73, %74, %75, %76, %77, %78, %79, %80, %81, %82, %83, %84, %85, %86, %87, %88, %89, %90, %91, %92, %93, %94, %95, %96, %97, %98, %99, %100, %101, %102, %103, %104, %105, %106, %107, %108, %109, %110, %111, %112, %113, %114, %115, %116, %117, %118, %119, %120, %121, %122, %123, %124, %125, %126, %127}, %128, %129, 1, 1, 1, 0, %130;"
    : "+f"(d[0]), "+f"(d[1]), "+f"(d[2]), "+f"(d[3]), "+f"(d[4]), "+f"(d[5]), "+f"(d[6]), "+f"(d[7]), "+f"(d[8]), "+f"(d[9]), "+f"(d[10]), "+f"(d[11]), "+f"(d[12]), "+f"(d[13]), "+f"(d[14]), "+f"(d[15]), "+f"(d[16]), "+f"(d[17]), "+f"(d[18]), "+f"(d[19]), "+f"(d[20]), "+f"(d[21]), "+f"(d[22]), "+f"(d[23]), "+f"(d[24]), "+f"(d[25]), "+f"(d[26]), "+f"(d[27]), "+f"(d[28]), "+f"(d[29]), "+f"(d[30]), "+f"(d[31]), "+f"(d[32]), "+f"(d[33]), "+f"(d[34]), "+f"(d[35]), "+f"(d[36]), "+f"(d[37]), "+f"(d[38]), "+f"(d[39]), "+f"(d[40]), "+f"(d[41]), "+f"(d[42]), "+f"(d[43]), "+f"(d[44]), "+f"(d[45]), "+f"(d[46]), "+f"(d[47]), "+f"(d[48]), "+f"(d[49]), "+f"(d[50]), "+f"(d[51]), "+f"(d[52]), "+f"(d[53]), "+f"(d[54]), "+f"(d[55]), "+f"(d[56]), "+f"(d[57]), "+f"(d[58]), "+f"(d[59]), "+f"(d[60]), "+f"(d[61]), "+f"(d[62]), "+f"(d[63]), "+f"(d[64]), "+f"(d[65]), "+f"(d[66]), "+f"(d[67]), "+f"(d[68]), "+f"(d[69]), "+f"(d[70]), "+f"(d[71]), "+f"(d[72]), "+f"(d[73]), "+f"(d[74]), "+f"(d[75]), "+f"(d[76]), "+f"(d[77]), "+f"(d[78]), "+f"(d[79]), "+f"(d[80]), "+f"(d[81]), "+f"(d[82]), "+f"(d[83]), "+f"(d[84]), "+f"(d[85]), "+f"(d[86]), "+f"(d[87]), "+f"(d[88]), "+f"(d[89]), "+f"(d[90]), "+f"(d[91]), "+f"(d[92]), "+f"(d[93]), "+f"(d[94]), "+f"(d[95]), "+f"(d[96]), "+f"(d[97]), "+f"(d[98]), "+f"(d[99]), "+f"(d[100]), "+f"(d[101]), "+f"(d[102]), "+f"(d[103]), "+f"(d[104]), "+f"(d[105]), "+f"(d[106]), "+f"(d[107]), "+f"(d[108]), "+f"(d[109]), "+f"(d[110]), "+f"(d[111]), "+f"(d[112]), "+f"(d[113]), "+f"(d[114]), "+f"(d[115]), "+f"(d[116]), "+f"(d[117]), "+f"(d[118]), "+f"(d[119]), "+f"(d[120]), "+f"(d[121]), "+f"(d[122]), "+f"(d[123]), "+f"(d[124]), "+f"(d[125]), "+f"(d[126]), "+f"(d[127])
    : "l"(da), "l"(db), "n"(TB));
}
template <int TB>
__device__ __forceinline__ void wg_ss32(float (&d)[16], uint64_t da, uint64_t db) {
  asm volatile(
    "wgmma.mma_async.sync.aligned.m64n32k16.f32.bf16.bf16 {%0, %1, %2, %3, %4, %5, %6, %7, %8, %9, %10, %11, %12, %13, %14, %15}, %16, %17, 1, 1, 1, 0, %18;"
    : "+f"(d[0]), "+f"(d[1]), "+f"(d[2]), "+f"(d[3]), "+f"(d[4]), "+f"(d[5]), "+f"(d[6]), "+f"(d[7]), "+f"(d[8]), "+f"(d[9]), "+f"(d[10]), "+f"(d[11]), "+f"(d[12]), "+f"(d[13]), "+f"(d[14]), "+f"(d[15])
    : "l"(da), "l"(db), "n"(TB));
}
template <int TB>
__device__ __forceinline__ void wg_rs256(float (&d)[128], uint32_t a0, uint32_t a1, uint32_t a2, uint32_t a3, uint64_t db) {
  asm volatile(
    "wgmma.mma_async.sync.aligned.m64n256k16.f32.bf16.bf16 {%0, %1, %2, %3, %4, %5, %6, %7, %8, %9, %10, %11, %12, %13, %14, %15, %16, %17, %18, %19, %20, %21, %22, %23, %24, %25, %26, %27, %28, %29, %30, %31, %32, %33, %34, %35, %36, %37, %38, %39, %40, %41, %42, %43, %44, %45, %46, %47, %48, %49, %50, %51, %52, %53, %54, %55, %56, %57, %58, %59, %60, %61, %62, %63, %64, %65, %66, %67, %68, %69, %70, %71, %72, %73, %74, %75, %76, %77, %78, %79, %80, %81, %82, %83, %84, %85, %86, %87, %88, %89, %90, %91, %92, %93, %94, %95, %96, %97, %98, %99, %100, %101, %102, %103, %104, %105, %106, %107, %108, %109, %110, %111, %112, %113, %114, %115, %116, %117, %118, %119, %120, %121, %122, %123, %124, %125, %126, %127}, {%128, %129, %130, %131}, %132, 1, 1, 1, %133;"
    : "+f"(d[0]), "+f"(d[1]), "+f"(d[2]), "+f"(d[3]), "+f"(d[4]), "+f"(d[5]), "+f"(d[6]), "+f"(d[7]), "+f"(d[8]), "+f"(d[9]), "+f"(d[10]), "+f"(d[11]), "+f"(d[12]), "+f"(d[13]), "+f"(d[14]), "+f"(d[15]), "+f"(d[16]), "+f"(d[17]), "+f"(d[18]), "+f"(d[19]), "+f"(d[20]), "+f"(d[21]), "+f"(d[22]), "+f"(d[23]), "+f"(d[24]), "+f"(d[25]), "+f"(d[26]), "+f"(d[27]), "+f"(d[28]), "+f"(d[29]), "+f"(d[30]), "+f"(d[31]), "+f"(d[32]), "+f"(d[33]), "+f"(d[34]), "+f"(d[35]), "+f"(d[36]), "+f"(d[37]), "+f"(d[38]), "+f"(d[39]), "+f"(d[40]), "+f"(d[41]), "+f"(d[42]), "+f"(d[43]), "+f"(d[44]), "+f"(d[45]), "+f"(d[46]), "+f"(d[47]), "+f"(d[48]), "+f"(d[49]), "+f"(d[50]), "+f"(d[51]), "+f"(d[52]), "+f"(d[53]), "+f"(d[54]), "+f"(d[55]), "+f"(d[56]), "+f"(d[57]), "+f"(d[58]), "+f"(d[59]), "+f"(d[60]), "+f"(d[61]), "+f"(d[62]), "+f"(d[63]), "+f"(d[64]), "+f"(d[65]), "+f"(d[66]), "+f"(d[67]), "+f"(d[68]), "+f"(d[69]), "+f"(d[70]), "+f"(d[71]), "+f"(d[72]), "+f"(d[73]), "+f"(d[74]), "+f"(d[75]), "+f"(d[76]), "+f"(d[77]), "+f"(d[78]), "+f"(d[79]), "+f"(d[80]), "+f"(d[81]), "+f"(d[82]), "+f"(d[83]), "+f"(d[84]), "+f"(d[85]), "+f"(d[86]), "+f"(d[87]), "+f"(d[88]), "+f"(d[89]), "+f"(d[90]), "+f"(d[91]), "+f"(d[92]), "+f"(d[93]), "+f"(d[94]), "+f"(d[95]), "+f"(d[96]), "+f"(d[97]), "+f"(d[98]), "+f"(d[99]), "+f"(d[100]), "+f"(d[101]), "+f"(d[102]), "+f"(d[103]), "+f"(d[104]), "+f"(d[105]), "+f"(d[106]), "+f"(d[107]), "+f"(d[108]), "+f"(d[109]), "+f"(d[110]), "+f"(d[111]), "+f"(d[112]), "+f"(d[113]), "+f"(d[114]), "+f"(d[115]), "+f"(d[116]), "+f"(d[117]), "+f"(d[118]), "+f"(d[119]), "+f"(d[120]), "+f"(d[121]), "+f"(d[122]), "+f"(d[123]), "+f"(d[124]), "+f"(d[125]), "+f"(d[126]), "+f"(d[127])
    : "r"(a0), "r"(a1), "r"(a2), "r"(a3), "l"(db), "n"(TB));
}
template <int TB>
__device__ __forceinline__ void wg_rs32(float (&d)[16], uint32_t a0, uint32_t a1, uint32_t a2, uint32_t a3, uint64_t db) {
  asm volatile(
    "wgmma.mma_async.sync.aligned.m64n32k16.f32.bf16.bf16 {%0, %1, %2, %3, %4, %5, %6, %7, %8, %9, %10, %11, %12, %13, %14, %15}, {%16, %17, %18, %19}, %20, 1, 1, 1, %21;"
    : "+f"(d[0]), "+f"(d[1]), "+f"(d[2]), "+f"(d[3]), "+f"(d[4]), "+f"(d[5]), "+f"(d[6]), "+f"(d[7]), "+f"(d[8]), "+f"(d[9]), "+f"(d[10]), "+f"(d[11]), "+f"(d[12]), "+f"(d[13]), "+f"(d[14]), "+f"(d[15])
    : "r"(a0), "r"(a1), "r"(a2), "r"(a3), "l"(db), "n"(TB));
}
template <int TB>
__device__ __forceinline__ void wg_cv128(float (&d)[64], uint32_t a0, uint32_t a1, uint32_t a2, uint32_t a3, uint64_t db) {
  asm volatile(
    "wgmma.mma_async.sync.aligned.m64n128k16.f32.bf16.bf16 {%0, %1, %2, %3, %4, %5, %6, %7, %8, %9, %10, %11, %12, %13, %14, %15, %16, %17, %18, %19, %20, %21, %22, %23, %24, %25, %26, %27, %28, %29, %30, %31, %32, %33, %34, %35, %36, %37, %38, %39, %40, %41, %42, %43, %44, %45, %46, %47, %48, %49, %50, %51, %52, %53, %54, %55, %56, %57, %58, %59, %60, %61, %62, %63}, {%64, %65, %66, %67}, %68, 1, 1, 1, %69;"
    : "+f"(d[0]), "+f"(d[1]), "+f"(d[2]), "+f"(d[3]), "+f"(d[4]), "+f"(d[5]), "+f"(d[6]), "+f"(d[7]), "+f"(d[8]), "+f"(d[9]), "+f"(d[10]), "+f"(d[11]), "+f"(d[12]), "+f"(d[13]), "+f"(d[14]), "+f"(d[15]), "+f"(d[16]), "+f"(d[17]), "+f"(d[18]), "+f"(d[19]), "+f"(d[20]), "+f"(d[21]), "+f"(d[22]), "+f"(d[23]), "+f"(d[24]), "+f"(d[25]), "+f"(d[26]), "+f"(d[27]), "+f"(d[28]), "+f"(d[29]), "+f"(d[30]), "+f"(d[31]), "+f"(d[32]), "+f"(d[33]), "+f"(d[34]), "+f"(d[35]), "+f"(d[36]), "+f"(d[37]), "+f"(d[38]), "+f"(d[39]), "+f"(d[40]), "+f"(d[41]), "+f"(d[42]), "+f"(d[43]), "+f"(d[44]), "+f"(d[45]), "+f"(d[46]), "+f"(d[47]), "+f"(d[48]), "+f"(d[49]), "+f"(d[50]), "+f"(d[51]), "+f"(d[52]), "+f"(d[53]), "+f"(d[54]), "+f"(d[55]), "+f"(d[56]), "+f"(d[57]), "+f"(d[58]), "+f"(d[59]), "+f"(d[60]), "+f"(d[61]), "+f"(d[62]), "+f"(d[63])
    : "r"(a0), "r"(a1), "r"(a2), "r"(a3), "l"(db), "n"(TB));
}
template <int TB>
__device__ __forceinline__ void wg_cv96(float (&d)[48], uint32_t a0, uint32_t a1, uint32_t a2, uint32_t a3, uint64_t db) {
  asm volatile(
    "wgmma.mma_async.sync.aligned.m64n96k16.f32.bf16.bf16 {%0, %1, %2, %3, %4, %5, %6, %7, %8, %9, %10, %11, %12, %13, %14, %15, %16, %17, %18, %19, %20, %21, %22, %23, %24, %25, %26, %27, %28, %29, %30, %31, %32, %33, %34, %35, %36, %37, %38, %39, %40, %41, %42, %43, %44, %45, %46, %47}, {%48, %49, %50, %51}, %52, 1, 1, 1, %53;"
    : "+f"(d[0]), "+f"(d[1]), "+f"(d[2]), "+f"(d[3]), "+f"(d[4]), "+f"(d[5]), "+f"(d[6]), "+f"(d[7]), "+f"(d[8]), "+f"(d[9]), "+f"(d[10]), "+f"(d[11]), "+f"(d[12]), "+f"(d[13]), "+f"(d[14]), "+f"(d[15]), "+f"(d[16]), "+f"(d[17]), "+f"(d[18]), "+f"(d[19]), "+f"(d[20]), "+f"(d[21]), "+f"(d[22]), "+f"(d[23]), "+f"(d[24]), "+f"(d[25]), "+f"(d[26]), "+f"(d[27]), "+f"(d[28]), "+f"(d[29]), "+f"(d[30]), "+f"(d[31]), "+f"(d[32]), "+f"(d[33]), "+f"(d[34]), "+f"(d[35]), "+f"(d[36]), "+f"(d[37]), "+f"(d[38]), "+f"(d[39]), "+f"(d[40]), "+f"(d[41]), "+f"(d[42]), "+f"(d[43]), "+f"(d[44]), "+f"(d[45]), "+f"(d[46]), "+f"(d[47])
    : "r"(a0), "r"(a1), "r"(a2), "r"(a3), "l"(db), "n"(TB));
}
template <int TB>
__device__ __forceinline__ void wg_cv64(float (&d)[32], uint32_t a0, uint32_t a1, uint32_t a2, uint32_t a3, uint64_t db) {
  asm volatile(
    "wgmma.mma_async.sync.aligned.m64n64k16.f32.bf16.bf16 {%0, %1, %2, %3, %4, %5, %6, %7, %8, %9, %10, %11, %12, %13, %14, %15, %16, %17, %18, %19, %20, %21, %22, %23, %24, %25, %26, %27, %28, %29, %30, %31}, {%32, %33, %34, %35}, %36, 1, 1, 1, %37;"
    : "+f"(d[0]), "+f"(d[1]), "+f"(d[2]), "+f"(d[3]), "+f"(d[4]), "+f"(d[5]), "+f"(d[6]), "+f"(d[7]), "+f"(d[8]), "+f"(d[9]), "+f"(d[10]), "+f"(d[11]), "+f"(d[12]), "+f"(d[13]), "+f"(d[14]), "+f"(d[15]), "+f"(d[16]), "+f"(d[17]), "+f"(d[18]), "+f"(d[19]), "+f"(d[20]), "+f"(d[21]), "+f"(d[22]), "+f"(d[23]), "+f"(d[24]), "+f"(d[25]), "+f"(d[26]), "+f"(d[27]), "+f"(d[28]), "+f"(d[29]), "+f"(d[30]), "+f"(d[31])
    : "r"(a0), "r"(a1), "r"(a2), "r"(a3), "l"(db), "n"(TB));
}
template <int TB>
__device__ __forceinline__ void wg_rs256_init(float (&d)[128], uint32_t a0, uint32_t a1, uint32_t a2, uint32_t a3, uint64_t db) {
  asm volatile(
    "wgmma.mma_async.sync.aligned.m64n256k16.f32.bf16.bf16 {%0, %1, %2, %3, %4, %5, %6, %7, %8, %9, %10, %11, %12, %13, %14, %15, %16, %17, %18, %19, %20, %21, %22, %23, %24, %25, %26, %27, %28, %29, %30, %31, %32, %33, %34, %35, %36, %37, %38, %39, %40, %41, %42, %43, %44, %45, %46, %47, %48, %49, %50, %51, %52, %53, %54, %55, %56, %57, %58, %59, %60, %61, %62, %63, %64, %65, %66, %67, %68, %69, %70, %71, %72, %73, %74, %75, %76, %77, %78, %79, %80, %81, %82, %83, %84, %85, %86, %87, %88, %89, %90, %91, %92, %93, %94, %95, %96, %97, %98, %99, %100, %101, %102, %103, %104, %105, %106, %107, %108, %109, %110, %111, %112, %113, %114, %115, %116, %117, %118, %119, %120, %121, %122, %123, %124, %125, %126, %127}, {%128, %129, %130, %131}, %132, 0, 1, 1, %133;"
    : "=f"(d[0]), "=f"(d[1]), "=f"(d[2]), "=f"(d[3]), "=f"(d[4]), "=f"(d[5]), "=f"(d[6]), "=f"(d[7]), "=f"(d[8]), "=f"(d[9]), "=f"(d[10]), "=f"(d[11]), "=f"(d[12]), "=f"(d[13]), "=f"(d[14]), "=f"(d[15]), "=f"(d[16]), "=f"(d[17]), "=f"(d[18]), "=f"(d[19]), "=f"(d[20]), "=f"(d[21]), "=f"(d[22]), "=f"(d[23]), "=f"(d[24]), "=f"(d[25]), "=f"(d[26]), "=f"(d[27]), "=f"(d[28]), "=f"(d[29]), "=f"(d[30]), "=f"(d[31]), "=f"(d[32]), "=f"(d[33]), "=f"(d[34]), "=f"(d[35]), "=f"(d[36]), "=f"(d[37]), "=f"(d[38]), "=f"(d[39]), "=f"(d[40]), "=f"(d[41]), "=f"(d[42]), "=f"(d[43]), "=f"(d[44]), "=f"(d[45]), "=f"(d[46]), "=f"(d[47]), "=f"(d[48]), "=f"(d[49]), "=f"(d[50]), "=f"(d[51]), "=f"(d[52]), "=f"(d[53]), "=f"(d[54]), "=f"(d[55]), "=f"(d[56]), "=f"(d[57]), "=f"(d[58]), "=f"(d[59]), "=f"(d[60]), "=f"(d[61]), "=f"(d[62]), "=f"(d[63]), "=f"(d[64]), "=f"(d[65]), "=f"(d[66]), "=f"(d[67]), "=f"(d[68]), "=f"(d[69]), "=f"(d[70]), "=f"(d[71]), "=f"(d[72]), "=f"(d[73]), "=f"(d[74]), "=f"(d[75]), "=f"(d[76]), "=f"(d[77]), "=f"(d[78]), "=f"(d[79]), "=f"(d[80]), "=f"(d[81]), "=f"(d[82]), "=f"(d[83]), "=f"(d[84]), "=f"(d[85]), "=f"(d[86]), "=f"(d[87]), "=f"(d[88]), "=f"(d[89]), "=f"(d[90]), "=f"(d[91]), "=f"(d[92]), "=f"(d[93]), "=f"(d[94]), "=f"(d[95]), "=f"(d[96]), "=f"(d[97]), "=f"(d[98]), "=f"(d[99]), "=f"(d[100]), "=f"(d[101]), "=f"(d[102]), "=f"(d[103]), "=f"(d[104]), "=f"(d[105]), "=f"(d[106]), "=f"(d[107]), "=f"(d[108]), "=f"(d[109]), "=f"(d[110]), "=f"(d[111]), "=f"(d[112]), "=f"(d[113]), "=f"(d[114]), "=f"(d[115]), "=f"(d[116]), "=f"(d[117]), "=f"(d[118]), "=f"(d[119]), "=f"(d[120]), "=f"(d[121]), "=f"(d[122]), "=f"(d[123]), "=f"(d[124]), "=f"(d[125]), "=f"(d[126]), "=f"(d[127])
    : "r"(a0), "r"(a1), "r"(a2), "r"(a3), "l"(db), "n"(TB));
}
template <int TB>
__device__ __forceinline__ void wg_rs32_init(float (&d)[16], uint32_t a0, uint32_t a1, uint32_t a2, uint32_t a3, uint64_t db) {
  asm volatile(
    "wgmma.mma_async.sync.aligned.m64n32k16.f32.bf16.bf16 {%0, %1, %2, %3, %4, %5, %6, %7, %8, %9, %10, %11, %12, %13, %14, %15}, {%16, %17, %18, %19}, %20, 0, 1, 1, %21;"
    : "=f"(d[0]), "=f"(d[1]), "=f"(d[2]), "=f"(d[3]), "=f"(d[4]), "=f"(d[5]), "=f"(d[6]), "=f"(d[7]), "=f"(d[8]), "=f"(d[9]), "=f"(d[10]), "=f"(d[11]), "=f"(d[12]), "=f"(d[13]), "=f"(d[14]), "=f"(d[15])
    : "r"(a0), "r"(a1), "r"(a2), "r"(a3), "l"(db), "n"(TB));
}

constexpr int NST = 7, SLOT = 9216;
constexpr uint32_t SM_XN = 0, SM_HIN = 147456, SM_RING = 163840, SM_BAR = SM_RING + NST * SLOT;
constexpr uint32_t SM_KD = SM_BAR + 256, SMEM_BYTES = SM_KD + 3840;
constexpr uint32_t B_FULL = 0, B_EMPTY = 56, B_XN = 112, B_K2048 = 176, B_HF = 184, B_HE = 200, B_CV = 216, B_PT = 224, B_YT = 232, B_SG = 240, B_X = 248;
constexpr uint32_t PR_LN = 114688;
constexpr uint32_t T_U = 81920, T_KP = 99328, T_YT = 81920, T_PART = SM_HIN;
constexpr uint32_t U_BYTES = U_LEN * 2, KP_BYTES = KP_LEN * 4, IMG = 18432;

struct Params {
  CUtensorMap xn, gate, up, dn, dn5, dp, dp5, x, x5, y, y5, out, out5;
  const __nv_bfloat16 *xp, *logA, *Aim, *Cre, *Cim, *logdt, *Dsk;
};

__device__ __forceinline__ float us2f(uint32_t v) { return __uint_as_float(v << 16); }
struct KgIn { uint32_t la, ai, cr, ci, ldt, dsk; };
__device__ __forceinline__ void kgen_load(const Params& p, int ch0, int tid, KgIn& in) {
  const int e = ch0 * (NM_ / 2) + tid;
  in.la = __ldg((const uint32_t*)p.logA + e); in.ai = __ldg((const uint32_t*)p.Aim + e);
  in.cr = __ldg((const uint32_t*)p.Cre + e); in.ci = __ldg((const uint32_t*)p.Cim + e);
  in.ldt = __ldg((const unsigned short*)p.logdt + ch0 + (tid >> 6)); in.dsk = __ldg((const unsigned short*)p.Dsk + ch0 + (tid >> 6));
}
struct KgState { float acc[5][4]; float v, j1, j2; const float4* par; };
__device__ __forceinline__ void kgen_params(unsigned char* scr, int tid, KgIn in, KgState& st) {
  const int warp = tid >> 5, lane = tid & 31;
  float4* par = (float4*)(scr + (warp >> 1) * 4096 + 272 + (warp & 1) * 1024);
  const float dt = bf_round(expf(bf_lo(in.ldt)));
  float v = 0.f;
#pragma unroll 1
  for (int r = 0; r < 2; r++) {
    const float are = -bf_round(expf(bf_lo(in.la))) * dt * 1.4426950408889634f;
    float w = bf_lo(in.ai) * dt * 0.15915494309189535f;
    const float cr = 2.f * bf_lo(in.cr) * dt, ci = 2.f * bf_lo(in.ci) * dt;
    float we = 2048.f * w; we = (we - rintf(we)) * 6.283185307179586f;
    w -= rintf(w);
    par[2 * lane + r] = make_float4(are, w * 6.283185307179586f, cr, ci);
    float m; asm("ex2.approx.ftz.f32 %0, %1;" : "=f"(m) : "f"(are * 2048.f));
    v = fmaf(m, cr * __cosf(we) - ci * __sinf(we), v);
    in.la >>= 16; in.ai >>= 16; in.cr >>= 16; in.ci >>= 16;
  }
#pragma unroll
  for (int o = 16; o; o >>= 1) v += __shfl_xor_sync(0xffffffffu, v, o);
  __syncwarp();
#pragma unroll
  for (int t = 0; t < 5; t++) { st.acc[t][0] = st.acc[t][1] = st.acc[t][2] = st.acc[t][3] = 0.f; }
  if (lane == 0 && !(warp & 1)) st.acc[0][0] = bf_lo(in.dsk);
  st.v = v; st.j1 = (float)(lane >> 2); st.j2 = st.j1 + 8.f; st.par = par + (lane & 3);
}
__device__ __forceinline__ void kgen_step(KgState& st, int ks) {
  const float4 pr = st.par[ks * 4];
  float r1, i1, r2, i2;
  {
    float m1, m2;
    asm("ex2.approx.ftz.f32 %0, %1;" : "=f"(m1) : "f"(pr.x * st.j1));
    asm("ex2.approx.ftz.f32 %0, %1;" : "=f"(m2) : "f"(pr.x * st.j2));
    const float t1 = pr.y * st.j1, t2 = pr.y * st.j2;
    r1 = m1 * __cosf(t1); i1 = m1 * __sinf(t1); r2 = m2 * __cosf(t2); i2 = m2 * __sinf(t2);
  }
  float ar1[4], ai1[4], ar2[4], ai2[4];
#pragma unroll
  for (int s = 0; s < 4; s++) {
    ar1[s] = r1; ai1[s] = i1; ar2[s] = r2; ai2[s] = i2;
    float nr = fmaf(r1, r1, -i1 * i1); i1 = (r1 * i1) * 2.f; r1 = nr;
    nr = fmaf(r2, r2, -i2 * i2); i2 = (r2 * i2) * 2.f; r2 = nr;
  }
  float b0[5], b1[5];
  auto cmul = [&](int t, float er, float ei) { b0[t] = fmaf(pr.z, er, -(pr.w * ei)); b1[t] = fmaf(-pr.z, ei, -(pr.w * er)); };
  cmul(0, r1, i1);
  cmul(1, r2, i2);
#pragma unroll
  for (int s = 1; s < 4; s++) {
    float nr = fmaf(r2, r2, -i2 * i2); i2 = (r2 * i2) * 2.f; r2 = nr;
    cmul(1 + s, r2, i2);
  }
  asm volatile(
      "mma.sync.aligned.m16n8k8.row.col.f32.tf32.tf32.f32 {%0,%1,%2,%3}, {%20,%21,%22,%23}, {%36,%37}, {%0,%1,%2,%3};\n"
      "mma.sync.aligned.m16n8k8.row.col.f32.tf32.tf32.f32 {%4,%5,%6,%7}, {%20,%21,%22,%23}, {%38,%39}, {%4,%5,%6,%7};\n"
      "mma.sync.aligned.m16n8k8.row.col.f32.tf32.tf32.f32 {%8,%9,%10,%11}, {%24,%25,%26,%27}, {%40,%41}, {%8,%9,%10,%11};\n"
      "mma.sync.aligned.m16n8k8.row.col.f32.tf32.tf32.f32 {%12,%13,%14,%15}, {%28,%29,%30,%31}, {%42,%43}, {%12,%13,%14,%15};\n"
      "mma.sync.aligned.m16n8k8.row.col.f32.tf32.tf32.f32 {%16,%17,%18,%19}, {%32,%33,%34,%35}, {%44,%45}, {%16,%17,%18,%19};"
      : "+f"(st.acc[0][0]), "+f"(st.acc[0][1]), "+f"(st.acc[0][2]), "+f"(st.acc[0][3]), "+f"(st.acc[1][0]), "+f"(st.acc[1][1]), "+f"(st.acc[1][2]), "+f"(st.acc[1][3]),
        "+f"(st.acc[2][0]), "+f"(st.acc[2][1]), "+f"(st.acc[2][2]), "+f"(st.acc[2][3]), "+f"(st.acc[3][0]), "+f"(st.acc[3][1]), "+f"(st.acc[3][2]), "+f"(st.acc[3][3]),
        "+f"(st.acc[4][0]), "+f"(st.acc[4][1]), "+f"(st.acc[4][2]), "+f"(st.acc[4][3])
      : "r"(__float_as_uint(ar1[0])), "r"(__float_as_uint(ar2[0])), "r"(__float_as_uint(ai1[0])), "r"(__float_as_uint(ai2[0])),
        "r"(__float_as_uint(ar1[1])), "r"(__float_as_uint(ar2[1])), "r"(__float_as_uint(ai1[1])), "r"(__float_as_uint(ai2[1])),
        "r"(__float_as_uint(ar1[2])), "r"(__float_as_uint(ar2[2])), "r"(__float_as_uint(ai1[2])), "r"(__float_as_uint(ai2[2])),
        "r"(__float_as_uint(ar1[3])), "r"(__float_as_uint(ar2[3])), "r"(__float_as_uint(ai1[3])), "r"(__float_as_uint(ai2[3])),
        "r"(__float_as_uint(b0[0])), "r"(__float_as_uint(b1[0])), "r"(__float_as_uint(b0[1])), "r"(__float_as_uint(b1[1])), "r"(__float_as_uint(b0[2])),
        "r"(__float_as_uint(b1[2])), "r"(__float_as_uint(b0[3])), "r"(__float_as_uint(b1[3])), "r"(__float_as_uint(b0[4])), "r"(__float_as_uint(b1[4])));
}
__device__ __forceinline__ void kgen_finish(unsigned char* scr, unsigned short* kd, unsigned short* k2048, int tid, KgState& st) {
  const int warp = tid >> 5, lane = tid & 31, g = lane >> 2, q = lane & 3;
  float* red = (float*)(scr + (warp >> 1) * 4096 + 1296);
  __syncwarp();
  if (warp & 1) {
#pragma unroll
    for (int t = 0; t < 5; t++)
#pragma unroll
      for (int e = 0; e < 4; e++) red[(4 * t + e) * 32 + lane] = st.acc[t][e];
    red[640] = st.v;
  }
  named_bar(3, 256);
  if (!(warp & 1)) {
    *k2048 = (unsigned short)pack_bf16(st.v + red[640], 0.f);
#pragma unroll
    for (int t = 0; t < 5; t++)
#pragma unroll
      for (int e = 0; e < 4; e++)
        kd[t * 128 + 32 * q + 16 * (e & 1) + 8 * (e >> 1) + g] = (unsigned short)pack_bf16(st.acc[t][e] + red[(4 * t + e) * 32 + lane], 0.f);
  }
}
__device__ __forceinline__ int kd_index(int l, int sh) {
  const int m = sh ? 1 : 0;
  return ((l + ((1 << sh) >> 1) - m + ((l >> sh) & m)) >> sh) + 128 * sh;
}
template <int NT>
__device__ __forceinline__ void kexpand(uint32_t kd, uint32_t stride, uint32_t k2048, int ch0, int nch, int tid) {
  uint4* const dst0 = (uint4*)(g_kp + (size_t)ch0 * KP_LEN);
#pragma unroll 1
  for (int it = tid; it < KP_LEN / 4; it += NT) {
    const int i0 = it * 4 - 16;
    const bool ok = i0 >= 0 && i0 < L_ - 4;
    const int l0 = ok ? i0 : 4;
    const int sh = max(0, 24 - __clz(l0 | 1)), shp = max(0, 24 - __clz((l0 - 1) | 1));
    const int e0 = kd_index(l0, sh), b1 = e0 & ~1;
    const uint32_t np = 0x54 + 0x22 * (kd_index(l0 - 1, shp) - b1), n0 = 0x10 + 0x22 * (e0 - b1), n1 = 0x10 + 0x22 * (kd_index(l0 + 1, sh) - b1);
    const uint32_t n2 = 0x10 + 0x22 * (kd_index(l0 + 2, sh) - b1), n3 = 0x10 + 0x22 * (kd_index(l0 + 3, sh) - b1);
    const uint32_t s0 = (n0 + 0x44) | (np << 8), s1 = n1 | (n0 << 8), s2 = n2 | (n1 << 8), s3 = n3 | (n2 << 8);
    const uint32_t mk = ok ? 0xffffffffu : 0u, mp = i0 > 0 ? mk : 0xffffu & mk;
    uint32_t a = kd + 2 * b1;
    const uint32_t o2 = b1 < 638 ? 4 : 0;
    uint4* dst = dst0 + it;
    if (i0 == L_ - 4) continue;
#pragma unroll 2
    for (int c = 0; c < nch; c++) {
      const uint32_t x0 = lds32(a - 4), x1 = lds32(a), x2 = lds32(a + o2);
      *dst = make_uint4(__byte_perm(x0, x1, s0) & mp, __byte_perm(x1, x2, s1) & mk, __byte_perm(x1, x2, s2) & mk, __byte_perm(x1, x2, s3) & mk);
      a += stride; dst += KP_LEN / 4;
    }
  }
  if (tid < nch) {
    uint32_t z, y;
    asm volatile("ld.shared.u16 %0, [%1];" : "=r"(z) : "r"(k2048 + 2 * tid) : "memory");
    asm volatile("ld.shared.u16 %0, [%1];" : "=r"(y) : "r"(kd + tid * stride + 1278) : "memory");
    dst0[tid * (KP_LEN / 4) + 515] = make_uint4(z | (y << 16), z * 0x10001u, z * 0x10001u, z * 0x10001u);
  }
  fence_async_all();
}

template <int NR>
__device__ __forceinline__ void conv_mma(float (&d)[NR], const uint32_t* a, uint64_t db) {
  if constexpr (NR == 64) wg_cv128<0>(d, a[0], a[1], a[2], a[3], db);
  else if constexpr (NR == 48) wg_cv96<0>(d, a[0], a[1], a[2], a[3], db);
  else if constexpr (NR == 32) wg_cv64<0>(d, a[0], a[1], a[2], a[3], db);
  else wg_rs32<0>(d, a[0], a[1], a[2], a[3], db);
}
__device__ __forceinline__ void conv_load(uint32_t (&a)[8], uint32_t o) {
#pragma unroll
  for (int c = 0; c < 2; c++) {
    a[4 * c + 0] = lds32(o + c * KP_BYTES); a[4 * c + 1] = lds32(o + c * KP_BYTES + 512);
    a[4 * c + 2] = lds32(o + c * KP_BYTES - 32); a[4 * c + 3] = lds32(o + c * KP_BYTES + 480);
  }
}
template <int NR>
__device__ __forceinline__ void conv_phase(float (&dA)[NR], float (&dB)[NR], uint32_t (&a)[4][8], uint32_t kp, uint64_t dU) {
#pragma unroll 1
  for (int i = 0; i < 2; i++) {
#pragma unroll
    for (int k = 0; k < 4; k++) {
      wg_fence();
      conv_mma<NR>(dA, a[k], dU - 2 * k); conv_mma<NR>(dB, a[k] + 4, dU - 2 * k + (U_BYTES >> 4));
      wg_commit();
      wg_wait<1>();
      if (k == 2 && i) kp += 64 * 24;
      conv_load(a[(k + 2) & 3], kp + 64 * (k + 2));
    }
    kp += 256;
    dU -= 8;
  }
  wg_wait<0>();
  reg_fence(dA); reg_fence(dB);
}
template <int NR>
__device__ __forceinline__ void upper_copy(float (&dst)[NR - 16], const float (&src)[NR]) {
#pragma unroll
  for (int i = 0; i < NR - 16; i++) asm volatile("mov.b32 %0, %1;" : "=f"(dst[i]) : "f"(src[i + 16]));
}
__device__ __forceinline__ void conv2(uint32_t sb, int wg, int w, int lane, int ch, int cnt) {
  const int g = lane >> 2, q = lane & 3;
  float dA[64], dB[64];
  uint32_t a[4][8];
  const uint32_t kp = sb + T_KP + 2 * wg * KP_BYTES + 4 * (16 + 256 * (w >> 1) + 8 * (w & 1) + g - 2 * q);
  const uint64_t dU = mk_desc(sb + T_U + 2 * wg * U_BYTES + 256, 16, 256, 3);
#pragma unroll
  for (int i = 0; i < 64; i++) { dA[i] = 0.f; dB[i] = 0.f; }
  conv_load(a[0], kp); conv_load(a[1], kp + 64);
  conv_phase<64>(dA, dB, a, kp, dU);
  float eA[48], eB[48];
  upper_copy<64>(eA, dA); upper_copy<64>(eB, dB);
  conv_phase<48>(eA, eB, a, kp + 2048, dU);
  float fA[32], fB[32];
  upper_copy<48>(fA, eA); upper_copy<48>(fB, eB);
  conv_phase<32>(fA, fB, a, kp + 4096, dU);
  float gA[16], gB[16];
  upper_copy<32>(gA, fA); upper_copy<32>(gB, fB);
  conv_phase<16>(gA, gB, a, kp + 6144, dU);
#pragma unroll
  for (int i = 0; i < 16; i++) {
    dA[16 + i] = eA[i]; dA[32 + i] = fA[i]; dA[48 + i] = gA[i];
    dB[16 + i] = eB[i]; dB[32 + i] = fB[i]; dB[48 + i] = gB[i];
  }
  PROF_T(53);
  float z[2][16][2];
#pragma unroll
  for (int m = 0; m < 16; m++)
#pragma unroll
    for (int e = 0; e < 2; e++) {
      z[0][m][e] = m ? dA[4 * m + e] + dA[4 * m - 2 + e] : dA[e];
      z[1][m][e] = m ? dB[4 * m + e] + dB[4 * m - 2 + e] : dB[e];
    }
  named_bar(1 + wg, 128);
  const uint32_t xb = sb + T_KP + 2 * wg * KP_BYTES;
  const uint32_t xw = xb + (w * 32 + lane) * 16, xr = xb + ((w ^ 2) * 32 + lane) * 16;
  float k[2][8][2];
  if (w < 2) {
#pragma unroll
    for (int c = 0; c < 2; c++)
#pragma unroll
      for (int m = 0; m < 8; m += 2) {
        sts128(xw + (4 * c + (m >> 1)) * 2048, make_uint4(__float_as_uint(z[c][8 + m][0]), __float_as_uint(z[c][8 + m][1]), __float_as_uint(z[c][9 + m][0]), __float_as_uint(z[c][9 + m][1])));
        k[c][m][0] = z[c][m][0]; k[c][m][1] = z[c][m][1]; k[c][m + 1][0] = z[c][m + 1][0]; k[c][m + 1][1] = z[c][m + 1][1];
      }
  } else {
#pragma unroll
    for (int c = 0; c < 2; c++)
#pragma unroll
      for (int m = 0; m < 8; m += 2) {
        sts128(xw + (4 * c + (m >> 1)) * 2048, m ? make_uint4(__float_as_uint(z[c][m - 2][0]), __float_as_uint(z[c][m - 2][1]), __float_as_uint(z[c][m - 1][0]), __float_as_uint(z[c][m - 1][1])) : make_uint4(0u, 0u, 0u, 0u));
        k[c][m][0] = z[c][6 + m][0]; k[c][m][1] = z[c][6 + m][1]; k[c][m + 1][0] = z[c][7 + m][0]; k[c][m + 1][1] = z[c][7 + m][1];
      }
  }
  named_bar(1 + wg, 128);
  const uint32_t yb = sb + T_U + 2 * wg * U_BYTES;
#pragma unroll
  for (int c = 0; c < 2; c++)
#pragma unroll
    for (int m = 0; m < 8; m += 4) {
      const uint4 u = lds128(xr + (4 * c + (m >> 1)) * 2048), v = lds128(xr + (4 * c + (m >> 1) + 1) * 2048);
      stmatrix_x4_t(yb + c * 4096 + (64 * (w >> 1) + 8 * m + lane) * 32 + 16 * (w & 1),
                    pack_bf16(k[c][m][0] + __uint_as_float(u.x), k[c][m][1] + __uint_as_float(u.y)), pack_bf16(k[c][m + 1][0] + __uint_as_float(u.z), k[c][m + 1][1] + __uint_as_float(u.w)),
                    pack_bf16(k[c][m + 2][0] + __uint_as_float(v.x), k[c][m + 2][1] + __uint_as_float(v.y)), pack_bf16(k[c][m + 3][0] + __uint_as_float(v.z), k[c][m + 3][1] + __uint_as_float(v.w)));
    }
  fence_async_smem();
  named_bar(1 + wg, 128);
  if (w == 0 && lane == 0) {
    PROF_T(54);
    bulk_s2g(g_y + (size_t)ch * L_, yb, 8192);
    bulk_commit_wait();
    PROF_T(55);
    cnt_add_done(cnt);
  }
  __syncwarp();
}

__global__ void __cluster_dims__(2, 1, 1) __launch_bounds__(384, 1) fused_kernel(const __grid_constant__ Params p) {
  extern __shared__ __align__(1024) unsigned char smem_raw[];
  const uint32_t sb = smem_u32(smem_raw);
  const uint32_t bar = sb + SM_BAR;
  const int j = blockIdx.x & 1, pair = blockIdx.x >> 1, mt = pair & 15, sp = pair >> 4;
  const bool spare = pair >= 64;
  const int warp = __shfl_sync(0xffffffffu, threadIdx.x >> 5, 0), wg = warp >> 2, w = warp & 3;
  const int row0 = mt * 128 + (2 * sp + j) * 16;
  const int f0 = sp * 1152;
  const long long t_start = clock64();
  KgIn kin;
  if (wg < 2) kgen_load(p, spare ? 512 + ((int)blockIdx.x - 128) * 16 : blockIdx.x * 4, threadIdx.x, kin);
  if (threadIdx.x == 256) {
    mbar_init(bar + B_X, 1);
    if (!spare) {
      mbar_expect_tx(bar + B_X, 16 * D_ * 2);
      bulk_g2s(sb + PR_LN, p.xp + (size_t)row0 * D_, 16 * D_ * 2, bar + B_X);
    }
#pragma unroll
    for (int i = 0; i < 30; i++) if (i != 22) mbar_init(bar + 8 * i, (i >= 7 && i < 14) ? 8 : 1);
    mbar_init(bar + B_SG, 2);
    mbar_expect_tx(bar + B_HF, 8192); mbar_expect_tx(bar + B_HF + 8, 8192);
    asm volatile("fence.mbarrier_init.release.cluster;" ::: "memory");
    if (!spare) {
#pragma unroll 1
      for (int u = 0; u < NST; u++) {
        const uint32_t dst = sb + SM_RING + u * SLOT, fb = bar + B_FULL + 8 * u;
        mbar_expect_tx(fb, 8192);
        tma_2d(dst, &p.gate, f0 + 64 * j, 32 * u, fb);
        tma_2d(dst + 4096, &p.up, f0 + 64 * j, 32 * u, fb);
      }
    }
  }
  __syncthreads();
  asm volatile("barrier.cluster.arrive.relaxed.aligned;" ::: "memory");

  if (wg == 2) {
    const int t = threadIdx.x & 127, lane = t & 31;
    const bool el = elect_one();
    if (!spare) {
      const uint32_t ra = sb + PR_LN + (t >> 3) * (D_ * 2) + (t & 7) * 16;
      PROF_T(60);
      mbar_wait(bar + B_X, 0);
      PROF_T(61);
      const float x0 = bf_lo(lds32(sb + PR_LN + (t >> 3) * (D_ * 2)));
      float s = 0.f, q = 0.f;
#pragma unroll 3
      for (int i = 0; i < 9; i++) {
        const uint4 v = lds128(ra + i * 128);
        const uint32_t u[4] = {v.x, v.y, v.z, v.w};
#pragma unroll
        for (int k = 0; k < 4; k++) {
          const float a = bf_lo(u[k]) - x0, b = bf_hi(u[k]) - x0;
          s += a + b; q = fmaf(a, a, q); q = fmaf(b, b, q);
        }
      }
#pragma unroll
      for (int o = 4; o; o >>= 1) { s += __shfl_xor_sync(0xffffffffu, s, o); q += __shfl_xor_sync(0xffffffffu, q, o); }
      s *= (1.0f / D_);
      const float mb = bf_round(s + x0);
      const float var = fmaxf(fmaf(-s, s, q * (1.0f / D_)), 0.f);
      const float rinv = 1.0f / bf_round(sqrtf(bf_round(bf_round(var) + 1e-5f)));
#pragma unroll 3
      for (int i = 0; i < 9; i++) {
        const uint4 v = lds128(ra + i * 128);
        uint32_t u[4] = {v.x, v.y, v.z, v.w};
#pragma unroll
        for (int k = 0; k < 4; k++) {
          const uint32_t d = pack_bf16(bf_lo(u[k]) - mb, bf_hi(u[k]) - mb);
          u[k] = pack_bf16(bf_lo(d) * rinv, bf_hi(d) * rinv);
        }
        sts128(ra + i * 128, make_uint4(u[0], u[1], u[2], u[3]));
      }
      fence_async_smem();
      named_bar(5, 128);
      PROF_T(62);
      if (w == 0) {
        if (el) {
          bulk_s2g(g_xn + (size_t)row0 * D_, sb + PR_LN, 16 * D_ * 2);
          bulk_commit_wait();
          PROF_T(64);
          cnt_add_done(C_LN + mt);
        }
        __syncwarp();
        PROF_T(63);
      } else {
        const uint32_t* s_ln = (const uint32_t*)(smem_raw + PR_LN);
        const int sw = (row0 >> 6) & 1;
#pragma unroll 1
        for (int it = t - 32; it < 576; it += 96) {
          const int cp = it >> 1, hf = it & 1;
          uint32_t lo[4], hi[4];
#pragma unroll
          for (int r = 0; r < 4; r++) {
            const uint32_t a = s_ln[(8 * hf + 2 * r) * 288 + cp], b = s_ln[(8 * hf + 2 * r + 1) * 288 + cp];
            lo[r] = __byte_perm(a, b, 0x5410); hi[r] = __byte_perm(a, b, 0x7632);
          }
          uint4* d = (uint4*)(g_u + (size_t)(2 * cp) * U_LEN + 128 + row0) + (hf ^ sw);
          d[0] = make_uint4(lo[0], lo[1], lo[2], lo[3]);
          d[U_LEN / 8] = make_uint4(hi[0], hi[1], hi[2], hi[3]);
        }
      }
    }
    asm volatile("barrier.cluster.wait.aligned;" ::: "memory");
    asm volatile("setmaxnreg.dec.sync.aligned.u32 24;");
    if (w == 0) {
      if (!spare) {
        cnt_wait(C_LN + mt, 8);
        PROF_T(67);
        fence_async_all();
#pragma unroll 1
        for (int kb = 0; kb < 9; kb++) {
          if (kb == 7) named_bar(5, 128);
          if (el) {
            if (kb < 8) mbar_expect_tx(bar + B_XN + 8 * kb, kb < 7 ? 16384 : 32768);
            tma_2d(sb + SM_XN + kb * 16384, &p.xn, kb * 64, mt * 128, bar + B_XN + 8 * min(kb, 7));
          }
        }
        PROF_T(69);
        uint32_t slot = 0, ph = 0;
#pragma unroll 1
        for (int c = 0; c <= 9; c++) {
          const int fc = f0 + c * 128;
          if (c < 9) {
            for (int u = c ? 0 : NST; u < 18; u++) {
              mbar_wait(bar + B_EMPTY + 8 * slot, ph);
              if (el) {
                const uint32_t dst = sb + SM_RING + slot * SLOT, fb = bar + B_FULL + 8 * slot;
                mbar_expect_tx(fb, 8192);
                tma_2d(dst, &p.gate, fc + 64 * j, 32 * u, fb);
                tma_2d(dst + 4096, &p.up, fc + 64 * j, 32 * u, fb);
              }
              if (++slot == NST) { slot = 0; ph ^= 1; }
            }
          }
          const int fp = (fc - 128 + 64 * (1 - j)) >> 3, fo = fc + 64 * j;
#pragma unroll
          for (int i = 0; i < 8; i++) {
            const bool isP = i < 4;
            const int u = i & 3;
            if (isP ? (c == 0) : (c == 9)) continue;
            mbar_wait(bar + B_EMPTY + 8 * slot, ph);
            if (el) {
              const uint32_t dst = sb + SM_RING + slot * SLOT, fb = bar + B_FULL + 8 * slot;
              mbar_expect_tx(fb, 9216);
              if (isP) {
                tma_5d(dst, &p.dp, 0, 0, fp + 4 * (u >> 1), 2 * (u & 1), 4 * j, fb);
                tma_4d(dst + 8192, &p.dp5, 512 + 32 * j, 0, fp + 4 * (u >> 1), 2 * (u & 1), fb);
              } else {
                tma_3d(dst, &p.dn, 0, fo + 16 * u, 4 * j, fb);
                tma_2d(dst + 8192, &p.dn5, 512 + 32 * j, fo + 16 * u, fb);
              }
            }
            if (++slot == NST) { slot = 0; ph ^= 1; }
          }
        }
        const int ch0 = blockIdx.x * 4;
        named_bar(7, 128);
        cnt_wait(C_U, 384);
        fence_async_all();
        if (el) {
          mbar_expect_tx(bar + B_CV, 4 * U_BYTES + 4 * KP_BYTES);
          bulk_g2s(sb + T_KP, g_kp + (size_t)ch0 * KP_LEN, 4 * KP_BYTES, bar + B_CV);
          bulk_g2s(sb + T_U, g_u + (size_t)ch0 * U_LEN, 4 * U_BYTES, bar + B_CV);
        }
        unsigned char* img = g_part + (size_t)(2 * mt + j) * 16 * IMG;
        mbar_wait(bar + B_SG, 0);
        PROF_T(71);
        if (lane < 15) {
          const int qi = lane / 5, pc = lane - 5 * qi, r = (sp + 1 + qi) & 3;
          bulk_s2g(img + (r * 4 + sp) * IMG + pc * 4096, sb + pc * 16384 + (r >> 1) * 8192 + (r & 1) * (pc < 4 ? 4096 : 2048), pc < 4 ? 4096 : 2048);
          bulk_commit_wait();
        } else if (lane == 15) {
          mbar_expect_tx(bar + B_PT, 4 * IMG);
#pragma unroll 1
          for (int i = 0; i < 4; i++) tma_2d(sb + T_PART + 3 * IMG + i * 4096, &p.x, 256 * j + 64 * i, mt * 128 + 32 * sp, bar + B_PT);
          tma_2d(sb + T_PART + 3 * IMG + 16384, &p.x5, 512 + 32 * j, mt * 128 + 32 * sp, bar + B_PT);
        }
        __syncwarp();
        PROF_T(72);
        if (el) cnt_add_done(C_PART + 2 * mt + j);
        PROF_T(73);
        cnt_wait(C_PART + 2 * mt + j, 4);
        fence_async_all();
        PROF_T(74);
        if (lane < 3) bulk_g2s(sb + T_PART + lane * IMG, img + (sp * 4 + ((sp + 1 + lane) & 3)) * IMG, IMG, bar + B_PT);
        cnt_wait(C_Y5, 32);
        cnt_wait(C_Y + (ch0 >> 8), 128);
        cnt_wait(C_Y + j, 128);
        PROF_T(75);
        fence_async_all();
        if (el) {
          mbar_expect_tx(bar + B_YT, IMG);
          tma_2d(sb + T_YT, &p.y, mt * 128 + 32 * sp, 256 * j, bar + B_YT);
          tma_2d(sb + T_YT + 16384, &p.y5, mt * 128 + 32 * sp, 512 + 32 * j, bar + B_YT);
        }
        cnt_wait(C_Y + (j ^ 1), 128);
      } else {
        named_bar(7, 288);
        cnt_wait(C_U, 384);
        fence_async_all();
#pragma unroll 1
        for (int grp = 0; grp < 4; grp++) {
          const int ch0 = 512 + ((int)blockIdx.x - 128) * 16 + grp * 4;
          if (grp) mbar_wait(bar + B_SG, (grp - 1) & 1);
          if (el) {
            mbar_expect_tx(bar + B_CV, 4 * U_BYTES + 4 * KP_BYTES);
            bulk_g2s(sb + T_KP, g_kp + (size_t)ch0 * KP_LEN, 4 * KP_BYTES, bar + B_CV);
            bulk_g2s(sb + T_U, g_u + (size_t)ch0 * U_LEN, 4 * U_BYTES, bar + B_CV);
          }
        }
      }
      PROF_T(79);
      PROF_DUMP();
      unsigned int old = 0;
      if (el) old = atomicAdd(g_cnt + C_DONE * 32, 1u) + 1;
      if (__any_sync(0xffffffffu, old == gridDim.x)) { g_cnt[lane * 32] = 0u; g_cnt[(lane + 32) * 32] = 0u; }
    } else {
      if (!spare) {
        named_arrive(5, 128);
        if (lane == 0) { fence_async_all(); cnt_add(C_U); }
        named_bar(4, 352);
        kexpand<96>(sb + SM_HIN, 0, bar + B_K2048, blockIdx.x * 4, 1, t - 32);
        named_bar(8, 96);
        if (t == 32) { mbar_arrive_remote(mapa(bar + B_HE, j ^ 1)); mbar_arrive_remote(mapa(bar + B_HE + 8, j ^ 1)); }
        kexpand<96>(sb + SM_KD, 1280, bar + B_K2048 + 2, blockIdx.x * 4 + 1, 3, t - 32);
        named_arrive(7, 128);
      }
    }
  } else {
    const int t = threadIdx.x & 127, lane = t & 31;
    KgState kst;
    kgen_params(smem_raw + SM_HIN, threadIdx.x, kin, kst);
#define KPRE 16
    if (!spare) {
#pragma unroll 4
      for (int ks = 0; ks < KPRE; ks++) kgen_step(kst, ks);
    } else {
      const int c0 = 512 + ((int)blockIdx.x - 128) * 16;
#pragma unroll 1
      for (int grp = 0; grp < 4; grp++) {
        if (grp) { kgen_load(p, c0 + grp * 4, threadIdx.x, kin); kgen_params(smem_raw + SM_HIN + grp * 16384, threadIdx.x, kin, kst); }
#pragma unroll 2
        for (int ks = 0; ks < 16; ks++) kgen_step(kst, ks);
        kgen_finish(smem_raw + SM_HIN + grp * 16384, (unsigned short*)(smem_raw + SM_HIN + grp * 16384 + (warp >> 1) * 4096),
                    (unsigned short*)(smem_raw + SM_KD) + grp * 4 + (warp >> 1), threadIdx.x, kst);
      }
      named_bar(3, 256);
      kexpand<256>(sb + SM_HIN, 4096, sb + SM_KD, c0, 16, threadIdx.x);
      named_arrive(7, 288);
    }
    PROF_T(41);
    asm volatile("barrier.cluster.wait.aligned;" ::: "memory");
    asm volatile("setmaxnreg.inc.sync.aligned.u32 240;");
    if (!spare) {
      const bool leader = (t == 0);
      float O1[128], O2[16];
      uint32_t slot = 0, ph = 0, prev = 0;
      const uint32_t hin = sb + SM_HIN + wg * 8192;
      const uint32_t r_hin = mapa(hin + (16 * w + (lane >> 2)) * 128 + (((lane & 3) ^ (lane >> 2)) << 4), j ^ 1);
      const uint32_t r_hf = mapa(bar + B_HF + 8 * wg, j ^ 1), r_he = mapa(bar + B_HE + 8 * wg, j ^ 1);
      const uint64_t dA0 = mk_desc(sb + SM_XN + wg * 8192, 16, 1024, 1);
      const uint64_t dH0 = mk_desc(hin, 16, 1024, 1);
      const uint64_t dG0 = mk_desc(sb + SM_RING, 4096, 1024, 1);
      const uint64_t dW0 = mk_desc(sb + SM_RING, 2048, 1024, 1);
      const uint64_t dX0 = mk_desc(sb + SM_RING + 8192, 512, 512, 2);
      auto adv = [&]() { prev = slot; if (++slot == NST) { slot = 0; ph ^= 1; } };
      auto release = [&](uint32_t s) { if (lane == 0) mbar_arrive(bar + B_EMPTY + 8 * s); };
      auto acquire = [&]() -> bool {
        if (__all_sync(0xffffffffu, mbar_test(bar + B_FULL + 8 * slot, ph))) return true;
        wg_wait<0>();
        release(prev);
        mbar_wait(bar + B_FULL + 8 * slot, ph);
        return false;
      };
      auto peer_begin = [&](int cp) {
        mbar_wait(bar + B_HF + 8 * wg, cp & 1);
        if (leader && cp < 8) mbar_expect_tx(bar + B_HF + 8 * wg, 8192);
        fence_async_smem();
      };
      auto peer_unit = [&](int u) {
        wg_fence();
        wg_ss256<1>(O1, dH0 + 2 * u, dW0 + (uint64_t)(slot * (SLOT >> 4)));
        wg_ss32<1>(O2, dH0 + 2 * u, dX0 + (uint64_t)(slot * (SLOT >> 4)));
        wg_commit();
      };
      auto chunk = [&](auto first_c, const int c) {
        constexpr bool FIRST = decltype(first_c)::value;
        float S[64];
        {
          bool rel = false;
          if (FIRST) { mbar_wait(bar + B_XN, 0); mbar_wait(bar + B_FULL + 8 * slot, ph); PROF_T(42); PROF_G(2); }
          else mbar_wait(bar + B_FULL + 8 * slot, ph);
          const uint64_t db = dG0 + (uint64_t)(slot * (SLOT >> 4));
          wg_fence();
          wg_ss128_init<1>(S, dA0, db);
          wg_ss128<1>(S, dA0 + 2, db + 128);
          wg_commit();
          adv();
        }
#pragma unroll 1
        for (int u = 1; u < 18; u++) {
          if (FIRST && !(u & 1) && u < 16) mbar_wait(bar + B_XN + 8 * (u >> 1), 0);
          const bool rel = acquire();
          const uint64_t da = dA0 + (uint64_t)((u >> 1) * 1024 + (u & 1) * 4);
          const uint64_t db = dG0 + (uint64_t)(slot * (SLOT >> 4));
          wg_fence();
          wg_ss128<1>(S, da, db);
          wg_ss128<1>(S, da + 2, db + 128);
          wg_commit();
          if constexpr (FIRST) {
            if (u <= 16 - KPRE) kgen_step(kst, u - 1 + KPRE);
            else if (u == 17 - KPRE) {
              kgen_finish(smem_raw + SM_HIN, (unsigned short*)(smem_raw + (warp < 2 ? SM_HIN : SM_KD + ((warp >> 1) - 1) * 1280)),
                          (unsigned short*)(smem_raw + SM_BAR + B_K2048) + (warp >> 1), threadIdx.x, kst);
              named_arrive(4, 352);
            }
          }
          if constexpr (!FIRST) { if (u == 12) peer_begin(c - 1); }
          wg_wait<1>();
          if (rel) release(prev);
          adv();
        }
        uint32_t H[16];
        if constexpr (FIRST) { wg_wait<0>(); release(prev); }
        auto P = [&](int u) { if constexpr (!FIRST) { const bool rel = acquire(); peer_unit(u); wg_wait<1>(); if (rel) release(prev); adv(); } };
        auto E = [&](int u) {
#pragma unroll
          for (int i = 8 * u; i < 8 * u + 8; i++) asm volatile("" : "+f"(S[i]), "+f"(S[32 + i])::"memory");
#pragma unroll
          for (int g = 2 * u; g < 2 * u + 2; g++) {
            H[2 * g] = pack_bf16(geglu(S[4 * g], S[32 + 4 * g]), geglu(S[4 * g + 1], S[33 + 4 * g]));
            H[2 * g + 1] = pack_bf16(geglu(S[4 * g + 2], S[34 + 4 * g]), geglu(S[4 * g + 3], S[35 + 4 * g]));
          }
#pragma unroll
          for (int i = 4 * u; i < 4 * u + 4; i++) asm volatile("" : "+r"(H[i])::"memory");
        };
        auto O = [&](int u) {
          bool rel;
          if (FIRST && u == 0) { mbar_wait(bar + B_FULL + 8 * slot, ph); rel = false; } else rel = acquire();
          wg_fence();
          if (FIRST && u == 0) {
            wg_rs256_init<1>(O1, H[0], H[1], H[2], H[3], dW0 + (uint64_t)(slot * (SLOT >> 4)));
            wg_rs32_init<1>(O2, H[0], H[1], H[2], H[3], dX0 + (uint64_t)(slot * (SLOT >> 4)));
          } else {
            wg_rs256<1>(O1, H[4 * u], H[4 * u + 1], H[4 * u + 2], H[4 * u + 3], dW0 + (uint64_t)(slot * (SLOT >> 4)));
            wg_rs32<1>(O2, H[4 * u], H[4 * u + 1], H[4 * u + 2], H[4 * u + 3], dX0 + (uint64_t)(slot * (SLOT >> 4)));
          }
          wg_commit();
          if (u == 3) {
            mbar_wait(bar + B_HE + 8 * wg, c & 1);
            st_async_v4(r_hin, H[0], H[2], H[4], H[6], r_hf);
            st_async_v4(r_hin ^ 64, H[8], H[10], H[12], H[14], r_hf);
            st_async_v4(r_hin + 1024, H[1], H[3], H[5], H[7], r_hf);
            st_async_v4((r_hin ^ 64) + 1024, H[9], H[11], H[13], H[15], r_hf);
            named_bar(3, 256);
          }
          wg_wait<1>();
          if (rel) release(prev);
          if (u == 0) { if constexpr (!FIRST) { if (leader) mbar_arrive_remote(r_he); } }
          if (u == 3) { wg_wait<0>(); release(slot); }
          adv();
        };
#define ORDER 2
        P(0); E(0); P(1); P(2); E(1); P(3); O(0); E(2); O(1); O(2); E(3); O(3);
        PROF_T(4 + 4 * c);
      };
      chunk(std::true_type{}, 0);
#pragma unroll 1
      for (int c = 1; c < 9; c++) chunk(std::false_type{}, c);
      peer_begin(8);
#pragma unroll 1
      for (int u = 0; u < 4; u++) { mbar_wait(bar + B_FULL + 8 * slot, ph); peer_unit(u); adv(); }
      wg_wait<0>();
      reg_fence(O1); reg_fence(O2);
      PROF_T(40); PROF_G(3);
      const int mi = lane >> 3, li = lane & 7;
      {
        const int row = 16 * w + 8 * (mi & 1) + li;
        const uint32_t stg = sb + SM_XN + wg * 8192 + row * 128;
#pragma unroll
        for (int g = 0; g < 32; g += 2)
          stmatrix_x4(stg + (g >> 3) * 16384 + ((((g & 7) + (mi >> 1)) ^ li) << 4), pack_bf16(O1[4 * g], O1[4 * g + 1]), pack_bf16(O1[4 * g + 2], O1[4 * g + 3]),
                      pack_bf16(O1[4 * g + 4], O1[4 * g + 5]), pack_bf16(O1[4 * g + 6], O1[4 * g + 7]));
#pragma unroll
        for (int g = 0; g < 4; g += 2)
          stmatrix_x4(stg + 65536 - row * 64 + (((g + (mi >> 1)) ^ (li >> 1)) << 4), pack_bf16(O2[4 * g], O2[4 * g + 1]), pack_bf16(O2[4 * g + 2], O2[4 * g + 3]),
                      pack_bf16(O2[4 * g + 4], O2[4 * g + 5]), pack_bf16(O2[4 * g + 6], O2[4 * g + 7]));
        fence_async_smem();
        named_bar(1 + wg, 128);
        if (leader) mbar_arrive(bar + B_SG);
      }
      mbar_wait(bar + B_CV, 0);
      PROF_T(43);
      conv2(sb, wg, w, lane, blockIdx.x * 4 + 2 * wg, C_Y + (blockIdx.x >> 6));
      PROF_T(44); PROF_G(5);
      const int w8 = warp, row = 16 * (w8 & 1) + 8 * (mi & 1) + li;
      const uint32_t own = sb + SM_XN + (sp >> 1) * 8192;
      const int nblk = w8 < 4 ? 5 : 4;
      named_bar(3, 256);
      mbar_wait(bar + B_PT, 0);
#pragma unroll 1
      for (int k = 0; k < nblk; k++) {
        const uint32_t o = k < 4 ? row * 128 + (((2 * k + (mi >> 1)) ^ li) << 4) : row * 64 + (((2 * (w8 >> 1) + (mi >> 1)) ^ (li >> 1)) << 4);
        const uint32_t oa = own + o + (k < 4 ? (w8 >> 1) * 16384 + (sp & 1) * 4096 : 65536 + (sp & 1) * 2048);
        const uint32_t pa = sb + T_PART + o + (k < 4 ? (w8 >> 1) * 4096 : 16384);
        uint32_t r[4];
        float f[8];
        ldmatrix_x4(oa, r);
#pragma unroll
        for (int i = 0; i < 4; i++) { f[2 * i] = bf_lo(r[i]); f[2 * i + 1] = bf_hi(r[i]); }
#pragma unroll
        for (int s = 0; s < 4; s++) {
          ldmatrix_x4(pa + s * IMG, r);
#pragma unroll
          for (int i = 0; i < 4; i++) { f[2 * i] += bf_lo(r[i]); f[2 * i + 1] += bf_hi(r[i]); }
        }
        stmatrix_x4(oa, pack_bf16(f[0], f[1]), pack_bf16(f[2], f[3]), pack_bf16(f[4], f[5]), pack_bf16(f[6], f[7]));
      }
      __syncwarp();
      PROF_T(56);
      mbar_wait(bar + B_YT, 0);
      PROF_T(45); PROF_G(6);
#pragma unroll 1
      for (int k = 0; k < nblk; k++) {
        const uint32_t o = k < 4 ? row * 128 + (((2 * k + (mi >> 1)) ^ li) << 4) : row * 64 + (((2 * (w8 >> 1) + (mi >> 1)) ^ (li >> 1)) << 4);
        const uint32_t oa = own + o + (k < 4 ? (w8 >> 1) * 16384 + (sp & 1) * 4096 : 65536 + (sp & 1) * 2048);
        const int chl = (k < 4 ? 64 * (w8 >> 1) + 16 * k : 256 + 16 * (w8 >> 1)) + 8 * (mi >> 1) + li;
        uint32_t r[4], y0, y1, y2, y3;
        ldmatrix_x4(oa, r);
        ldmatrix_x4_t(sb + T_YT + chl * 64 + (((2 * (w8 & 1) + (mi & 1)) ^ (li >> 1)) << 4), y0, y1, y2, y3);
        stmatrix_x4(oa, pack_bf16(bf_lo(r[0]) + bf_lo(y0), bf_hi(r[0]) + bf_hi(y0)), pack_bf16(bf_lo(r[1]) + bf_lo(y1), bf_hi(r[1]) + bf_hi(y1)),
                    pack_bf16(bf_lo(r[2]) + bf_lo(y2), bf_hi(r[2]) + bf_hi(y2)), pack_bf16(bf_lo(r[3]) + bf_lo(y3), bf_hi(r[3]) + bf_hi(y3)));
      }
      PROF_T(57);
      fence_async_smem();
      named_bar(3, 256);
      if (threadIdx.x < 5) {
        if (threadIdx.x < 4) tma_store_2d(&p.out, own + threadIdx.x * 16384 + (sp & 1) * 4096, 256 * j + 64 * threadIdx.x, mt * 128 + 32 * sp);
        else tma_store_2d(&p.out5, own + 65536 + (sp & 1) * 2048, 512 + 32 * j, mt * 128 + 32 * sp);
        asm volatile("cp.async.bulk.commit_group;" ::: "memory");
        asm volatile("cp.async.bulk.wait_group.read 0;" ::: "memory");
      }
      PROF_T(46); PROF_G(7);
      PROF_DUMP();
    } else {
#pragma unroll 1
      for (int grp = 0; grp < 4; grp++) {
        mbar_wait(bar + B_CV, grp & 1);
        conv2(sb, wg, w, lane, 512 + ((int)blockIdx.x - 128) * 16 + grp * 4 + 2 * wg, C_Y5);
        if (t == 0) mbar_arrive(bar + B_SG);
      }
      PROF_T(46);
      PROF_DUMP();
    }
  }
}

typedef CUresult (*PFN_enc)(CUtensorMap*, CUtensorMapDataType, cuuint32_t, void*, const cuuint64_t*, const cuuint64_t*, const cuuint32_t*,
                            const cuuint32_t*, CUtensorMapInterleave, CUtensorMapSwizzle, CUtensorMapL2promotion, CUtensorMapFloatOOBfill);

void enc(PFN_enc fn, CUtensorMap* m, void* ptr, int rank, const cuuint64_t* dims, const cuuint64_t* strides, const cuuint32_t* box, CUtensorMapSwizzle sw) {
  cuuint32_t es[5] = {1, 1, 1, 1, 1};
  fn(m, CU_TENSOR_MAP_DATA_TYPE_BFLOAT16, rank, ptr, dims, strides, box, es, CU_TENSOR_MAP_INTERLEAVE_NONE, sw,
     CU_TENSOR_MAP_L2_PROMOTION_L2_128B, CU_TENSOR_MAP_FLOAT_OOB_FILL_NONE);
}

}

extern "C" void kernel_launch(void* const* d_in, const int* in_sizes, int n_in, void* d_out, int out_size) {
  static Params pr;
  static void* key[5] = {nullptr, nullptr, nullptr, nullptr, nullptr};
  if (key[0] != d_in[8] || key[1] != d_in[9] || key[2] != d_in[10] || key[3] != d_in[0] || key[4] != d_out) {
    key[0] = d_in[8]; key[1] = d_in[9]; key[2] = d_in[10]; key[3] = d_in[0]; key[4] = d_out;
    void* fnp = nullptr; cudaDriverEntryPointQueryResult st;
    cudaGetDriverEntryPoint("cuTensorMapEncodeTiled", &fnp, cudaEnableDefault, &st);
    PFN_enc fn = (PFN_enc)fnp;
    void *p_xn, *p_y;
    cudaGetSymbolAddress(&p_xn, g_xn); cudaGetSymbolAddress(&p_y, g_y);
    { cuuint64_t d[2] = {D_, L_}, s[1] = {D_ * 2};
      { cuuint32_t b[2] = {64, 128}; enc(fn, &pr.xn, p_xn, 2, d, s, b, CU_TENSOR_MAP_SWIZZLE_128B); }
      { cuuint32_t b[2] = {64, 32}; enc(fn, &pr.x, d_in[0], 2, d, s, b, CU_TENSOR_MAP_SWIZZLE_128B); enc(fn, &pr.out, d_out, 2, d, s, b, CU_TENSOR_MAP_SWIZZLE_128B); }
      { cuuint32_t b[2] = {32, 32}; enc(fn, &pr.x5, d_in[0], 2, d, s, b, CU_TENSOR_MAP_SWIZZLE_64B); enc(fn, &pr.out5, d_out, 2, d, s, b, CU_TENSOR_MAP_SWIZZLE_64B); } }
    { cuuint64_t d[2] = {F_, D_}, s[1] = {F_ * 2}; cuuint32_t b[2] = {64, 32};
      enc(fn, &pr.gate, d_in[8], 2, d, s, b, CU_TENSOR_MAP_SWIZZLE_128B); enc(fn, &pr.up, d_in[9], 2, d, s, b, CU_TENSOR_MAP_SWIZZLE_128B); }
    { void* wd = d_in[10];
      { cuuint64_t d[3] = {64, F_, 9}, s[2] = {D_ * 2, 128}; cuuint32_t b[3] = {64, 16, 4}; enc(fn, &pr.dn, wd, 3, d, s, b, CU_TENSOR_MAP_SWIZZLE_128B); }
      { cuuint64_t d[2] = {D_, F_}, s[1] = {D_ * 2}; cuuint32_t b[2] = {32, 16}; enc(fn, &pr.dn5, wd, 2, d, s, b, CU_TENSOR_MAP_SWIZZLE_64B); }
      { cuuint64_t d[5] = {64, 2, F_ / 8, 4, 9}, s[4] = {D_ * 2, D_ * 16, D_ * 4, 128}; cuuint32_t b[5] = {64, 2, 4, 2, 4};
        enc(fn, &pr.dp, wd, 5, d, s, b, CU_TENSOR_MAP_SWIZZLE_128B); }
      { cuuint64_t d[4] = {D_, 2, F_ / 8, 4}, s[3] = {D_ * 2, D_ * 16, D_ * 4}; cuuint32_t b[4] = {32, 2, 4, 2};
        enc(fn, &pr.dp5, wd, 4, d, s, b, CU_TENSOR_MAP_SWIZZLE_64B); }
    }
    { cuuint64_t d[2] = {L_, D_}, s[1] = {L_ * 2};
      { cuuint32_t b[2] = {32, 256}; enc(fn, &pr.y, p_y, 2, d, s, b, CU_TENSOR_MAP_SWIZZLE_64B); }
      { cuuint32_t b[2] = {32, 32}; enc(fn, &pr.y5, p_y, 2, d, s, b, CU_TENSOR_MAP_SWIZZLE_64B); } }
    cudaFuncSetAttribute(fused_kernel, cudaFuncAttributeMaxDynamicSharedMemorySize, SMEM_BYTES);
  }
  const __nv_bfloat16* const* in = (const __nv_bfloat16* const*)d_in;
  pr.xp = in[0]; pr.logA = in[1]; pr.Aim = in[2]; pr.Cre = in[3]; pr.Cim = in[4]; pr.logdt = in[5]; pr.Dsk = in[6];
  fused_kernel<<<132, 384, SMEM_BYTES>>>(pr);
}
```

```cpp
#include <cuda_runtime.h>
#include <cuda_bf16.h>
#include <cuda.h>
#include <stdint.h>
#include <stdio.h>
#include <type_traits>
#define CV_BASEOFF 0

namespace {

constexpr int L_ = 2048, D_ = 576, F_ = 4608, NM_ = 128;
constexpr int KP_LEN = 2080;
constexpr int U_LEN = 2176;

__device__ __align__(1024) __nv_bfloat16 g_xn[L_ * D_];
__device__ __align__(1024) __nv_bfloat16 g_u[D_ * U_LEN];
__device__ __align__(1024) unsigned char g_part[32 * 16 * 18432];
__device__ __align__(1024) __nv_bfloat16 g_y[D_ * L_];
__device__ __align__(1024) unsigned int g_cnt[64 * 32];
constexpr int C_LN = 0, C_PART = 16, C_U = 48, C_Y = 49, C_Y5 = 51, C_DONE = 52;

#define PROF_T(idx) do {} while (0)
#define PROF_G(idx) do {} while (0)
#define PROF_DUMP() do {} while (0)
__device__ __forceinline__ uint32_t smem_u32(const void* p) { return (uint32_t)__cvta_generic_to_shared(p); }
__device__ __forceinline__ void mbar_init(uint32_t bar, uint32_t cnt) { asm volatile("mbarrier.init.shared::cta.b64 [%0], %1;" ::"r"(bar), "r"(cnt)); }
__device__ __forceinline__ void mbar_expect_tx(uint32_t bar, uint32_t bytes) { asm volatile("mbarrier.arrive.expect_tx.shared::cta.b64 _, [%0], %1;" ::"r"(bar), "r"(bytes) : "memory"); }
__device__ __forceinline__ void mbar_arrive(uint32_t bar) { asm volatile("mbarrier.arrive.shared::cta.b64 _, [%0];" ::"r"(bar) : "memory"); }
__device__ __forceinline__ void mbar_arrive_remote(uint32_t bar) { asm volatile("mbarrier.arrive.shared::cluster.b64 _, [%0];" ::"r"(bar) : "memory"); }
__device__ __forceinline__ bool mbar_try_wait(uint32_t bar, uint32_t parity) {
  uint32_t ok;
  asm volatile("{\n.reg .pred p;\nmbarrier.try_wait.parity.shared::cta.b64 p, [%1], %2;\nselp.u32 %0, 1, 0, p;\n}" : "=r"(ok) : "r"(bar), "r"(parity) : "memory");
  return ok;
}
__device__ __forceinline__ bool mbar_test(uint32_t bar, uint32_t parity) {
  uint32_t ok;
  asm volatile("{\n.reg .pred p;\nmbarrier.test_wait.parity.shared::cta.b64 p, [%1], %2;\nselp.u32 %0, 1, 0, p;\n}" : "=r"(ok) : "r"(bar), "r"(parity) : "memory");
  return ok;
}
__device__ __forceinline__ void mbar_wait(uint32_t bar, uint32_t parity) {
  asm volatile("{\n.reg .pred p, q;\n.reg .u32 n;\nmov.u32 n, 0;\nLW:\nmbarrier.try_wait.parity.shared::cta.b64 p, [%0], %1;\n"
               "add.u32 n, n, 1;\nsetp.lt.and.u32 q, n, 65536, !p;\n@q bra LW;\n}" ::"r"(bar), "r"(parity) : "memory");
}
__device__ __forceinline__ void mbar_spin(uint32_t bar, uint32_t parity) {
  asm volatile("{\n.reg .pred p, q;\n.reg .u32 n;\nmov.u32 n, 0;\nLW:\nmbarrier.test_wait.parity.shared::cta.b64 p, [%0], %1;\n"
               "add.u32 n, n, 1;\nsetp.lt.and.u32 q, n, 4194304, !p;\n@q bra LW;\n}" ::"r"(bar), "r"(parity) : "memory");
}
__device__ __forceinline__ bool elect_one() {
  uint32_t ok;
  asm volatile("{\n.reg .pred p;\nelect.sync _|p, 0xffffffff;\nselp.u32 %0, 1, 0, p;\n}" : "=r"(ok));
  return ok;
}
__device__ __forceinline__ void tma_2d(uint32_t dst, const CUtensorMap* map, int c0, int c1, uint32_t bar) {
  asm volatile("cp.async.bulk.tensor.2d.shared::cluster.global.mbarrier::complete_tx::bytes [%0], [%1, {%3, %4}], [%2];"
               ::"r"(dst), "l"(map), "r"(bar), "r"(c0), "r"(c1) : "memory");
}
__device__ __forceinline__ void tma_3d(uint32_t dst, const CUtensorMap* map, int c0, int c1, int c2, uint32_t bar) {
  asm volatile("cp.async.bulk.tensor.3d.shared::cluster.global.mbarrier::complete_tx::bytes [%0], [%1, {%3, %4, %5}], [%2];"
               ::"r"(dst), "l"(map), "r"(bar), "r"(c0), "r"(c1), "r"(c2) : "memory");
}
__device__ __forceinline__ void tma_4d(uint32_t dst, const CUtensorMap* map, int c0, int c1, int c2, int c3, uint32_t bar) {
  asm volatile("cp.async.bulk.tensor.4d.shared::cluster.global.mbarrier::complete_tx::bytes [%0], [%1, {%3, %4, %5, %6}], [%2];"
               ::"r"(dst), "l"(map), "r"(bar), "r"(c0), "r"(c1), "r"(c2), "r"(c3) : "memory");
}
__device__ __forceinline__ void tma_5d(uint32_t dst, const CUtensorMap* map, int c0, int c1, int c2, int c3, int c4, uint32_t bar) {
  asm volatile("cp.async.bulk.tensor.5d.shared::cluster.global.mbarrier::complete_tx::bytes [%0], [%1, {%3, %4, %5, %6, %7}], [%2];"
               ::"r"(dst), "l"(map), "r"(bar), "r"(c0), "r"(c1), "r"(c2), "r"(c3), "r"(c4) : "memory");
}
__device__ __forceinline__ void tma_store_3d(const CUtensorMap* map, uint32_t src, int c0, int c1, int c2) {
  asm volatile("cp.async.bulk.tensor.3d.global.shared::cta.bulk_group [%0, {%2, %3, %4}], [%1];"
               ::"l"(map), "r"(src), "r"(c0), "r"(c1), "r"(c2) : "memory");
}
__device__ __forceinline__ void bulk_g2s(uint32_t dst, const void* src, uint32_t bytes, uint32_t bar) {
  asm volatile("cp.async.bulk.shared::cluster.global.mbarrier::complete_tx::bytes [%0], [%1], %2, [%3];"
               ::"r"(dst), "l"(src), "r"(bytes), "r"(bar) : "memory");
}
__device__ __forceinline__ void prefetch_map(const CUtensorMap* m) { asm volatile("prefetch.tensormap [%0];" ::"l"(m) : "memory"); }
__device__ __forceinline__ uint32_t mapa(uint32_t addr, uint32_t rank) { uint32_t r; asm volatile("mapa.shared::cluster.u32 %0, %1, %2;" : "=r"(r) : "r"(addr), "r"(rank)); return r; }
__device__ __forceinline__ void cluster_sync() { asm volatile("barrier.cluster.arrive.release.aligned;\nbarrier.cluster.wait.acquire.aligned;" ::: "memory"); }
__device__ __forceinline__ void fence_async_smem() { asm volatile("fence.proxy.async.shared::cta;" ::: "memory"); }
__device__ __forceinline__ void wg_fence() { asm volatile("wgmma.fence.sync.aligned;" ::: "memory"); }
__device__ __forceinline__ void wg_commit() { asm volatile("wgmma.commit_group.sync.aligned;" ::: "memory"); }
template <int N> __device__ __forceinline__ void wg_wait() { asm volatile("wgmma.wait_group.sync.aligned %0;" ::"n"(N) : "memory"); }
template <int N> __device__ __forceinline__ void reg_fence(float (&d)[N]) {
#pragma unroll
  for (int i = 0; i < N; i++) asm volatile("" : "+f"(d[i])::"memory");
}
__device__ __forceinline__ void named_bar(int id, int n) { asm volatile("bar.sync %0, %1;" ::"r"(id), "r"(n) : "memory"); }
__device__ __forceinline__ uint64_t mk_desc(uint32_t addr, uint32_t lbo, uint32_t sbo, uint32_t sw) {
  return (uint64_t)((addr & 0x3FFFF) >> 4) | ((uint64_t)(lbo >> 4) << 16) | ((uint64_t)(sbo >> 4) << 32) | ((uint64_t)sw << 62);
}
__device__ __forceinline__ uint32_t pack_bf16(float lo, float hi) {
  uint32_t r; asm("cvt.rn.bf16x2.f32 %0, %1, %2;" : "=r"(r) : "f"(hi), "f"(lo)); return r;
}
__device__ __forceinline__ float bf_lo(uint32_t v) { return __uint_as_float(v << 16); }
__device__ __forceinline__ float bf_hi(uint32_t v) { return __uint_as_float(v & 0xffff0000u); }
__device__ __forceinline__ float bf_round(float x) { return __bfloat162float(__float2bfloat16_rn(x)); }
__device__ __forceinline__ void st_async_v4(uint32_t addr, uint32_t a, uint32_t b, uint32_t c, uint32_t d, uint32_t bar) {
  asm volatile("st.async.weak.shared::cluster.mbarrier::complete_tx::bytes.v4.b32 [%0], {%1, %2, %3, %4}, [%5];"
               ::"r"(addr), "r"(a), "r"(b), "r"(c), "r"(d), "r"(bar) : "memory");
}
__device__ __forceinline__ void stmatrix_x4_t(uint32_t addr, uint32_t a, uint32_t b, uint32_t c, uint32_t d) {
  asm volatile("stmatrix.sync.aligned.m8n8.x4.trans.shared.b16 [%0], {%1, %2, %3, %4};" ::"r"(addr), "r"(a), "r"(b), "r"(c), "r"(d) : "memory");
}
__device__ __forceinline__ void ldmatrix_x4_t(uint32_t addr, uint32_t& a, uint32_t& b, uint32_t& c, uint32_t& d) {
  asm volatile("ldmatrix.sync.aligned.m8n8.x4.trans.shared.b16 {%0, %1, %2, %3}, [%4];" : "=r"(a), "=r"(b), "=r"(c), "=r"(d) : "r"(addr) : "memory");
}
__device__ __forceinline__ uint32_t lds32(uint32_t addr) { uint32_t v; asm volatile("ld.shared.b32 %0, [%1];" : "=r"(v) : "r"(addr) : "memory"); return v; }
__device__ __forceinline__ float geglu(float g, float u) {
  float z = g * fmaf(g * g, 0.0356774081f, 0.7978845608f);
  float t; asm("tanh.approx.f32 %0, %1;" : "=f"(t) : "f"(z));
  return (g * u) * fmaf(t, 0.5f, 0.5f);
}

__device__ __forceinline__ uint4 lds128(uint32_t addr) { uint4 v; asm volatile("ld.shared.v4.b32 {%0,%1,%2,%3}, [%4];" : "=r"(v.x), "=r"(v.y), "=r"(v.z), "=r"(v.w) : "r"(addr) : "memory"); return v; }
__device__ __forceinline__ void sts32(uint32_t addr, uint32_t v) { asm volatile("st.shared.b32 [%0], %1;" ::"r"(addr), "r"(v) : "memory"); }
__device__ __forceinline__ void stmatrix_x4(uint32_t addr, uint32_t a, uint32_t b, uint32_t c, uint32_t d) {
  asm volatile("stmatrix.sync.aligned.m8n8.x4.shared.b16 [%0], {%1, %2, %3, %4};" ::"r"(addr), "r"(a), "r"(b), "r"(c), "r"(d) : "memory");
}
__device__ __forceinline__ void ldmatrix_x4(uint32_t addr, uint32_t (&r)[4]) {
  asm volatile("ldmatrix.sync.aligned.m8n8.x4.shared.b16 {%0, %1, %2, %3}, [%4];" : "=r"(r[0]), "=r"(r[1]), "=r"(r[2]), "=r"(r[3]) : "r"(addr) : "memory");
}
__device__ __forceinline__ void sts128(uint32_t addr, uint4 v) { asm volatile("st.shared.v4.b32 [%0], {%1,%2,%3,%4};" ::"r"(addr), "r"(v.x), "r"(v.y), "r"(v.z), "r"(v.w) : "memory"); }
__device__ __forceinline__ void bulk_s2g(void* dst, uint32_t src, uint32_t bytes) {
  asm volatile("cp.async.bulk.global.shared::cta.bulk_group [%0], [%1], %2;" ::"l"(dst), "r"(src), "r"(bytes) : "memory");
}
__device__ __forceinline__ void tma_store_2d(const CUtensorMap* map, uint32_t src, int c0, int c1) {
  asm volatile("cp.async.bulk.tensor.2d.global.shared::cta.bulk_group [%0, {%2, %3}], [%1];" ::"l"(map), "r"(src), "r"(c0), "r"(c1) : "memory");
}
__device__ __forceinline__ void bulk_commit_wait() {
  asm volatile("cp.async.bulk.commit_group;" ::: "memory");
  asm volatile("cp.async.bulk.wait_group 0;" ::: "memory");
}
__device__ __forceinline__ void named_arrive(int id, int n) { asm volatile("bar.arrive %0, %1;" ::"r"(id), "r"(n) : "memory"); }
__device__ __forceinline__ void fence_async_all() { asm volatile("fence.proxy.async.global;" ::: "memory"); }
__device__ __forceinline__ void cnt_add(int idx) {
  asm volatile("red.release.gpu.global.add.u32 [%0], 1;" ::"l"(g_cnt + idx * 32) : "memory");
}
__device__ __forceinline__ void cnt_add_done(int idx) {
  asm volatile("red.relaxed.gpu.global.add.u32 [%0], 1;" ::"l"(g_cnt + idx * 32) : "memory");
}
__device__ __forceinline__ void cnt_wait(int idx, uint32_t target) {
  const unsigned int* p = g_cnt + idx * 32;
#pragma unroll 1
  for (int it = 0; it < (1 << 18); it++) {
    uint32_t v; asm volatile("ld.acquire.gpu.global.u32 %0, [%1];" : "=r"(v) : "l"(p) : "memory");
    if (v >= target) break;
  }
}
__device__ __forceinline__ void prefetch_l2(const void* p, uint32_t bytes) { asm volatile("cp.async.bulk.prefetch.L2.global [%0], %1;" ::"l"(p), "r"(bytes) : "memory"); }

template <int TB>
__device__ __forceinline__ void wg_ss128_init(float (&d)[64], uint64_t da, uint64_t db) {
  asm volatile(
    "wgmma.mma_async.sync.aligned.m64n128k16.f32.bf16.bf16 {%0, %1, %2, %3, %4, %5, %6, %7, %8, %9, %10, %11, %12, %13, %14, %15, %16, %17, %18, %19, %20, %21, %22, %23, %24, %25, %26, %27, %28, %29, %30, %31, %32, %33, %34, %35, %36, %37, %38, %39, %40, %41, %42, %43, %44, %45, %46, %47, %48, %49, %50, %51, %52, %53, %54, %55, %56, %57, %58, %59, %60, %61, %62, %63}, %64, %65, 0, 1, 1, 0, %66;"
    : "=f"(d[0]), "=f"(d[1]), "=f"(d[2]), "=f"(d[3]), "=f"(d[4]), "=f"(d[5]), "=f"(d[6]), "=f"(d[7]), "=f"(d[8]), "=f"(d[9]), "=f"(d[10]), "=f"(d[11]), "=f"(d[12]), "=f"(d[13]), "=f"(d[14]), "=f"(d[15]), "=f"(d[16]), "=f"(d[17]), "=f"(d[18]), "=f"(d[19]), "=f"(d[20]), "=f"(d[21]), "=f"(d[22]), "=f"(d[23]), "=f"(d[24]), "=f"(d[25]), "=f"(d[26]), "=f"(d[27]), "=f"(d[28]), "=f"(d[29]), "=f"(d[30]), "=f"(d[31]), "=f"(d[32]), "=f"(d[33]), "=f"(d[34]), "=f"(d[35]), "=f"(d[36]), "=f"(d[37]), "=f"(d[38]), "=f"(d[39]), "=f"(d[40]), "=f"(d[41]), "=f"(d[42]), "=f"(d[43]), "=f"(d[44]), "=f"(d[45]), "=f"(d[46]), "=f"(d[47]), "=f"(d[48]), "=f"(d[49]), "=f"(d[50]), "=f"(d[51]), "=f"(d[52]), "=f"(d[53]), "=f"(d[54]), "=f"(d[55]), "=f"(d[56]), "=f"(d[57]), "=f"(d[58]), "=f"(d[59]), "=f"(d[60]), "=f"(d[61]), "=f"(d[62]), "=f"(d[63])
    : "l"(da), "l"(db), "n"(TB));
}
template <int TB>
__device__ __forceinline__ void wg_ss128(float (&d)[64], uint64_t da, uint64_t db) {
  asm volatile(
    "wgmma.mma_async.sync.aligned.m64n128k16.f32.bf16.bf16 {%0, %1, %2, %3, %4, %5, %6, %7, %8, %9, %10, %11, %12, %13, %14, %15, %16, %17, %18, %19, %20, %21, %22, %23, %24, %25, %26, %27, %28, %29, %30, %31, %32, %33, %34, %35, %36, %37, %38, %39, %40, %41, %42, %43, %44, %45, %46, %47, %48, %49, %50, %51, %52, %53, %54, %55, %56, %57, %58, %59, %60, %61, %62, %63}, %64, %65, 1, 1, 1, 0, %66;"
    : "+f"(d[0]), "+f"(d[1]), "+f"(d[2]), "+f"(d[3]), "+f"(d[4]), "+f"(d[5]), "+f"(d[6]), "+f"(d[7]), "+f"(d[8]), "+f"(d[9]), "+f"(d[10]), "+f"(d[11]), "+f"(d[12]), "+f"(d[13]), "+f"(d[14]), "+f"(d[15]), "+f"(d[16]), "+f"(d[17]), "+f"(d[18]), "+f"(d[19]), "+f"(d[20]), "+f"(d[21]), "+f"(d[22]), "+f"(d[23]), "+f"(d[24]), "+f"(d[25]), "+f"(d[26]), "+f"(d[27]), "+f"(d[28]), "+f"(d[29]), "+f"(d[30]), "+f"(d[31]), "+f"(d[32]), "+f"(d[33]), "+f"(d[34]), "+f"(d[35]), "+f"(d[36]), "+f"(d[37]), "+f"(d[38]), "+f"(d[39]), "+f"(d[40]), "+f"(d[41]), "+f"(d[42]), "+f"(d[43]), "+f"(d[44]), "+f"(d[45]), "+f"(d[46]), "+f"(d[47]), "+f"(d[48]), "+f"(d[49]), "+f"(d[50]), "+f"(d[51]), "+f"(d[52]), "+f"(d[53]), "+f"(d[54]), "+f"(d[55]), "+f"(d[56]), "+f"(d[57]), "+f"(d[58]), "+f"(d[59]), "+f"(d[60]), "+f"(d[61]), "+f"(d[62]), "+f"(d[63])
    : "l"(da), "l"(db), "n"(TB));
}
template <int TB>
__device__ __forceinline__ void wg_ss256(float (&d)[128], uint64_t da, uint64_t db) {
  asm volatile(
    "wgmma.mma_async.sync.aligned.m64n256k16.f32.bf16.bf16 {%0, %1, %2, %3, %4, %5, %6, %7, %8, %9, %10, %11, %12, %13, %14, %15, %16, %17, %18, %19, %20, %21, %22, %23, %24, %25, %26, %27, %28, %29, %30, %31, %32, %33, %34, %35, %36, %37, %38, %39, %40, %41, %42, %43, %44, %45, %46, %47, %48, %49, %50, %51, %52, %53, %54, %55, %56, %57, %58, %59, %60, %61, %62, %63, %64, %65, %66, %67, %68, %69, %70, %71, %72, %73, %74, %75, %76, %77, %78, %79, %80, %81, %82, %83, %84, %85, %86, %87, %88, %89, %90, %91, %92, %93, %94, %95, %96, %97, %98, %99, %100, %101, %102, %103, %104, %105, %106, %107, %108, %109, %110, %111, %112, %113, %114, %115, %116, %117, %118, %119, %120, %121, %122, %123, %124, %125, %126, %127}, %128, %129, 1, 1, 1, 0, %130;"
    : "+f"(d[0]), "+f"(d[1]), "+f"(d[2]), "+f"(d[3]), "+f"(d[4]), "+f"(d[5]), "+f"(d[6]), "+f"(d[7]), "+f"(d[8]), "+f"(d[9]), "+f"(d[10]), "+f"(d[11]), "+f"(d[12]), "+f"(d[13]), "+f"(d[14]), "+f"(d[15]), "+f"(d[16]), "+f"(d[17]), "+f"(d[18]), "+f"(d[19]), "+f"(d[20]), "+f"(d[21]), "+f"(d[22]), "+f"(d[23]), "+f"(d[24]), "+f"(d[25]), "+f"(d[26]), "+f"(d[27]), "+f"(d[28]), "+f"(d[29]), "+f"(d[30]), "+f"(d[31]), "+f"(d[32]), "+f"(d[33]), "+f"(d[34]), "+f"(d[35]), "+f"(d[36]), "+f"(d[37]), "+f"(d[38]), "+f"(d[39]), "+f"(d[40]), "+f"(d[41]), "+f"(d[42]), "+f"(d[43]), "+f"(d[44]), "+f"(d[45]), "+f"(d[46]), "+f"(d[47]), "+f"(d[48]), "+f"(d[49]), "+f"(d[50]), "+f"(d[51]), "+f"(d[52]), "+f"(d[53]), "+f"(d[54]), "+f"(d[55]), "+f"(d[56]), "+f"(d[57]), "+f"(d[58]), "+f"(d[59]), "+f"(d[60]), "+f"(d[61]), "+f"(d[62]), "+f"(d[63]), "+f"(d[64]), "+f"(d[65]), "+f"(d[66]), "+f"(d[67]), "+f"(d[68]), "+f"(d[69]), "+f"(d[70]), "+f"(d[71]), "+f"(d[72]), "+f"(d[73]), "+f"(d[74]), "+f"(d[75]), "+f"(d[76]), "+f"(d[77]), "+f"(d[78]), "+f"(d[79]), "+f"(d[80]), "+f"(d[81]), "+f"(d[82]), "+f"(d[83]), "+f"(d[84]), "+f"(d[85]), "+f"(d[86]), "+f"(d[87]), "+f"(d[88]), "+f"(d[89]), "+f"(d[90]), "+f"(d[91]), "+f"(d[92]), "+f"(d[93]), "+f"(d[94]), "+f"(d[95]), "+f"(d[96]), "+f"(d[97]), "+f"(d[98]), "+f"(d[99]), "+f"(d[100]), "+f"(d[101]), "+f"(d[102]), "+f"(d[103]), "+f"(d[104]), "+f"(d[105]), "+f"(d[106]), "+f"(d[107]), "+f"(d[108]), "+f"(d[109]), "+f"(d[110]), "+f"(d[111]), "+f"(d[112]), "+f"(d[113]), "+f"(d[114]), "+f"(d[115]), "+f"(d[116]), "+f"(d[117]), "+f"(d[118]), "+f"(d[119]), "+f"(d[120]), "+f"(d[121]), "+f"(d[122]), "+f"(d[123]), "+f"(d[124]), "+f"(d[125]), "+f"(d[126]), "+f"(d[127])
    : "l"(da), "l"(db), "n"(TB));
}
template <int TB>
__device__ __forceinline__ void wg_ss32(float (&d)[16], uint64_t da, uint64_t db) {
  asm volatile(
    "wgmma.mma_async.sync.aligned.m64n32k16.f32.bf16.bf16 {%0, %1, %2, %3, %4, %5, %6, %7, %8, %9, %10, %11, %12, %13, %14, %15}, %16, %17, 1, 1, 1, 0, %18;"
    : "+f"(d[0]), "+f"(d[1]), "+f"(d[2]), "+f"(d[3]), "+f"(d[4]), "+f"(d[5]), "+f"(d[6]), "+f"(d[7]), "+f"(d[8]), "+f"(d[9]), "+f"(d[10]), "+f"(d[11]), "+f"(d[12]), "+f"(d[13]), "+f"(d[14]), "+f"(d[15])
    : "l"(da), "l"(db), "n"(TB));
}
template <int TB>
__device__ __forceinline__ void wg_rs256(float (&d)[128], uint32_t a0, uint32_t a1, uint32_t a2, uint32_t a3, uint64_t db) {
  asm volatile(
    "wgmma.mma_async.sync.aligned.m64n256k16.f32.bf16.bf16 {%0, %1, %2, %3, %4, %5, %6, %7, %8, %9, %10, %11, %12, %13, %14, %15, %16, %17, %18, %19, %20, %21, %22, %23, %24, %25, %26, %27, %28, %29, %30, %31, %32, %33, %34, %35, %36, %37, %38, %39, %40, %41, %42, %43, %44, %45, %46, %47, %48, %49, %50, %51, %52, %53, %54, %55, %56, %57, %58, %59, %60, %61, %62, %63, %64, %65, %66, %67, %68, %69, %70, %71, %72, %73, %74, %75, %76, %77, %78, %79, %80, %81, %82, %83, %84, %85, %86, %87, %88, %89, %90, %91, %92, %93, %94, %95, %96, %97, %98, %99, %100, %101, %102, %103, %104, %105, %106, %107, %108, %109, %110, %111, %112, %113, %114, %115, %116, %117, %118, %119, %120, %121, %122, %123, %124, %125, %126, %127}, {%128, %129, %130, %131}, %132, 1, 1, 1, %133;"
    : "+f"(d[0]), "+f"(d[1]), "+f"(d[2]), "+f"(d[3]), "+f"(d[4]), "+f"(d[5]), "+f"(d[6]), "+f"(d[7]), "+f"(d[8]), "+f"(d[9]), "+f"(d[10]), "+f"(d[11]), "+f"(d[12]), "+f"(d[13]), "+f"(d[14]), "+f"(d[15]), "+f"(d[16]), "+f"(d[17]), "+f"(d[18]), "+f"(d[19]), "+f"(d[20]), "+f"(d[21]), "+f"(d[22]), "+f"(d[23]), "+f"(d[24]), "+f"(d[25]), "+f"(d[26]), "+f"(d[27]), "+f"(d[28]), "+f"(d[29]), "+f"(d[30]), "+f"(d[31]), "+f"(d[32]), "+f"(d[33]), "+f"(d[34]), "+f"(d[35]), "+f"(d[36]), "+f"(d[37]), "+f"(d[38]), "+f"(d[39]), "+f"(d[40]), "+f"(d[41]), "+f"(d[42]), "+f"(d[43]), "+f"(d[44]), "+f"(d[45]), "+f"(d[46]), "+f"(d[47]), "+f"(d[48]), "+f"(d[49]), "+f"(d[50]), "+f"(d[51]), "+f"(d[52]), "+f"(d[53]), "+f"(d[54]), "+f"(d[55]), "+f"(d[56]), "+f"(d[57]), "+f"(d[58]), "+f"(d[59]), "+f"(d[60]), "+f"(d[61]), "+f"(d[62]), "+f"(d[63]), "+f"(d[64]), "+f"(d[65]), "+f"(d[66]), "+f"(d[67]), "+f"(d[68]), "+f"(d[69]), "+f"(d[70]), "+f"(d[71]), "+f"(d[72]), "+f"(d[73]), "+f"(d[74]), "+f"(d[75]), "+f"(d[76]), "+f"(d[77]), "+f"(d[78]), "+f"(d[79]), "+f"(d[80]), "+f"(d[81]), "+f"(d[82]), "+f"(d[83]), "+f"(d[84]), "+f"(d[85]), "+f"(d[86]), "+f"(d[87]), "+f"(d[88]), "+f"(d[89]), "+f"(d[90]), "+f"(d[91]), "+f"(d[92]), "+f"(d[93]), "+f"(d[94]), "+f"(d[95]), "+f"(d[96]), "+f"(d[97]), "+f"(d[98]), "+f"(d[99]), "+f"(d[100]), "+f"(d[101]), "+f"(d[102]), "+f"(d[103]), "+f"(d[104]), "+f"(d[105]), "+f"(d[106]), "+f"(d[107]), "+f"(d[108]), "+f"(d[109]), "+f"(d[110]), "+f"(d[111]), "+f"(d[112]), "+f"(d[113]), "+f"(d[114]), "+f"(d[115]), "+f"(d[116]), "+f"(d[117]), "+f"(d[118]), "+f"(d[119]), "+f"(d[120]), "+f"(d[121]), "+f"(d[122]), "+f"(d[123]), "+f"(d[124]), "+f"(d[125]), "+f"(d[126]), "+f"(d[127])
    : "r"(a0), "r"(a1), "r"(a2), "r"(a3), "l"(db), "n"(TB));
}
template <int TB>
__device__ __forceinline__ void wg_rs32(float (&d)[16], uint32_t a0, uint32_t a1, uint32_t a2, uint32_t a3, uint64_t db) {
  asm volatile(
    "wgmma.mma_async.sync.aligned.m64n32k16.f32.bf16.bf16 {%0, %1, %2, %3, %4, %5, %6, %7, %8, %9, %10, %11, %12, %13, %14, %15}, {%16, %17, %18, %19}, %20, 1, 1, 1, %21;"
    : "+f"(d[0]), "+f"(d[1]), "+f"(d[2]), "+f"(d[3]), "+f"(d[4]), "+f"(d[5]), "+f"(d[6]), "+f"(d[7]), "+f"(d[8]), "+f"(d[9]), "+f"(d[10]), "+f"(d[11]), "+f"(d[12]), "+f"(d[13]), "+f"(d[14]), "+f"(d[15])
    : "r"(a0), "r"(a1), "r"(a2), "r"(a3), "l"(db), "n"(TB));
}
template <int TB>
__device__ __forceinline__ void wg_cv128(float (&d)[64], uint32_t a0, uint32_t a1, uint32_t a2, uint32_t a3, uint64_t db) {
  asm volatile(
    "wgmma.mma_async.sync.aligned.m64n128k16.f32.bf16.bf16 {%0, %1, %2, %3, %4, %5, %6, %7, %8, %9, %10, %11, %12, %13, %14, %15, %16, %17, %18, %19, %20, %21, %22, %23, %24, %25, %26, %27, %28, %29, %30, %31, %32, %33, %34, %35, %36, %37, %38, %39, %40, %41, %42, %43, %44, %45, %46, %47, %48, %49, %50, %51, %52, %53, %54, %55, %56, %57, %58, %59, %60, %61, %62, %63}, {%64, %65, %66, %67}, %68, 1, 1, 1, %69;"
    : "+f"(d[0]), "+f"(d[1]), "+f"(d[2]), "+f"(d[3]), "+f"(d[4]), "+f"(d[5]), "+f"(d[6]), "+f"(d[7]), "+f"(d[8]), "+f"(d[9]), "+f"(d[10]), "+f"(d[11]), "+f"(d[12]), "+f"(d[13]), "+f"(d[14]), "+f"(d[15]), "+f"(d[16]), "+f"(d[17]), "+f"(d[18]), "+f"(d[19]), "+f"(d[20]), "+f"(d[21]), "+f"(d[22]), "+f"(d[23]), "+f"(d[24]), "+f"(d[25]), "+f"(d[26]), "+f"(d[27]), "+f"(d[28]), "+f"(d[29]), "+f"(d[30]), "+f"(d[31]), "+f"(d[32]), "+f"(d[33]), "+f"(d[34]), "+f"(d[35]), "+f"(d[36]), "+f"(d[37]), "+f"(d[38]), "+f"(d[39]), "+f"(d[40]), "+f"(d[41]), "+f"(d[42]), "+f"(d[43]), "+f"(d[44]), "+f"(d[45]), "+f"(d[46]), "+f"(d[47]), "+f"(d[48]), "+f"(d[49]), "+f"(d[50]), "+f"(d[51]), "+f"(d[52]), "+f"(d[53]), "+f"(d[54]), "+f"(d[55]), "+f"(d[56]), "+f"(d[57]), "+f"(d[58]), "+f"(d[59]), "+f"(d[60]), "+f"(d[61]), "+f"(d[62]), "+f"(d[63])
    : "r"(a0), "r"(a1), "r"(a2), "r"(a3), "l"(db), "n"(TB));
}
template <int TB>
__device__ __forceinline__ void wg_cv96(float (&d)[48], uint32_t a0, uint32_t a1, uint32_t a2, uint32_t a3, uint64_t db) {
  asm volatile(
    "wgmma.mma_async.sync.aligned.m64n96k16.f32.bf16.bf16 {%0, %1, %2, %3, %4, %5, %6, %7, %8, %9, %10, %11, %12, %13, %14, %15, %16, %17, %18, %19, %20, %21, %22, %23, %24, %25, %26, %27, %28, %29, %30, %31, %32, %33, %34, %35, %36, %37, %38, %39, %40, %41, %42, %43, %44, %45, %46, %47}, {%48, %49, %50, %51}, %52, 1, 1, 1, %53;"
    : "+f"(d[0]), "+f"(d[1]), "+f"(d[2]), "+f"(d[3]), "+f"(d[4]), "+f"(d[5]), "+f"(d[6]), "+f"(d[7]), "+f"(d[8]), "+f"(d[9]), "+f"(d[10]), "+f"(d[11]), "+f"(d[12]), "+f"(d[13]), "+f"(d[14]), "+f"(d[15]), "+f"(d[16]), "+f"(d[17]), "+f"(d[18]), "+f"(d[19]), "+f"(d[20]), "+f"(d[21]), "+f"(d[22]), "+f"(d[23]), "+f"(d[24]), "+f"(d[25]), "+f"(d[26]), "+f"(d[27]), "+f"(d[28]), "+f"(d[29]), "+f"(d[30]), "+f"(d[31]), "+f"(d[32]), "+f"(d[33]), "+f"(d[34]), "+f"(d[35]), "+f"(d[36]), "+f"(d[37]), "+f"(d[38]), "+f"(d[39]), "+f"(d[40]), "+f"(d[41]), "+f"(d[42]), "+f"(d[43]), "+f"(d[44]), "+f"(d[45]), "+f"(d[46]), "+f"(d[47])
    : "r"(a0), "r"(a1), "r"(a2), "r"(a3), "l"(db), "n"(TB));
}
template <int TB>
__device__ __forceinline__ void wg_cv64(float (&d)[32], uint32_t a0, uint32_t a1, uint32_t a2, uint32_t a3, uint64_t db) {
  asm volatile(
    "wgmma.mma_async.sync.aligned.m64n64k16.f32.bf16.bf16 {%0, %1, %2, %3, %4, %5, %6, %7, %8, %9, %10, %11, %12, %13, %14, %15, %16, %17, %18, %19, %20, %21, %22, %23, %24, %25, %26, %27, %28, %29, %30, %31}, {%32, %33, %34, %35}, %36, 1, 1, 1, %37;"
    : "+f"(d[0]), "+f"(d[1]), "+f"(d[2]), "+f"(d[3]), "+f"(d[4]), "+f"(d[5]), "+f"(d[6]), "+f"(d[7]), "+f"(d[8]), "+f"(d[9]), "+f"(d[10]), "+f"(d[11]), "+f"(d[12]), "+f"(d[13]), "+f"(d[14]), "+f"(d[15]), "+f"(d[16]), "+f"(d[17]), "+f"(d[18]), "+f"(d[19]), "+f"(d[20]), "+f"(d[21]), "+f"(d[22]), "+f"(d[23]), "+f"(d[24]), "+f"(d[25]), "+f"(d[26]), "+f"(d[27]), "+f"(d[28]), "+f"(d[29]), "+f"(d[30]), "+f"(d[31])
    : "r"(a0), "r"(a1), "r"(a2), "r"(a3), "l"(db), "n"(TB));
}
template <int TB>
__device__ __forceinline__ void wg_rs256_init(float (&d)[128], uint32_t a0, uint32_t a1, uint32_t a2, uint32_t a3, uint64_t db) {
  asm volatile(
    "wgmma.mma_async.sync.aligned.m64n256k16.f32.bf16.bf16 {%0, %1, %2, %3, %4, %5, %6, %7, %8, %9, %10, %11, %12, %13, %14, %15, %16, %17, %18, %19, %20, %21, %22, %23, %24, %25, %26, %27, %28, %29, %30, %31, %32, %33, %34, %35, %36, %37, %38, %39, %40, %41, %42, %43, %44, %45, %46, %47, %48, %49, %50, %51, %52, %53, %54, %55, %56, %57, %58, %59, %60, %61, %62, %63, %64, %65, %66, %67, %68, %69, %70, %71, %72, %73, %74, %75, %76, %77, %78, %79, %80, %81, %82, %83, %84, %85, %86, %87, %88, %89, %90, %91, %92, %93, %94, %95, %96, %97, %98, %99, %100, %101, %102, %103, %104, %105, %106, %107, %108, %109, %110, %111, %112, %113, %114, %115, %116, %117, %118, %119, %120, %121, %122, %123, %124, %125, %126, %127}, {%128, %129, %130, %131}, %132, 0, 1, 1, %133;"
    : "=f"(d[0]), "=f"(d[1]), "=f"(d[2]), "=f"(d[3]), "=f"(d[4]), "=f"(d[5]), "=f"(d[6]), "=f"(d[7]), "=f"(d[8]), "=f"(d[9]), "=f"(d[10]), "=f"(d[11]), "=f"(d[12]), "=f"(d[13]), "=f"(d[14]), "=f"(d[15]), "=f"(d[16]), "=f"(d[17]), "=f"(d[18]), "=f"(d[19]), "=f"(d[20]), "=f"(d[21]), "=f"(d[22]), "=f"(d[23]), "=f"(d[24]), "=f"(d[25]), "=f"(d[26]), "=f"(d[27]), "=f"(d[28]), "=f"(d[29]), "=f"(d[30]), "=f"(d[31]), "=f"(d[32]), "=f"(d[33]), "=f"(d[34]), "=f"(d[35]), "=f"(d[36]), "=f"(d[37]), "=f"(d[38]), "=f"(d[39]), "=f"(d[40]), "=f"(d[41]), "=f"(d[42]), "=f"(d[43]), "=f"(d[44]), "=f"(d[45]), "=f"(d[46]), "=f"(d[47]), "=f"(d[48]), "=f"(d[49]), "=f"(d[50]), "=f"(d[51]), "=f"(d[52]), "=f"(d[53]), "=f"(d[54]), "=f"(d[55]), "=f"(d[56]), "=f"(d[57]), "=f"(d[58]), "=f"(d[59]), "=f"(d[60]), "=f"(d[61]), "=f"(d[62]), "=f"(d[63]), "=f"(d[64]), "=f"(d[65]), "=f"(d[66]), "=f"(d[67]), "=f"(d[68]), "=f"(d[69]), "=f"(d[70]), "=f"(d[71]), "=f"(d[72]), "=f"(d[73]), "=f"(d[74]), "=f"(d[75]), "=f"(d[76]), "=f"(d[77]), "=f"(d[78]), "=f"(d[79]), "=f"(d[80]), "=f"(d[81]), "=f"(d[82]), "=f"(d[83]), "=f"(d[84]), "=f"(d[85]), "=f"(d[86]), "=f"(d[87]), "=f"(d[88]), "=f"(d[89]), "=f"(d[90]), "=f"(d[91]), "=f"(d[92]), "=f"(d[93]), "=f"(d[94]), "=f"(d[95]), "=f"(d[96]), "=f"(d[97]), "=f"(d[98]), "=f"(d[99]), "=f"(d[100]), "=f"(d[101]), "=f"(d[102]), "=f"(d[103]), "=f"(d[104]), "=f"(d[105]), "=f"(d[106]), "=f"(d[107]), "=f"(d[108]), "=f"(d[109]), "=f"(d[110]), "=f"(d[111]), "=f"(d[112]), "=f"(d[113]), "=f"(d[114]), "=f"(d[115]), "=f"(d[116]), "=f"(d[117]), "=f"(d[118]), "=f"(d[119]), "=f"(d[120]), "=f"(d[121]), "=f"(d[122]), "=f"(d[123]), "=f"(d[124]), "=f"(d[125]), "=f"(d[126]), "=f"(d[127])
    : "r"(a0), "r"(a1), "r"(a2), "r"(a3), "l"(db), "n"(TB));
}
template <int TB>
__device__ __forceinline__ void wg_rs32_init(float (&d)[16], uint32_t a0, uint32_t a1, uint32_t a2, uint32_t a3, uint64_t db) {
  asm volatile(
    "wgmma.mma_async.sync.aligned.m64n32k16.f32.bf16.bf16 {%0, %1, %2, %3, %4, %5, %6, %7, %8, %9, %10, %11, %12, %13, %14, %15}, {%16, %17, %18, %19}, %20, 0, 1, 1, %21;"
    : "=f"(d[0]), "=f"(d[1]), "=f"(d[2]), "=f"(d[3]), "=f"(d[4]), "=f"(d[5]), "=f"(d[6]), "=f"(d[7]), "=f"(d[8]), "=f"(d[9]), "=f"(d[10]), "=f"(d[11]), "=f"(d[12]), "=f"(d[13]), "=f"(d[14]), "=f"(d[15])
    : "r"(a0), "r"(a1), "r"(a2), "r"(a3), "l"(db), "n"(TB));
}

#define FULLW() mbar_wait(bar + B_FULL + 8 * slot, ph)
#define EMPTYW() mbar_wait(bar + B_EMPTY + 8 * slot, ph)
constexpr int NST = 7, SLOT = 9216;
constexpr uint32_t SM_XN = 0, SM_HIN = 147456, SM_RING = 163840, SM_BAR = SM_RING + 7 * SLOT;
constexpr uint32_t SM_KD = SM_BAR + 256, SMEM_BYTES = SM_KD + 3840;
constexpr uint32_t B_FULL = 0, B_EMPTY = 56, B_XN = 112, B_K2048 = 176, B_HF = 184, B_HE = 200, B_CV = 216, B_PT = 224, B_YT = 232, B_SG = 240, B_X = 248;
constexpr uint32_t PR_LN = 65536, PR_PAR = 98304, PR_K0 = SM_HIN + 12288;
constexpr uint32_t T_U = 81920, T_KP = 99328, T_K0 = 133120, T_YT = 81920, T_PART = SM_HIN;
constexpr uint32_t U_BYTES = U_LEN * 2, KP_BYTES = KP_LEN * 4, IMG = 18432;

struct Params {
  CUtensorMap xn, gate, up, dn, dn5, dp, dp5, x, x5, y, y5, out, out5;
  const __nv_bfloat16 *xp, *logA, *Aim, *Cre, *Cim, *logdt, *Dsk;
};

__device__ __forceinline__ float us2f(uint32_t v) { return __uint_as_float(v << 16); }
struct KgIn { uint32_t la, ai, cr, ci, ldt, dsk; };
__device__ __forceinline__ void kgen_load(const Params& p, int ch0, int tid, KgIn& in) {
  const int e = ch0 * (NM_ / 2) + tid;
  in.la = __ldg((const uint32_t*)p.logA + e); in.ai = __ldg((const uint32_t*)p.Aim + e);
  in.cr = __ldg((const uint32_t*)p.Cre + e); in.ci = __ldg((const uint32_t*)p.Cim + e);
  in.ldt = __ldg((const unsigned short*)p.logdt + ch0 + (tid >> 6)); in.dsk = __ldg((const unsigned short*)p.Dsk + ch0 + (tid >> 6));
}
struct KgState { float acc[5][4]; float v; };
struct cf { float r, i; };
__device__ __forceinline__ cf cmul(cf a, cf b) { return {fmaf(a.r, b.r, -(a.i * b.i)), fmaf(a.r, b.i, a.i * b.r)}; }
__device__ __forceinline__ cf csq(cf a) { return {fmaf(a.r, a.r, -(a.i * a.i)), (a.r + a.r) * a.i}; }
__device__ __forceinline__ cf cexp2(float lm, float th) {
  float m; asm("ex2.approx.ftz.f32 %0, %1;" : "=f"(m) : "f"(lm));
  return {m * __cosf(th), m * __sinf(th)};
}
__device__ __forceinline__ float turns(float w) { return (w - rintf(w)) * 6.283185307179586f; }
__device__ __forceinline__ void kgen_params(unsigned char* sm, int tid, KgIn in, KgState& st) {
  const int warp = tid >> 5, lane = tid & 31;
  float4* par = (float4*)(sm + PR_PAR + warp * 6144) + lane;
  const float dt = bf_round(expf(bf_lo(in.ldt)));
  float v = 0.f;
#pragma unroll 1
  for (int r = 0; r < 2; r++) {
    const float x = -bf_round(expf(bf_lo(in.la))) * dt * 1.4426950408889634f;
    const float w = bf_lo(in.ai) * dt * 0.15915494309189535f;
    const cf c = {2.f * bf_lo(in.cr) * dt, 2.f * bf_lo(in.ci) * dt};
    const cf e2 = cexp2(2.f * x, turns(2.f * w)), e64 = cexp2(64.f * x, turns(64.f * w));
    const cf e4 = csq(e2), e6 = cmul(e2, e4), e128 = csq(e64), e256 = csq(e128), e512 = csq(e256), e1024 = csq(e512);
    const cf c1 = cmul(c, e128), c256 = cmul(c, e256), c512 = cmul(c, e512), c4 = cmul(c, e1024);
    const cf c516 = cmul(c512, e4), c258 = cmul(c256, e2), c260 = cmul(c256, e4), c262 = cmul(c256, e6);
    v += fmaf(c4.r, e1024.r, -(c4.i * e1024.i));
    par[0] = make_float4(x, turns(w), turns(8.f * w), turns(128.f * w));
    par[64] = make_float4(c.r, c.i, c1.r, c1.i);
    par[128] = make_float4(c4.r, c4.i, e64.r, e64.i);
    par[192] = make_float4(c512.r, c512.i, c516.r, c516.i);
    par[256] = make_float4(c256.r, c256.i, c258.r, c258.i);
    par[320] = make_float4(c260.r, c260.i, c262.r, c262.i);
    par += 32;
    in.la >>= 16; in.ai >>= 16; in.cr >>= 16; in.ci >>= 16;
  }
#pragma unroll
  for (int o = 16; o; o >>= 1) v += __shfl_xor_sync(0xffffffffu, v, o);
  __syncwarp();
#pragma unroll
  for (int t = 0; t < 5; t++) { st.acc[t][0] = st.acc[t][1] = st.acc[t][2] = st.acc[t][3] = 0.f; }
  if (lane == 0 && !(warp & 1)) st.acc[0][0] = bf_lo(in.dsk);
  st.v = v;
}
__device__ __forceinline__ void kgen_steps(unsigned char* sm, int tid, KgState& st) {
  const int warp = tid >> 5, lane = tid & 31, g = lane >> 2, q = lane & 3;
  const float4* par = (const float4*)(sm + PR_PAR + warp * 6144) + q;
  const float2* p3 = (const float2*)(par + 192) + (g & 1);
  const float2* p2 = (const float2*)(par + 256 + 64 * ((g >> 1) & 1)) + (g & 1);
  const float g1 = (float)g, g8 = 8.f * g1, g128 = 128.f * g1;
  const int l1 = 4 * (g >> 1) + q, l2 = 4 * (g >> 2) + q;
#pragma unroll 4
  for (int ks = 0; ks < 16; ks++) {
    const float4 P = par[4 * ks], Q = par[64 + 4 * ks], R = par[128 + 4 * ks];
    const float2 c3 = p3[8 * ks], c2 = p2[8 * ks];
    const cf e = cexp2(P.x * g1, P.y * g1), a1 = cexp2(P.x * g8, P.z * g1), t = cexp2(P.x * g128, P.w * g1);
    const cf a2 = cmul(a1, cf{R.z, R.w});
    const cf t1 = {__shfl_sync(0xffffffffu, t.r, l1), __shfl_sync(0xffffffffu, t.i, l1)};
    const cf t2 = {__shfl_sync(0xffffffffu, t.r, l2), __shfl_sync(0xffffffffu, t.i, l2)};
    auto mma = [&](float (&d)[4], cf u, float cr, float ci) {
      const float b0 = fmaf(u.r, cr, -(u.i * ci)), b1 = fmaf(-u.r, ci, -(u.i * cr));
      asm("mma.sync.aligned.m16n8k8.row.col.f32.tf32.tf32.f32 {%0,%1,%2,%3}, {%4,%5,%6,%7}, {%8,%9}, {%0,%1,%2,%3};"
          : "+f"(d[0]), "+f"(d[1]), "+f"(d[2]), "+f"(d[3])
          : "r"(__float_as_uint(a1.r)), "r"(__float_as_uint(a2.r)), "r"(__float_as_uint(a1.i)), "r"(__float_as_uint(a2.i)),
            "r"(__float_as_uint(b0)), "r"(__float_as_uint(b1)));
    };
    mma(st.acc[0], e, Q.x, Q.y);
    mma(st.acc[1], e, Q.z, Q.w);
    mma(st.acc[4], t, R.x, R.y);
    mma(st.acc[2], t2, c2.x, c2.y);
    mma(st.acc[3], t1, c3.x, c3.y);
  }
}
__device__ __forceinline__ void kgen_finish(unsigned char* sm, unsigned short* kd, unsigned short* k2048, int tid, KgState& st) {
  const int warp = tid >> 5, lane = tid & 31, g = lane >> 2, q = lane & 3;
  float4* red = (float4*)(sm + SM_HIN + (warp >> 1) * 3072) + lane;
  if (warp & 1) {
#pragma unroll
    for (int t = 0; t < 5; t++) red[t * 32] = make_float4(st.acc[t][0], st.acc[t][1], st.acc[t][2], st.acc[t][3]);
    red[160].x = st.v;
  }
  named_bar(3, 256);
  if (!(warp & 1)) {
    uint32_t lo[5], hi[5];
#pragma unroll
    for (int t = 0; t < 5; t++) {
      const float4 r = red[t * 32];
      lo[t] = pack_bf16(st.acc[t][0] + r.x, st.acc[t][1] + r.y); hi[t] = pack_bf16(st.acc[t][2] + r.z, st.acc[t][3] + r.w);
    }
    *k2048 = (unsigned short)pack_bf16(st.v + red[160].x, 0.f);
    uint32_t* kw = (uint32_t*)kd;
    kw[lane] = lo[0]; kw[32 + lane] = hi[0]; kw[64 + lane] = lo[1]; kw[96 + lane] = hi[1];
    kw[128 + 2 * g + (q & 1) + 32 * (q >> 1)] = lo[2]; kw[144 + 2 * g + (q & 1) + 32 * (q >> 1)] = hi[2];
    kw[192 + g + 16 * q] = lo[3]; kw[200 + g + 16 * q] = hi[3];
    kd[512 + g + 32 * q] = (unsigned short)lo[4]; kd[528 + g + 32 * q] = (unsigned short)(lo[4] >> 16);
    kd[520 + g + 32 * q] = (unsigned short)hi[4]; kd[536 + g + 32 * q] = (unsigned short)(hi[4] >> 16);
  }
}
constexpr int kd_index(int l) {
  if (l < 256) return l;
  const int sh = l < 512 ? 1 : l < 1024 ? 2 : 3;
  return ((l + (1 << (sh - 1)) - 1 + ((l >> sh) & 1)) >> sh) + 128 * sh;
}
struct KTab { unsigned int e[512 * 4]; };
constexpr KTab make_ktab() {
  KTab t = {};
  for (int it = 0; it < 511; it++) {
    const int l0 = 4 * it, b1 = kd_index(l0) & ~1;
    const unsigned int np = 0x54 + 0x22 * (l0 ? kd_index(l0 - 1) - b1 : 0);
    unsigned int n[4] = {0, 0, 0, 0};
    for (int k = 0; k < 4; k++) n[k] = 0x10 + 0x22 * (kd_index(l0 + k) - b1);
    t.e[4 * it] = 2 * b1 | ((b1 < 638 ? 4u : 0u) << 16);
    t.e[4 * it + 1] = (n[0] + 0x44) | (np << 8) | (n[1] << 16) | (n[0] << 24);
    t.e[4 * it + 2] = n[2] | (n[1] << 8) | (n[3] << 16) | (n[2] << 24);
    t.e[4 * it + 3] = l0 ? 0xffffffffu : 0xffffu;
  }
  return t;
}
__device__ __align__(16) const KTab g_ktab = make_ktab();
template <int NT>
__device__ __forceinline__ void kexpand(uint32_t sb, uint32_t k0, uint32_t k1, uint32_t k2048, int tid, uint4 e) {
#pragma unroll 1
  for (int it = tid; it < 511; it += NT) {
    const uint4 en = __ldg((const uint4*)g_ktab.e + min(it + NT, 511));
    const uint32_t o = e.x & 0xffffu, o2 = o + (e.x >> 16), dst = sb + T_KP + 64 + 16 * it;
#pragma unroll
    for (int c = 0; c < 4; c++) {
      const uint32_t a = c ? k1 + 1280 * (c - 1) : k0;
      const uint32_t x0 = lds32(a + o - 4), x1 = lds32(a + o), x2 = lds32(a + o2);
      sts128(dst + c * KP_BYTES, make_uint4(__byte_perm(x0, x1, e.y) & e.w, __byte_perm(x1, x2, e.y >> 16), __byte_perm(x1, x2, e.z), __byte_perm(x1, x2, e.z >> 16)));
    }
    e = en;
  }
  if (tid < 36) {
    const int c = tid / 9, i = tid - 9 * c;
    uint4 v = make_uint4(0u, 0u, 0u, 0u);
    if (i == 4) {
      uint32_t z, y;
      asm volatile("ld.shared.u16 %0, [%1];" : "=r"(z) : "r"(k2048 + 2 * c) : "memory");
      asm volatile("ld.shared.u16 %0, [%1];" : "=r"(y) : "r"((c ? k1 + 1280 * (c - 1) : k0) + 1278) : "memory");
      v = make_uint4(z | (y << 16), z * 0x10001u, z * 0x10001u, z * 0x10001u);
    }
    sts128(sb + T_KP + c * KP_BYTES + 16 * (i < 4 ? i : 511 + i), v);
  }
}

template <int NR>
__device__ __forceinline__ void conv_mma(float (&d)[NR], const uint32_t* a, uint64_t db) {
  if constexpr (NR == 64) wg_cv128<0>(d, a[0], a[1], a[2], a[3], db);
  else if constexpr (NR == 48) wg_cv96<0>(d, a[0], a[1], a[2], a[3], db);
  else if constexpr (NR == 32) wg_cv64<0>(d, a[0], a[1], a[2], a[3], db);
  else wg_rs32<0>(d, a[0], a[1], a[2], a[3], db);
}
__device__ __forceinline__ void conv_load(uint32_t (&a)[8], uint32_t o) {
#pragma unroll
  for (int c = 0; c < 2; c++) {
    a[4 * c + 0] = lds32(o + c * KP_BYTES); a[4 * c + 1] = lds32(o + c * KP_BYTES + 512);
    a[4 * c + 2] = lds32(o + c * KP_BYTES - 32); a[4 * c + 3] = lds32(o + c * KP_BYTES + 480);
  }
}
template <int NR>
__device__ __forceinline__ void conv_phase(float (&dA)[NR], float (&dB)[NR], uint32_t (&a)[4][8], uint32_t kp, uint64_t dU) {
#pragma unroll 1
  for (int i = 0; i < 2; i++) {
#pragma unroll
    for (int k = 0; k < 4; k++) {
      wg_fence();
      conv_mma<NR>(dA, a[k], dU - 2 * k); conv_mma<NR>(dB, a[k] + 4, dU - 2 * k + (U_BYTES >> 4));
      wg_commit();
      wg_wait<1>();
      if (k == 2 && i) kp += 64 * 24;
      conv_load(a[(k + 2) & 3], kp + 64 * (k + 2));
    }
    kp += 256;
    dU -= 8;
  }
  wg_wait<0>();
  reg_fence(dA); reg_fence(dB);
}
template <int NR>
__device__ __forceinline__ void upper_copy(float (&dst)[NR - 16], const float (&src)[NR]) {
#pragma unroll
  for (int i = 0; i < NR - 16; i++) asm volatile("mov.b32 %0, %1;" : "=f"(dst[i]) : "f"(src[i + 16]));
}
__device__ __forceinline__ void conv2(uint32_t sb, int wg, int w, int lane, int ch, int cnt) {
  const int g = lane >> 2, q = lane & 3;
  float dA[64], dB[64];
  uint32_t a[4][8];
  const uint32_t kp = sb + T_KP + 2 * wg * KP_BYTES + 4 * (16 + 256 * (w >> 1) + 8 * (w & 1) + g - 2 * q);
  const uint64_t dU = mk_desc(sb + T_U + 2 * wg * U_BYTES + 256, 16, 256, 3);
#pragma unroll
  for (int i = 0; i < 64; i++) { dA[i] = 0.f; dB[i] = 0.f; }
  conv_load(a[0], kp); conv_load(a[1], kp + 64);
  conv_phase<64>(dA, dB, a, kp, dU);
  float eA[48], eB[48];
  upper_copy<64>(eA, dA); upper_copy<64>(eB, dB);
  conv_phase<48>(eA, eB, a, kp + 2048, dU);
  float fA[32], fB[32];
  upper_copy<48>(fA, eA); upper_copy<48>(fB, eB);
  conv_phase<32>(fA, fB, a, kp + 4096, dU);
  float gA[16], gB[16];
  upper_copy<32>(gA, fA); upper_copy<32>(gB, fB);
  conv_phase<16>(gA, gB, a, kp + 6144, dU);
#pragma unroll
  for (int i = 0; i < 16; i++) {
    dA[16 + i] = eA[i]; dA[32 + i] = fA[i]; dA[48 + i] = gA[i];
    dB[16 + i] = eB[i]; dB[32 + i] = fB[i]; dB[48 + i] = gB[i];
  }
  PROF_T(53);
  float z[2][16][2];
#pragma unroll
  for (int m = 0; m < 16; m++)
#pragma unroll
    for (int e = 0; e < 2; e++) {
      z[0][m][e] = m ? dA[4 * m + e] + dA[4 * m - 2 + e] : dA[e];
      z[1][m][e] = m ? dB[4 * m + e] + dB[4 * m - 2 + e] : dB[e];
    }
  named_bar(1 + wg, 128);
  const uint32_t xb = sb + T_KP + 2 * wg * KP_BYTES;
  const uint32_t xw = xb + (w * 32 + lane) * 16, xr = xb + ((w ^ 2) * 32 + lane) * 16;
  float k[2][8][2];
  if (w < 2) {
#pragma unroll
    for (int c = 0; c < 2; c++)
#pragma unroll
      for (int m = 0; m < 8; m += 2) {
        sts128(xw + (4 * c + (m >> 1)) * 2048, make_uint4(__float_as_uint(z[c][8 + m][0]), __float_as_uint(z[c][8 + m][1]), __float_as_uint(z[c][9 + m][0]), __float_as_uint(z[c][9 + m][1])));
        k[c][m][0] = z[c][m][0]; k[c][m][1] = z[c][m][1]; k[c][m + 1][0] = z[c][m + 1][0]; k[c][m + 1][1] = z[c][m + 1][1];
      }
  } else {
#pragma unroll
    for (int c = 0; c < 2; c++)
#pragma unroll
      for (int m = 0; m < 8; m += 2) {
        sts128(xw + (4 * c + (m >> 1)) * 2048, m ? make_uint4(__float_as_uint(z[c][m - 2][0]), __float_as_uint(z[c][m - 2][1]), __float_as_uint(z[c][m - 1][0]), __float_as_uint(z[c][m - 1][1])) : make_uint4(0u, 0u, 0u, 0u));
        k[c][m][0] = z[c][6 + m][0]; k[c][m][1] = z[c][6 + m][1]; k[c][m + 1][0] = z[c][7 + m][0]; k[c][m + 1][1] = z[c][7 + m][1];
      }
  }
  named_bar(1 + wg, 128);
  const uint32_t yb = sb + T_U + 2 * wg * U_BYTES;
#pragma unroll
  for (int c = 0; c < 2; c++)
#pragma unroll
    for (int m = 0; m < 8; m += 4) {
      const uint4 u = lds128(xr + (4 * c + (m >> 1)) * 2048), v = lds128(xr + (4 * c + (m >> 1) + 1) * 2048);
      stmatrix_x4_t(yb + c * 4096 + (64 * (w >> 1) + 8 * m + lane) * 32 + 16 * (w & 1),
                    pack_bf16(k[c][m][0] + __uint_as_float(u.x), k[c][m][1] + __uint_as_float(u.y)), pack_bf16(k[c][m + 1][0] + __uint_as_float(u.z), k[c][m + 1][1] + __uint_as_float(u.w)),
                    pack_bf16(k[c][m + 2][0] + __uint_as_float(v.x), k[c][m + 2][1] + __uint_as_float(v.y)), pack_bf16(k[c][m + 3][0] + __uint_as_float(v.z), k[c][m + 3][1] + __uint_as_float(v.w)));
    }
  fence_async_smem();
  named_bar(1 + wg, 128);
  if (w == 0 && lane == 0) {
    PROF_T(54);
    bulk_s2g(g_y + (size_t)ch * L_, yb, 8192);
    bulk_commit_wait();
    PROF_T(55);
    cnt_add_done(cnt);
  }
  __syncwarp();
}

__global__ void __cluster_dims__(2, 1, 1) __launch_bounds__(384, 1) fused_kernel(const __grid_constant__ Params p) {
  extern __shared__ __align__(1024) unsigned char smem_raw[];
  const uint32_t sb = smem_u32(smem_raw);
  const uint32_t bar = sb + SM_BAR;
  const uint32_t vb = blockIdx.x;
  const int j = vb & 1, pair = vb >> 1, mt = pair & 15, sp = pair >> 4;
  const bool spare = pair >= 64;
  const int warp = __shfl_sync(0xffffffffu, threadIdx.x >> 5, 0), wg = warp >> 2, w = warp & 3;
  const int row0 = mt * 128 + (2 * sp + j) * 16;
  const int f0 = sp * 1152;
  const long long t_start = clock64();
  KgIn kin;
  if (wg < 2) kgen_load(p, spare ? 512 + ((int)vb - 128) * 16 : vb * 4, threadIdx.x, kin);
  if (threadIdx.x >= 288 && threadIdx.x < 301) prefetch_map(&p.xn + (threadIdx.x - 288));
  if (threadIdx.x == 256) {
    mbar_init(bar + B_X, 1);
    if (!spare) {
      mbar_expect_tx(bar + B_X, 16 * D_ * 2);
      bulk_g2s(sb + PR_LN, p.xp + (size_t)row0 * D_, 16 * D_ * 2, bar + B_X);
    }
#pragma unroll
    for (int i = 0; i < 30; i++) if (i != 22) mbar_init(bar + 8 * i, (i >= 7 && i < 14) ? 8 : (i == 27 && !spare) ? 4 : 1);
    mbar_init(bar + B_SG, 2);
    mbar_expect_tx(bar + B_HF, 8192); mbar_expect_tx(bar + B_HF + 8, 8192);
    asm volatile("fence.mbarrier_init.release.cluster;" ::: "memory");
    if (!spare) {
#pragma unroll 1
      for (int u = 0; u < NST; u++) {
        const uint32_t dst = sb + SM_RING + u * SLOT, fb = bar + B_FULL + 8 * u;
        mbar_expect_tx(fb, 8192);
        tma_2d(dst, &p.gate, f0 + 64 * j, 32 * u, fb);
        tma_2d(dst + 4096, &p.up, f0 + 64 * j, 32 * u, fb);
      }
    }
  }
  __syncthreads();
  asm volatile("barrier.cluster.arrive.relaxed.aligned;" ::: "memory");

  if (wg == 2) {
    const int t = threadIdx.x & 127, lane = t & 31;
    const bool el = elect_one();
    asm volatile("barrier.cluster.wait.aligned;" ::: "memory");
    asm volatile("setmaxnreg.dec.sync.aligned.u32 24;");
    if (w == 0) {
      if (!spare) {
        named_bar(5, 288);
        PROF_T(62);
        if (el) {
          bulk_s2g(g_xn + (size_t)row0 * D_, sb + PR_LN, 16 * D_ * 2);
          bulk_commit_wait();
          cnt_add_done(C_LN + mt);
        }
        __syncwarp();
        PROF_T(63);
        cnt_wait(C_LN + mt, 8);
        PROF_T(67);
        fence_async_all();
#pragma unroll 1
        for (int kb = 0; kb < 9; kb++) {
          if (kb == 6) named_bar(4, 384);
          if (el) {
            if (kb < 8) mbar_expect_tx(bar + B_XN + 8 * kb, kb < 7 ? 16384 : 32768);
            tma_2d(sb + SM_XN + kb * 16384, &p.xn, kb * 64, mt * 128, bar + B_XN + 8 * min(kb, 7));
          }
        }
        PROF_T(69);
        uint32_t slot = 0, ph = 0;
#pragma unroll 1
        for (int c = 0; c <= 9; c++) {
          const int fc = f0 + c * 128;
          if (c < 9) {
            for (int u = c ? 0 : NST; u < 18; u++) {
              EMPTYW();
              if (el) {
                const uint32_t dst = sb + SM_RING + slot * SLOT, fb = bar + B_FULL + 8 * slot;
                mbar_expect_tx(fb, 8192);
                tma_2d(dst, &p.gate, fc + 64 * j, 32 * u, fb);
                tma_2d(dst + 4096, &p.up, fc + 64 * j, 32 * u, fb);
              }
              if (++slot == NST) { slot = 0; ph ^= 1; }
            }
          }
          const int fp = (fc - 128 + 64 * (1 - j)) >> 3, fo = fc + 64 * j;
#pragma unroll
          for (int i = 0; i < 8; i++) {
            const bool isP = i < 4;
            const int u = i & 3;
            if (isP ? (c == 0) : (c == 9)) continue;
            EMPTYW();
            if (el) {
              const uint32_t dst = sb + SM_RING + slot * SLOT, fb = bar + B_FULL + 8 * slot;
              mbar_expect_tx(fb, 9216);
              if (isP) {
                tma_5d(dst, &p.dp, 0, 0, fp + 4 * (u >> 1), 2 * (u & 1), 4 * j, fb);
                tma_4d(dst + 8192, &p.dp5, 512 + 32 * j, 0, fp + 4 * (u >> 1), 2 * (u & 1), fb);
              } else {
                tma_3d(dst, &p.dn, 0, fo + 16 * u, 4 * j, fb);
                tma_2d(dst + 8192, &p.dn5, 512 + 32 * j, fo + 16 * u, fb);
              }
            }
            if (++slot == NST) { slot = 0; ph ^= 1; }
          }
        }
        const int ch0 = vb * 4;
        cnt_wait(C_U, 384);
        fence_async_all();
        if (el) {
          mbar_expect_tx(bar + B_CV, 4 * U_BYTES);
          bulk_g2s(sb + T_U, g_u + (size_t)ch0 * U_LEN, 4 * U_BYTES, bar + B_CV);
        }
        unsigned char* img = g_part + (size_t)(2 * mt + j) * 16 * IMG;
        mbar_wait(bar + B_SG, 0);
        PROF_T(71);
        if (lane < 15) {
          const int qi = lane / 5, pc = lane - 5 * qi, r = (sp + 1 + qi) & 3;
          bulk_s2g(img + (r * 4 + sp) * IMG + pc * 4096, sb + pc * 16384 + (r >> 1) * 8192 + (r & 1) * (pc < 4 ? 4096 : 2048), pc < 4 ? 4096 : 2048);
          bulk_commit_wait();
        } else if (lane == 15) {
          mbar_expect_tx(bar + B_PT, 4 * IMG);
#pragma unroll 1
          for (int i = 0; i < 4; i++) tma_2d(sb + T_PART + 3 * IMG + i * 4096, &p.x, 256 * j + 64 * i, mt * 128 + 32 * sp, bar + B_PT);
          tma_2d(sb + T_PART + 3 * IMG + 16384, &p.x5, 512 + 32 * j, mt * 128 + 32 * sp, bar + B_PT);
        }
        __syncwarp();
        PROF_T(72);
        if (el) cnt_add_done(C_PART + 2 * mt + j);
        PROF_T(73);
        cnt_wait(C_PART + 2 * mt + j, 4);
        fence_async_all();
        PROF_T(74);
        if (lane < 3) bulk_g2s(sb + T_PART + lane * IMG, img + (sp * 4 + ((sp + 1 + lane) & 3)) * IMG, IMG, bar + B_PT);
        cnt_wait(C_Y5, 32);
        cnt_wait(C_Y + (ch0 >> 8), 128);
        cnt_wait(C_Y + j, 128);
        PROF_T(75);
        fence_async_all();
        if (el) {
          mbar_expect_tx(bar + B_YT, IMG);
          tma_2d(sb + T_YT, &p.y, mt * 128 + 32 * sp, 256 * j, bar + B_YT);
          tma_2d(sb + T_YT + 16384, &p.y5, mt * 128 + 32 * sp, 512 + 32 * j, bar + B_YT);
        }
        cnt_wait(C_Y + (j ^ 1), 128);
      } else {
        named_bar(7, 288);
        cnt_wait(C_U, 384);
        fence_async_all();
#pragma unroll 1
        for (int grp = 0; grp < 4; grp++) {
          const int ch0 = 512 + ((int)vb - 128) * 16 + grp * 4;
          if (grp) mbar_wait(bar + B_SG, (grp - 1) & 1);
          if (el) {
            mbar_expect_tx(bar + B_CV, 4 * U_BYTES);
            bulk_g2s(sb + T_U, g_u + (size_t)ch0 * U_LEN, 4 * U_BYTES, bar + B_CV);
          }
        }
      }
      PROF_T(79);
      PROF_DUMP();
      unsigned int old = 0;
      if (el) old = atomicAdd(g_cnt + C_DONE * 32, 1u) + 1;
      if (__any_sync(0xffffffffu, old == gridDim.x)) { g_cnt[lane * 32] = 0u; g_cnt[(lane + 32) * 32] = 0u; }
    } else {
      if (!spare) {
        named_bar(4, 384);
        uint4 k0v = make_uint4(0u, 0u, 0u, 0u);
        if (t < 112) k0v = lds128(sb + PR_K0 + (t - 32) * 16);
        named_bar(8, 96);
        if (t == 32) { mbar_arrive_remote(mapa(bar + B_HE, j ^ 1)); mbar_arrive_remote(mapa(bar + B_HE + 8, j ^ 1)); }
#pragma unroll 1
        for (int i = 0; i < 8; i++) mbar_wait(bar + B_XN + 8 * i, 0);
        const int tok = 8 * ((lane & 7) >> 1) + 2 * (lane >> 3) + (lane & 1);
#pragma unroll 1
        for (int it = w - 1; it < 36; it += 3) {
          const int oc = 9 * (2 * sp + j) + (it >> 2), tg = it & 3;
          uint4 v;
          ldmatrix_x4_t(sb + SM_XN + (oc >> 3) * 16384 + (32 * tg + tok) * 128 + (((oc ^ tok) & 7) << 4), v.x, v.y, v.z, v.w);
          ((uint4*)(g_u + (size_t)(8 * oc + (lane >> 2)) * U_LEN + 128 + mt * 128))[(4 * tg + (lane & 3)) ^ (tg >> 1)] = v;
        }
        __syncwarp();
        if (lane == 0) { fence_async_all(); cnt_add(C_U); }
        const uint4 e0 = __ldg((const uint4*)g_ktab.e + (t - 32));
        named_bar(9, 352);
        if (t < 112) sts128(sb + T_K0 + (t - 32) * 16, k0v);
        named_bar(8, 96);
        kexpand<96>(sb, sb + T_K0, sb + SM_KD, bar + B_K2048, t - 32, e0);
        __syncwarp();
        if (lane == 0) mbar_arrive(bar + B_CV);
      }
    }
  } else {
    const int t = threadIdx.x & 127, lane = t & 31;
    KgState kst;
    kgen_params(smem_raw, threadIdx.x, kin, kst);
    if (!spare) {
      {
        const uint32_t ra = sb + PR_LN + (threadIdx.x >> 4) * (D_ * 2) + (lane & 15) * 16;
        const bool last = !(lane & 8);
        PROF_T(60);
        mbar_wait(bar + B_X, 0);
        PROF_T(61);
        uint4 v[5];
#pragma unroll
        for (int i = 0; i < 5; i++) v[i] = (i < 4 || last) ? lds128(ra + i * 256) : make_uint4(0u, 0u, 0u, 0u);
        uint32_t* u = (uint32_t*)v;
        float s = 0.f, q = 0.f;
#pragma unroll
        for (int i = 0; i < 20; i++) s += bf_lo(u[i]) + bf_hi(u[i]);
#pragma unroll
        for (int o = 8; o; o >>= 1) s += __shfl_xor_sync(0xffffffffu, s, o);
        s *= (1.0f / D_);
#pragma unroll
        for (int i = 0; i < 20; i++) {
          const float a = bf_lo(u[i]) - s, b = bf_hi(u[i]) - s;
          if (i == 16) { if (!last) break; }
          q = fmaf(a, a, q); q = fmaf(b, b, q);
        }
#pragma unroll
        for (int o = 8; o; o >>= 1) q += __shfl_xor_sync(0xffffffffu, q, o);
        const float mb = bf_round(s);
        const float rinv = 1.0f / bf_round(sqrtf(bf_round(bf_round(q * (1.0f / D_)) + 1e-5f)));
#pragma unroll
        for (int i = 0; i < 20; i++) {
          const uint32_t d = pack_bf16(bf_lo(u[i]) - mb, bf_hi(u[i]) - mb);
          u[i] = pack_bf16(bf_lo(d) * rinv, bf_hi(d) * rinv);
        }
#pragma unroll
        for (int i = 0; i < 5; i++) if (i < 4 || last) sts128(ra + i * 256, v[i]);
        fence_async_smem();
        named_arrive(5, 288);
        PROF_T(64);
      }
      kgen_steps(smem_raw, threadIdx.x, kst);
      PROF_T(51);
      kgen_finish(smem_raw, (unsigned short*)(smem_raw + (warp < 2 ? PR_K0 : SM_KD + ((warp >> 1) - 1) * 1280)),
                  (unsigned short*)(smem_raw + SM_BAR + B_K2048) + (warp >> 1), threadIdx.x, kst);
      named_arrive(4, 384);
    } else {
      const int c0 = 512 + ((int)vb - 128) * 16;
#pragma unroll 1
      for (int grp = 0; grp < 4; grp++) {
        if (grp) { kgen_load(p, c0 + grp * 4, threadIdx.x, kin); kgen_params(smem_raw, threadIdx.x, kin, kst); }
        kgen_steps(smem_raw, threadIdx.x, kst);
        kgen_finish(smem_raw, (unsigned short*)(smem_raw + SM_RING + (grp * 4 + (warp >> 1)) * 1280),
                    (unsigned short*)(smem_raw + SM_KD) + grp * 4 + (warp >> 1), threadIdx.x, kst);
        named_bar(3, 256);
      }
      named_arrive(7, 288);
    }
    PROF_T(41);
    asm volatile("barrier.cluster.wait.aligned;" ::: "memory");
    asm volatile("setmaxnreg.inc.sync.aligned.u32 240;");
    if (!spare) {
      const bool leader = (t == 0);
      float O1[128], O2[16];
      uint32_t slot = 0, ph = 0, prev = 0;
      const uint32_t hin = sb + SM_HIN + wg * 8192;
      const uint32_t r_hin = mapa(hin + (16 * w + (lane >> 2)) * 128 + (((lane & 3) ^ (lane >> 2)) << 4), j ^ 1);
      const uint32_t r_hf = mapa(bar + B_HF + 8 * wg, j ^ 1), r_he = mapa(bar + B_HE + 8 * wg, j ^ 1);
      const uint64_t dA0 = mk_desc(sb + SM_XN + wg * 8192, 16, 1024, 1);
      const uint64_t dH0 = mk_desc(hin, 16, 1024, 1);
      const uint64_t dG0 = mk_desc(sb + SM_RING, 4096, 1024, 1);
      const uint64_t dW0 = mk_desc(sb + SM_RING, 2048, 1024, 1);
      const uint64_t dX0 = mk_desc(sb + SM_RING + 8192, 512, 512, 2);
      auto adv = [&]() { prev = slot; if (++slot == NST) { slot = 0; ph ^= 1; } };
      auto release = [&](uint32_t s) { if (lane == 0) mbar_arrive(bar + B_EMPTY + 8 * s); };
      auto peer_begin = [&](int cp) {
        mbar_wait(bar + B_HF + 8 * wg, cp & 1);
        if (leader && cp < 8) mbar_expect_tx(bar + B_HF + 8 * wg, 8192);
        fence_async_smem();
      };
      auto peer_unit = [&](int u) {
        wg_fence();
        wg_ss256<1>(O1, dH0 + 2 * u, dW0 + (uint64_t)(slot * (SLOT >> 4)));
        wg_ss32<1>(O2, dH0 + 2 * u, dX0 + (uint64_t)(slot * (SLOT >> 4)));
        wg_commit();
      };
      auto chunk = [&](auto first_c, const int c) {
        constexpr bool FIRST = decltype(first_c)::value;
        float S[64];
        {
          if (FIRST) mbar_wait(bar + B_XN, 0);
          FULLW();
          if (FIRST) { PROF_T(42); PROF_G(2); }
          const uint64_t db = dG0 + (uint64_t)(slot * (SLOT >> 4));
          wg_fence();
          wg_ss128_init<1>(S, dA0, db);
          wg_ss128<1>(S, dA0 + 2, db + 128);
          wg_commit();
          adv();
        }
#pragma unroll 1
        for (int u = 1; u < 18; u++) {
          if (FIRST && !(u & 1) && u < 16) mbar_wait(bar + B_XN + 8 * (u >> 1), 0);
          FULLW();
          const uint64_t da = dA0 + (uint64_t)((u >> 1) * 1024 + (u & 1) * 4);
          const uint64_t db = dG0 + (uint64_t)(slot * (SLOT >> 4));
          wg_fence();
          wg_ss128<1>(S, da, db);
          wg_ss128<1>(S, da + 2, db + 128);
          wg_commit();
          if constexpr (!FIRST) { if (u == 12) peer_begin(c - 1); }
          wg_wait<1>();
          release(prev);
          adv();
        }
        uint32_t H[16];
        if constexpr (FIRST) { wg_wait<0>(); release(prev); }
        uint32_t rs = prev;
        auto rel_next = [&]() { release(rs); if (++rs == NST) rs = 0; };
        auto P = [&](int u) {
          FULLW();
          peer_unit(u);
          if (u) { wg_wait<2>(); rel_next(); }
          if (u == 1 && c == 8) named_arrive(9, 352);
          adv();
        };
        auto E = [&](int u) {
#pragma unroll
          for (int i = 8 * u; i < 8 * u + 8; i++) asm volatile("" : "+f"(S[i]), "+f"(S[32 + i])::"memory");
#pragma unroll
          for (int g = 2 * u; g < 2 * u + 2; g++) {
            H[2 * g] = pack_bf16(geglu(S[4 * g], S[32 + 4 * g]), geglu(S[4 * g + 1], S[33 + 4 * g]));
            H[2 * g + 1] = pack_bf16(geglu(S[4 * g + 2], S[34 + 4 * g]), geglu(S[4 * g + 3], S[35 + 4 * g]));
          }
#pragma unroll
          for (int i = 4 * u; i < 4 * u + 4; i++) asm volatile("" : "+r"(H[i])::"memory");
        };
        auto O = [&](int u) {
          FULLW();
          wg_fence();
          if (FIRST && u == 0) {
            wg_rs256_init<1>(O1, H[0], H[1], H[2], H[3], dW0 + (uint64_t)(slot * (SLOT >> 4)));
            wg_rs32_init<1>(O2, H[0], H[1], H[2], H[3], dX0 + (uint64_t)(slot * (SLOT >> 4)));
            rs = slot;
          } else {
            wg_rs256<1>(O1, H[4 * u], H[4 * u + 1], H[4 * u + 2], H[4 * u + 3], dW0 + (uint64_t)(slot * (SLOT >> 4)));
            wg_rs32<1>(O2, H[4 * u], H[4 * u + 1], H[4 * u + 2], H[4 * u + 3], dX0 + (uint64_t)(slot * (SLOT >> 4)));
          }
          wg_commit();
          if (u == 3) {
            mbar_wait(bar + B_HE + 8 * wg, c & 1);
            st_async_v4(r_hin, H[0], H[2], H[4], H[6], r_hf);
            st_async_v4(r_hin ^ 64, H[8], H[10], H[12], H[14], r_hf);
            st_async_v4(r_hin + 1024, H[1], H[3], H[5], H[7], r_hf);
            st_async_v4((r_hin ^ 64) + 1024, H[9], H[11], H[13], H[15], r_hf);
          }
          if (!FIRST || u >= 2) { wg_wait<2>(); rel_next(); }
          if (u == 1) { if constexpr (!FIRST) { if (leader) mbar_arrive_remote(r_he); } }
          if (u == 3) { wg_wait<1>(); rel_next(); wg_wait<0>(); rel_next(); }
          adv();
        };
        if constexpr (FIRST) { E(0); O(0); E(1); O(1); E(2); O(2); E(3); O(3); }
        else { P(0); P(1); E(0); P(2); E(1); P(3); O(0); E(2); O(1); O(2); E(3); O(3); }
        PROF_T(4 + 4 * c);
      };
      chunk(std::true_type{}, 0);
#pragma unroll 1
      for (int c = 1; c < 9; c++) chunk(std::false_type{}, c);
      peer_begin(8);
#pragma unroll 1
      for (int u = 0; u < 4; u++) { FULLW(); peer_unit(u); adv(); }
      wg_wait<0>();
      reg_fence(O1); reg_fence(O2);
      PROF_T(40); PROF_G(3);
      const int mi = lane >> 3, li = lane & 7;
      {
        const int row = 16 * w + 8 * (mi & 1) + li;
        const uint32_t stg = sb + SM_XN + wg * 8192 + row * 128;
#pragma unroll
        for (int g = 0; g < 32; g += 2)
          stmatrix_x4(stg + (g >> 3) * 16384 + ((((g & 7) + (mi >> 1)) ^ li) << 4), pack_bf16(O1[4 * g], O1[4 * g + 1]), pack_bf16(O1[4 * g + 2], O1[4 * g + 3]),
                      pack_bf16(O1[4 * g + 4], O1[4 * g + 5]), pack_bf16(O1[4 * g + 6], O1[4 * g + 7]));
#pragma unroll
        for (int g = 0; g < 4; g += 2)
          stmatrix_x4(stg + 65536 - row * 64 + (((g + (mi >> 1)) ^ (li >> 1)) << 4), pack_bf16(O2[4 * g], O2[4 * g + 1]), pack_bf16(O2[4 * g + 2], O2[4 * g + 3]),
                      pack_bf16(O2[4 * g + 4], O2[4 * g + 5]), pack_bf16(O2[4 * g + 6], O2[4 * g + 7]));
        fence_async_smem();
        named_bar(1 + wg, 128);
        if (leader) mbar_arrive(bar + B_SG);
      }
      mbar_wait(bar + B_CV, 0);
      PROF_T(43);
      conv2(sb, wg, w, lane, vb * 4 + 2 * wg, C_Y + (vb >> 6));
      PROF_T(44); PROF_G(5);
      const int w8 = warp, row = 16 * (w8 & 1) + 8 * (mi & 1) + li;
      const uint32_t own = sb + SM_XN + (sp >> 1) * 8192;
      const int nblk = w8 < 4 ? 5 : 4;
      named_bar(3, 256);
      mbar_wait(bar + B_PT, 0);
#pragma unroll 1
      for (int k = 0; k < nblk; k++) {
        const uint32_t o = k < 4 ? row * 128 + (((2 * k + (mi >> 1)) ^ li) << 4) : row * 64 + (((2 * (w8 >> 1) + (mi >> 1)) ^ (li >> 1)) << 4);
        const uint32_t oa = own + o + (k < 4 ? (w8 >> 1) * 16384 + (sp & 1) * 4096 : 65536 + (sp & 1) * 2048);
        const uint32_t pa = sb + T_PART + o + (k < 4 ? (w8 >> 1) * 4096 : 16384);
        uint32_t r[4];
        float f[8];
        ldmatrix_x4(oa, r);
#pragma unroll
        for (int i = 0; i < 4; i++) { f[2 * i] = bf_lo(r[i]); f[2 * i + 1] = bf_hi(r[i]); }
#pragma unroll
        for (int s = 0; s < 4; s++) {
          ldmatrix_x4(pa + s * IMG, r);
#pragma unroll
          for (int i = 0; i < 4; i++) { f[2 * i] += bf_lo(r[i]); f[2 * i + 1] += bf_hi(r[i]); }
        }
        stmatrix_x4(oa, pack_bf16(f[0], f[1]), pack_bf16(f[2], f[3]), pack_bf16(f[4], f[5]), pack_bf16(f[6], f[7]));
      }
      __syncwarp();
      PROF_T(56);
      mbar_wait(bar + B_YT, 0);
      PROF_T(45); PROF_G(6);
#pragma unroll 1
      for (int k = 0; k < nblk; k++) {
        const uint32_t o = k < 4 ? row * 128 + (((2 * k + (mi >> 1)) ^ li) << 4) : row * 64 + (((2 * (w8 >> 1) + (mi >> 1)) ^ (li >> 1)) << 4);
        const uint32_t oa = own + o + (k < 4 ? (w8 >> 1) * 16384 + (sp & 1) * 4096 : 65536 + (sp & 1) * 2048);
        const int chl = (k < 4 ? 64 * (w8 >> 1) + 16 * k : 256 + 16 * (w8 >> 1)) + 8 * (mi >> 1) + li;
        uint32_t r[4], y0, y1, y2, y3;
        ldmatrix_x4(oa, r);
        ldmatrix_x4_t(sb + T_YT + chl * 64 + (((2 * (w8 & 1) + (mi & 1)) ^ (li >> 1)) << 4), y0, y1, y2, y3);
        stmatrix_x4(oa, pack_bf16(bf_lo(r[0]) + bf_lo(y0), bf_hi(r[0]) + bf_hi(y0)), pack_bf16(bf_lo(r[1]) + bf_lo(y1), bf_hi(r[1]) + bf_hi(y1)),
                    pack_bf16(bf_lo(r[2]) + bf_lo(y2), bf_hi(r[2]) + bf_hi(y2)), pack_bf16(bf_lo(r[3]) + bf_lo(y3), bf_hi(r[3]) + bf_hi(y3)));
      }
      PROF_T(57);
      fence_async_smem();
      named_bar(3, 256);
      if (threadIdx.x < 5) {
        if (threadIdx.x < 4) tma_store_2d(&p.out, own + threadIdx.x * 16384 + (sp & 1) * 4096, 256 * j + 64 * threadIdx.x, mt * 128 + 32 * sp);
        else tma_store_2d(&p.out5, own + 65536 + (sp & 1) * 2048, 512 + 32 * j, mt * 128 + 32 * sp);
        asm volatile("cp.async.bulk.commit_group;" ::: "memory");
        asm volatile("cp.async.bulk.wait_group.read 0;" ::: "memory");
      }
      PROF_T(46); PROF_G(7);
      PROF_DUMP();
    } else {
#pragma unroll 1
      for (int grp = 0; grp < 4; grp++) {
        kexpand<256>(sb, sb + SM_RING + grp * 5120, sb + SM_RING + grp * 5120 + 1280, sb + SM_KD + 8 * grp, threadIdx.x, __ldg((const uint4*)g_ktab.e + threadIdx.x));
        named_bar(3, 256);
        mbar_wait(bar + B_CV, grp & 1);
        conv2(sb, wg, w, lane, 512 + ((int)vb - 128) * 16 + grp * 4 + 2 * wg, C_Y5);
        if (t == 0) mbar_arrive(bar + B_SG);
        named_bar(3, 256);
      }
      PROF_T(46);
      PROF_DUMP();
    }
  }
}

typedef CUresult (*PFN_enc)(CUtensorMap*, CUtensorMapDataType, cuuint32_t, void*, const cuuint64_t*, const cuuint64_t*, const cuuint32_t*,
                            const cuuint32_t*, CUtensorMapInterleave, CUtensorMapSwizzle, CUtensorMapL2promotion, CUtensorMapFloatOOBfill);

void enc(PFN_enc fn, CUtensorMap* m, void* ptr, int rank, const cuuint64_t* dims, const cuuint64_t* strides, const cuuint32_t* box, CUtensorMapSwizzle sw) {
  cuuint32_t es[5] = {1, 1, 1, 1, 1};
  fn(m, CU_TENSOR_MAP_DATA_TYPE_BFLOAT16, rank, ptr, dims, strides, box, es, CU_TENSOR_MAP_INTERLEAVE_NONE, sw,
     CU_TENSOR_MAP_L2_PROMOTION_L2_128B, CU_TENSOR_MAP_FLOAT_OOB_FILL_NONE);
}

}

extern "C" void kernel_launch(void* const* d_in, const int* in_sizes, int n_in, void* d_out, int out_size) {
  static Params pr;
  static void* key[5] = {nullptr, nullptr, nullptr, nullptr, nullptr};
  if (key[0] != d_in[8] || key[1] != d_in[9] || key[2] != d_in[10] || key[3] != d_in[0] || key[4] != d_out) {
    key[0] = d_in[8]; key[1] = d_in[9]; key[2] = d_in[10]; key[3] = d_in[0]; key[4] = d_out;
    void* fnp = nullptr; cudaDriverEntryPointQueryResult st;
    cudaGetDriverEntryPoint("cuTensorMapEncodeTiled", &fnp, cudaEnableDefault, &st);
    PFN_enc fn = (PFN_enc)fnp;
    void *p_xn, *p_y;
    cudaGetSymbolAddress(&p_xn, g_xn); cudaGetSymbolAddress(&p_y, g_y);
    { cuuint64_t d[2] = {D_, L_}, s[1] = {D_ * 2};
      { cuuint32_t b[2] = {64, 128}; enc(fn, &pr.xn, p_xn, 2, d, s, b, CU_TENSOR_MAP_SWIZZLE_128B); }
      { cuuint32_t b[2] = {64, 32}; enc(fn, &pr.x, d_in[0], 2, d, s, b, CU_TENSOR_MAP_SWIZZLE_128B); enc(fn, &pr.out, d_out, 2, d, s, b, CU_TENSOR_MAP_SWIZZLE_128B); }
      { cuuint32_t b[2] = {32, 32}; enc(fn, &pr.x5, d_in[0], 2, d, s, b, CU_TENSOR_MAP_SWIZZLE_64B); enc(fn, &pr.out5, d_out, 2, d, s, b, CU_TENSOR_MAP_SWIZZLE_64B); } }
    { cuuint64_t d[2] = {F_, D_}, s[1] = {F_ * 2}; cuuint32_t b[2] = {64, 32};
      enc(fn, &pr.gate, d_in[8], 2, d, s, b, CU_TENSOR_MAP_SWIZZLE_128B); enc(fn, &pr.up, d_in[9], 2, d, s, b, CU_TENSOR_MAP_SWIZZLE_128B); }
    { void* wd = d_in[10];
      { cuuint64_t d[3] = {64, F_, 9}, s[2] = {D_ * 2, 128}; cuuint32_t b[3] = {64, 16, 4}; enc(fn, &pr.dn, wd, 3, d, s, b, CU_TENSOR_MAP_SWIZZLE_128B); }
      { cuuint64_t d[2] = {D_, F_}, s[1] = {D_ * 2}; cuuint32_t b[2] = {32, 16}; enc(fn, &pr.dn5, wd, 2, d, s, b, CU_TENSOR_MAP_SWIZZLE_64B); }
      { cuuint64_t d[5] = {64, 2, F_ / 8, 4, 9}, s[4] = {D_ * 2, D_ * 16, D_ * 4, 128}; cuuint32_t b[5] = {64, 2, 4, 2, 4};
        enc(fn, &pr.dp, wd, 5, d, s, b, CU_TENSOR_MAP_SWIZZLE_128B); }
      { cuuint64_t d[4] = {D_, 2, F_ / 8, 4}, s[3] = {D_ * 2, D_ * 16, D_ * 4}; cuuint32_t b[4] = {32, 2, 4, 2};
        enc(fn, &pr.dp5, wd, 4, d, s, b, CU_TENSOR_MAP_SWIZZLE_64B); }
    }
    { cuuint64_t d[2] = {L_, D_}, s[1] = {L_ * 2};
      { cuuint32_t b[2] = {32, 256}; enc(fn, &pr.y, p_y, 2, d, s, b, CU_TENSOR_MAP_SWIZZLE_64B); }
      { cuuint32_t b[2] = {32, 32}; enc(fn, &pr.y5, p_y, 2, d, s, b, CU_TENSOR_MAP_SWIZZLE_64B); } }
    cudaFuncSetAttribute(fused_kernel, cudaFuncAttributeMaxDynamicSharedMemorySize, SMEM_BYTES);
  }
  const __nv_bfloat16* const* in = (const __nv_bfloat16* const*)d_in;
  pr.xp = in[0]; pr.logA = in[1]; pr.Aim = in[2]; pr.Cre = in[3]; pr.Cim = in[4]; pr.logdt = in[5]; pr.Dsk = in[6];
  fused_kernel<<<132, 384, SMEM_BYTES>>>(pr);
}
```

```cpp
#include <cuda_runtime.h>
#include <cuda_bf16.h>
#include <cuda.h>
#include <stdint.h>
#include <stdio.h>
#include <type_traits>
#define CV_BASEOFF 0

namespace {

constexpr int L_ = 2048, D_ = 576, F_ = 4608, NM_ = 128;
constexpr int KP_LEN = 2080;
constexpr int U_LEN = 2176;

__device__ __align__(1024) __nv_bfloat16 g_xn[L_ * D_];
__device__ __align__(1024) __nv_bfloat16 g_u[D_ * U_LEN];
__device__ __align__(1024) unsigned char g_part[32 * 16 * 18432];
__device__ __align__(1024) __nv_bfloat16 g_y[D_ * L_];
__device__ __align__(1024) unsigned int g_cnt[64 * 32];
constexpr int C_LN = 0, C_PART = 16, C_U = 48, C_Y = 49, C_Y5 = 51, C_DONE = 52;

#define PROF_T(idx) do {} while (0)
#define PROF_G(idx) do {} while (0)
#define PROF_DUMP() do {} while (0)
__device__ __forceinline__ uint32_t smem_u32(const void* p) { return (uint32_t)__cvta_generic_to_shared(p); }
__device__ __forceinline__ void mbar_init(uint32_t bar, uint32_t cnt) { asm volatile("mbarrier.init.shared::cta.b64 [%0], %1;" ::"r"(bar), "r"(cnt)); }
__device__ __forceinline__ void mbar_expect_tx(uint32_t bar, uint32_t bytes) { asm volatile("mbarrier.arrive.expect_tx.shared::cta.b64 _, [%0], %1;" ::"r"(bar), "r"(bytes) : "memory"); }
__device__ __forceinline__ void mbar_arrive(uint32_t bar) { asm volatile("mbarrier.arrive.shared::cta.b64 _, [%0];" ::"r"(bar) : "memory"); }
__device__ __forceinline__ void mbar_arrive_remote(uint32_t bar) { asm volatile("mbarrier.arrive.shared::cluster.b64 _, [%0];" ::"r"(bar) : "memory"); }
__device__ __forceinline__ bool mbar_try_wait(uint32_t bar, uint32_t parity) {
  uint32_t ok;
  asm volatile("{\n.reg .pred p;\nmbarrier.try_wait.parity.shared::cta.b64 p, [%1], %2;\nselp.u32 %0, 1, 0, p;\n}" : "=r"(ok) : "r"(bar), "r"(parity) : "memory");
  return ok;
}
__device__ __forceinline__ bool mbar_test(uint32_t bar, uint32_t parity) {
  uint32_t ok;
  asm volatile("{\n.reg .pred p;\nmbarrier.test_wait.parity.shared::cta.b64 p, [%1], %2;\nselp.u32 %0, 1, 0, p;\n}" : "=r"(ok) : "r"(bar), "r"(parity) : "memory");
  return ok;
}
__device__ __forceinline__ void mbar_wait(uint32_t bar, uint32_t parity) {
  asm volatile("{\n.reg .pred p, q;\n.reg .u32 n;\nmov.u32 n, 0;\nLW:\nmbarrier.try_wait.parity.shared::cta.b64 p, [%0], %1;\n"
               "add.u32 n, n, 1;\nsetp.lt.and.u32 q, n, 65536, !p;\n@q bra LW;\n}" ::"r"(bar), "r"(parity) : "memory");
}
__device__ __forceinline__ void mbar_spin(uint32_t bar, uint32_t parity) {
  asm volatile("{\n.reg .pred p, q;\n.reg .u32 n;\nmov.u32 n, 0;\nLW:\nmbarrier.test_wait.parity.shared::cta.b64 p, [%0], %1;\n"
               "add.u32 n, n, 1;\nsetp.lt.and.u32 q, n, 4194304, !p;\n@q bra LW;\n}" ::"r"(bar), "r"(parity) : "memory");
}
__device__ __forceinline__ bool elect_one() {
  uint32_t ok;
  asm volatile("{\n.reg .pred p;\nelect.sync _|p, 0xffffffff;\nselp.u32 %0, 1, 0, p;\n}" : "=r"(ok));
  return ok;
}
__device__ __forceinline__ void tma_2d(uint32_t dst, const CUtensorMap* map, int c0, int c1, uint32_t bar) {
  asm volatile("cp.async.bulk.tensor.2d.shared::cluster.global.mbarrier::complete_tx::bytes [%0], [%1, {%3, %4}], [%2];"
               ::"r"(dst), "l"(map), "r"(bar), "r"(c0), "r"(c1) : "memory");
}
__device__ __forceinline__ void tma_3d(uint32_t dst, const CUtensorMap* map, int c0, int c1, int c2, uint32_t bar) {
  asm volatile("cp.async.bulk.tensor.3d.shared::cluster.global.mbarrier::complete_tx::bytes [%0], [%1, {%3, %4, %5}], [%2];"
               ::"r"(dst), "l"(map), "r"(bar), "r"(c0), "r"(c1), "r"(c2) : "memory");
}
__device__ __forceinline__ void tma_4d(uint32_t dst, const CUtensorMap* map, int c0, int c1, int c2, int c3, uint32_t bar) {
  asm volatile("cp.async.bulk.tensor.4d.shared::cluster.global.mbarrier::complete_tx::bytes [%0], [%1, {%3, %4, %5, %6}], [%2];"
               ::"r"(dst), "l"(map), "r"(bar), "r"(c0), "r"(c1), "r"(c2), "r"(c3) : "memory");
}
__device__ __forceinline__ void tma_5d(uint32_t dst, const CUtensorMap* map, int c0, int c1, int c2, int c3, int c4, uint32_t bar) {
  asm volatile("cp.async.bulk.tensor.5d.shared::cluster.global.mbarrier::complete_tx::bytes [%0], [%1, {%3, %4, %5, %6, %7}], [%2];"
               ::"r"(dst), "l"(map), "r"(bar), "r"(c0), "r"(c1), "r"(c2), "r"(c3), "r"(c4) : "memory");
}
__device__ __forceinline__ void tma_store_3d(const CUtensorMap* map, uint32_t src, int c0, int c1, int c2) {
  asm volatile("cp.async.bulk.tensor.3d.global.shared::cta.bulk_group [%0, {%2, %3, %4}], [%1];"
               ::"l"(map), "r"(src), "r"(c0), "r"(c1), "r"(c2) : "memory");
}
__device__ __forceinline__ void bulk_g2s(uint32_t dst, const void* src, uint32_t bytes, uint32_t bar) {
  asm volatile("cp.async.bulk.shared::cluster.global.mbarrier::complete_tx::bytes [%0], [%1], %2, [%3];"
               ::"r"(dst), "l"(src), "r"(bytes), "r"(bar) : "memory");
}
__device__ __forceinline__ void prefetch_map(const CUtensorMap* m) { asm volatile("prefetch.tensormap [%0];" ::"l"(m) : "memory"); }
__device__ __forceinline__ uint32_t mapa(uint32_t addr, uint32_t rank) { uint32_t r; asm volatile("mapa.shared::cluster.u32 %0, %1, %2;" : "=r"(r) : "r"(addr), "r"(rank)); return r; }
__device__ __forceinline__ void cluster_sync() { asm volatile("barrier.cluster.arrive.release.aligned;\nbarrier.cluster.wait.acquire.aligned;" ::: "memory"); }
__device__ __forceinline__ void fence_async_smem() { asm volatile("fence.proxy.async.shared::cta;" ::: "memory"); }
__device__ __forceinline__ void wg_fence() { asm volatile("wgmma.fence.sync.aligned;" ::: "memory"); }
__device__ __forceinline__ void wg_commit() { asm volatile("wgmma.commit_group.sync.aligned;" ::: "memory"); }
template <int N> __device__ __forceinline__ void wg_wait() { asm volatile("wgmma.wait_group.sync.aligned %0;" ::"n"(N) : "memory"); }
template <int N> __device__ __forceinline__ void reg_fence(float (&d)[N]) {
#pragma unroll
  for (int i = 0; i < N; i++) asm volatile("" : "+f"(d[i])::"memory");
}
__device__ __forceinline__ void named_bar(int id, int n) { asm volatile("bar.sync %0, %1;" ::"r"(id), "r"(n) : "memory"); }
__device__ __forceinline__ uint64_t mk_desc(uint32_t addr, uint32_t lbo, uint32_t sbo, uint32_t sw) {
  return (uint64_t)((addr & 0x3FFFF) >> 4) | ((uint64_t)(lbo >> 4) << 16) | ((uint64_t)(sbo >> 4) << 32) | ((uint64_t)sw << 62);
}
__device__ __forceinline__ uint32_t pack_bf16(float lo, float hi) {
  uint32_t r; asm("cvt.rn.bf16x2.f32 %0, %1, %2;" : "=r"(r) : "f"(hi), "f"(lo)); return r;
}
__device__ __forceinline__ float bf_lo(uint32_t v) { return __uint_as_float(v << 16); }
__device__ __forceinline__ float bf_hi(uint32_t v) { return __uint_as_float(v & 0xffff0000u); }
__device__ __forceinline__ float bf_round(float x) { return __bfloat162float(__float2bfloat16_rn(x)); }
__device__ __forceinline__ void st_async_v4(uint32_t addr, uint32_t a, uint32_t b, uint32_t c, uint32_t d, uint32_t bar) {
  asm volatile("st.async.weak.shared::cluster.mbarrier::complete_tx::bytes.v4.b32 [%0], {%1, %2, %3, %4}, [%5];"
               ::"r"(addr), "r"(a), "r"(b), "r"(c), "r"(d), "r"(bar) : "memory");
}
__device__ __forceinline__ void stmatrix_x4_t(uint32_t addr, uint32_t a, uint32_t b, uint32_t c, uint32_t d) {
  asm volatile("stmatrix.sync.aligned.m8n8.x4.trans.shared.b16 [%0], {%1, %2, %3, %4};" ::"r"(addr), "r"(a), "r"(b), "r"(c), "r"(d) : "memory");
}
__device__ __forceinline__ void ldmatrix_x4_t(uint32_t addr, uint32_t& a, uint32_t& b, uint32_t& c, uint32_t& d) {
  asm volatile("ldmatrix.sync.aligned.m8n8.x4.trans.shared.b16 {%0, %1, %2, %3}, [%4];" : "=r"(a), "=r"(b), "=r"(c), "=r"(d) : "r"(addr) : "memory");
}
__device__ __forceinline__ uint32_t lds32(uint32_t addr) { uint32_t v; asm volatile("ld.shared.b32 %0, [%1];" : "=r"(v) : "r"(addr) : "memory"); return v; }
__device__ __forceinline__ float geglu(float g, float u) {
  float z = g * fmaf(g * g, 0.0356774081f, 0.7978845608f);
  float t; asm("tanh.approx.f32 %0, %1;" : "=f"(t) : "f"(z));
  return (g * u) * fmaf(t, 0.5f, 0.5f);
}

__device__ __forceinline__ uint4 lds128(uint32_t addr) { uint4 v; asm volatile("ld.shared.v4.b32 {%0,%1,%2,%3}, [%4];" : "=r"(v.x), "=r"(v.y), "=r"(v.z), "=r"(v.w) : "r"(addr) : "memory"); return v; }
__device__ __forceinline__ void sts32(uint32_t addr, uint32_t v) { asm volatile("st.shared.b32 [%0], %1;" ::"r"(addr), "r"(v) : "memory"); }
__device__ __forceinline__ void stmatrix_x4(uint32_t addr, uint32_t a, uint32_t b, uint32_t c, uint32_t d) {
  asm volatile("stmatrix.sync.aligned.m8n8.x4.shared.b16 [%0], {%1, %2, %3, %4};" ::"r"(addr), "r"(a), "r"(b), "r"(c), "r"(d) : "memory");
}
__device__ __forceinline__ void ldmatrix_x4(uint32_t addr, uint32_t (&r)[4]) {
  asm volatile("ldmatrix.sync.aligned.m8n8.x4.shared.b16 {%0, %1, %2, %3}, [%4];" : "=r"(r[0]), "=r"(r[1]), "=r"(r[2]), "=r"(r[3]) : "r"(addr) : "memory");
}
__device__ __forceinline__ void sts128(uint32_t addr, uint4 v) { asm volatile("st.shared.v4.b32 [%0], {%1,%2,%3,%4};" ::"r"(addr), "r"(v.x), "r"(v.y), "r"(v.z), "r"(v.w) : "memory"); }
__device__ __forceinline__ void bulk_s2g(void* dst, uint32_t src, uint32_t bytes) {
  asm volatile("cp.async.bulk.global.shared::cta.bulk_group [%0], [%1], %2;" ::"l"(dst), "r"(src), "r"(bytes) : "memory");
}
__device__ __forceinline__ void tma_store_2d(const CUtensorMap* map, uint32_t src, int c0, int c1) {
  asm volatile("cp.async.bulk.tensor.2d.global.shared::cta.bulk_group [%0, {%2, %3}], [%1];" ::"l"(map), "r"(src), "r"(c0), "r"(c1) : "memory");
}
__device__ __forceinline__ void bulk_commit_wait() {
  asm volatile("cp.async.bulk.commit_group;" ::: "memory");
  asm volatile("cp.async.bulk.wait_group 0;" ::: "memory");
}
__device__ __forceinline__ void named_arrive(int id, int n) { asm volatile("bar.arrive %0, %1;" ::"r"(id), "r"(n) : "memory"); }
__device__ __forceinline__ void fence_async_all() { asm volatile("fence.proxy.async.global;" ::: "memory"); }
__device__ __forceinline__ void cnt_add(int idx) {
  asm volatile("red.release.gpu.global.add.u32 [%0], 1;" ::"l"(g_cnt + idx * 32) : "memory");
}
__device__ __forceinline__ void cnt_add_done(int idx) {
  asm volatile("red.relaxed.gpu.global.add.u32 [%0], 1;" ::"l"(g_cnt + idx * 32) : "memory");
}
__device__ __forceinline__ void cnt_wait(int idx, uint32_t target) {
  const unsigned int* p = g_cnt + idx * 32;
#pragma unroll 1
  for (int it = 0; it < (1 << 18); it++) {
    uint32_t v; asm volatile("ld.acquire.gpu.global.u32 %0, [%1];" : "=r"(v) : "l"(p) : "memory");
    if (v >= target) break;
  }
}
__device__ __forceinline__ void prefetch_l2(const void* p, uint32_t bytes) { asm volatile("cp.async.bulk.prefetch.L2.global [%0], %1;" ::"l"(p), "r"(bytes) : "memory"); }

template <int TB>
__device__ __forceinline__ void wg_ss128_init(float (&d)[64], uint64_t da, uint64_t db) {
  asm volatile(
    "wgmma.mma_async.sync.aligned.m64n128k16.f32.bf16.bf16 {%0, %1, %2, %3, %4, %5, %6, %7, %8, %9, %10, %11, %12, %13, %14, %15, %16, %17, %18, %19, %20, %21, %22, %23, %24, %25, %26, %27, %28, %29, %30, %31, %32, %33, %34, %35, %36, %37, %38, %39, %40, %41, %42, %43, %44, %45, %46, %47, %48, %49, %50, %51, %52, %53, %54, %55, %56, %57, %58, %59, %60, %61, %62, %63}, %64, %65, 0, 1, 1, 0, %66;"
    : "=f"(d[0]), "=f"(d[1]), "=f"(d[2]), "=f"(d[3]), "=f"(d[4]), "=f"(d[5]), "=f"(d[6]), "=f"(d[7]), "=f"(d[8]), "=f"(d[9]), "=f"(d[10]), "=f"(d[11]), "=f"(d[12]), "=f"(d[13]), "=f"(d[14]), "=f"(d[15]), "=f"(d[16]), "=f"(d[17]), "=f"(d[18]), "=f"(d[19]), "=f"(d[20]), "=f"(d[21]), "=f"(d[22]), "=f"(d[23]), "=f"(d[24]), "=f"(d[25]), "=f"(d[26]), "=f"(d[27]), "=f"(d[28]), "=f"(d[29]), "=f"(d[30]), "=f"(d[31]), "=f"(d[32]), "=f"(d[33]), "=f"(d[34]), "=f"(d[35]), "=f"(d[36]), "=f"(d[37]), "=f"(d[38]), "=f"(d[39]), "=f"(d[40]), "=f"(d[41]), "=f"(d[42]), "=f"(d[43]), "=f"(d[44]), "=f"(d[45]), "=f"(d[46]), "=f"(d[47]), "=f"(d[48]), "=f"(d[49]), "=f"(d[50]), "=f"(d[51]), "=f"(d[52]), "=f"(d[53]), "=f"(d[54]), "=f"(d[55]), "=f"(d[56]), "=f"(d[57]), "=f"(d[58]), "=f"(d[59]), "=f"(d[60]), "=f"(d[61]), "=f"(d[62]), "=f"(d[63])
    : "l"(da), "l"(db), "n"(TB));
}
template <int TB>
__device__ __forceinline__ void wg_ss128(float (&d)[64], uint64_t da, uint64_t db) {
  asm volatile(
    "wgmma.mma_async.sync.aligned.m64n128k16.f32.bf16.bf16 {%0, %1, %2, %3, %4, %5, %6, %7, %8, %9, %10, %11, %12, %13, %14, %15, %16, %17, %18, %19, %20, %21, %22, %23, %24, %25, %26, %27, %28, %29, %30, %31, %32, %33, %34, %35, %36, %37, %38, %39, %40, %41, %42, %43, %44, %45, %46, %47, %48, %49, %50, %51, %52, %53, %54, %55, %56, %57, %58, %59, %60, %61, %62, %63}, %64, %65, 1, 1, 1, 0, %66;"
    : "+f"(d[0]), "+f"(d[1]), "+f"(d[2]), "+f"(d[3]), "+f"(d[4]), "+f"(d[5]), "+f"(d[6]), "+f"(d[7]), "+f"(d[8]), "+f"(d[9]), "+f"(d[10]), "+f"(d[11]), "+f"(d[12]), "+f"(d[13]), "+f"(d[14]), "+f"(d[15]), "+f"(d[16]), "+f"(d[17]), "+f"(d[18]), "+f"(d[19]), "+f"(d[20]), "+f"(d[21]), "+f"(d[22]), "+f"(d[23]), "+f"(d[24]), "+f"(d[25]), "+f"(d[26]), "+f"(d[27]), "+f"(d[28]), "+f"(d[29]), "+f"(d[30]), "+f"(d[31]), "+f"(d[32]), "+f"(d[33]), "+f"(d[34]), "+f"(d[35]), "+f"(d[36]), "+f"(d[37]), "+f"(d[38]), "+f"(d[39]), "+f"(d[40]), "+f"(d[41]), "+f"(d[42]), "+f"(d[43]), "+f"(d[44]), "+f"(d[45]), "+f"(d[46]), "+f"(d[47]), "+f"(d[48]), "+f"(d[49]), "+f"(d[50]), "+f"(d[51]), "+f"(d[52]), "+f"(d[53]), "+f"(d[54]), "+f"(d[55]), "+f"(d[56]), "+f"(d[57]), "+f"(d[58]), "+f"(d[59]), "+f"(d[60]), "+f"(d[61]), "+f"(d[62]), "+f"(d[63])
    : "l"(da), "l"(db), "n"(TB));
}
template <int TB>
__device__ __forceinline__ void wg_ss256(float (&d)[128], uint64_t da, uint64_t db) {
  asm volatile(
    "wgmma.mma_async.sync.aligned.m64n256k16.f32.bf16.bf16 {%0, %1, %2, %3, %4, %5, %6, %7, %8, %9, %10, %11, %12, %13, %14, %15, %16, %17, %18, %19, %20, %21, %22, %23, %24, %25, %26, %27, %28, %29, %30, %31, %32, %33, %34, %35, %36, %37, %38, %39, %40, %41, %42, %43, %44, %45, %46, %47, %48, %49, %50, %51, %52, %53, %54, %55, %56, %57, %58, %59, %60, %61, %62, %63, %64, %65, %66, %67, %68, %69, %70, %71, %72, %73, %74, %75, %76, %77, %78, %79, %80, %81, %82, %83, %84, %85, %86, %87, %88, %89, %90, %91, %92, %93, %94, %95, %96, %97, %98, %99, %100, %101, %102, %103, %104, %105, %106, %107, %108, %109, %110, %111, %112, %113, %114, %115, %116, %117, %118, %119, %120, %121, %122, %123, %124, %125, %126, %127}, %128, %129, 1, 1, 1, 0, %130;"
    : "+f"(d[0]), "+f"(d[1]), "+f"(d[2]), "+f"(d[3]), "+f"(d[4]), "+f"(d[5]), "+f"(d[6]), "+f"(d[7]), "+f"(d[8]), "+f"(d[9]), "+f"(d[10]), "+f"(d[11]), "+f"(d[12]), "+f"(d[13]), "+f"(d[14]), "+f"(d[15]), "+f"(d[16]), "+f"(d[17]), "+f"(d[18]), "+f"(d[19]), "+f"(d[20]), "+f"(d[21]), "+f"(d[22]), "+f"(d[23]), "+f"(d[24]), "+f"(d[25]), "+f"(d[26]), "+f"(d[27]), "+f"(d[28]), "+f"(d[29]), "+f"(d[30]), "+f"(d[31]), "+f"(d[32]), "+f"(d[33]), "+f"(d[34]), "+f"(d[35]), "+f"(d[36]), "+f"(d[37]), "+f"(d[38]), "+f"(d[39]), "+f"(d[40]), "+f"(d[41]), "+f"(d[42]), "+f"(d[43]), "+f"(d[44]), "+f"(d[45]), "+f"(d[46]), "+f"(d[47]), "+f"(d[48]), "+f"(d[49]), "+f"(d[50]), "+f"(d[51]), "+f"(d[52]), "+f"(d[53]), "+f"(d[54]), "+f"(d[55]), "+f"(d[56]), "+f"(d[57]), "+f"(d[58]), "+f"(d[59]), "+f"(d[60]), "+f"(d[61]), "+f"(d[62]), "+f"(d[63]), "+f"(d[64]), "+f"(d[65]), "+f"(d[66]), "+f"(d[67]), "+f"(d[68]), "+f"(d[69]), "+f"(d[70]), "+f"(d[71]), "+f"(d[72]), "+f"(d[73]), "+f"(d[74]), "+f"(d[75]), "+f"(d[76]), "+f"(d[77]), "+f"(d[78]), "+f"(d[79]), "+f"(d[80]), "+f"(d[81]), "+f"(d[82]), "+f"(d[83]), "+f"(d[84]), "+f"(d[85]), "+f"(d[86]), "+f"(d[87]), "+f"(d[88]), "+f"(d[89]), "+f"(d[90]), "+f"(d[91]), "+f"(d[92]), "+f"(d[93]), "+f"(d[94]), "+f"(d[95]), "+f"(d[96]), "+f"(d[97]), "+f"(d[98]), "+f"(d[99]), "+f"(d[100]), "+f"(d[101]), "+f"(d[102]), "+f"(d[103]), "+f"(d[104]), "+f"(d[105]), "+f"(d[106]), "+f"(d[107]), "+f"(d[108]), "+f"(d[109]), "+f"(d[110]), "+f"(d[111]), "+f"(d[112]), "+f"(d[113]), "+f"(d[114]), "+f"(d[115]), "+f"(d[116]), "+f"(d[117]), "+f"(d[118]), "+f"(d[119]), "+f"(d[120]), "+f"(d[121]), "+f"(d[122]), "+f"(d[123]), "+f"(d[124]), "+f"(d[125]), "+f"(d[126]), "+f"(d[127])
    : "l"(da), "l"(db), "n"(TB));
}
template <int TB>
__device__ __forceinline__ void wg_ss32(float (&d)[16], uint64_t da, uint64_t db) {
  asm volatile(
    "wgmma.mma_async.sync.aligned.m64n32k16.f32.bf16.bf16 {%0, %1, %2, %3, %4, %5, %6, %7, %8, %9, %10, %11, %12, %13, %14, %15}, %16, %17, 1, 1, 1, 0, %18;"
    : "+f"(d[0]), "+f"(d[1]), "+f"(d[2]), "+f"(d[3]), "+f"(d[4]), "+f"(d[5]), "+f"(d[6]), "+f"(d[7]), "+f"(d[8]), "+f"(d[9]), "+f"(d[10]), "+f"(d[11]), "+f"(d[12]), "+f"(d[13]), "+f"(d[14]), "+f"(d[15])
    : "l"(da), "l"(db), "n"(TB));
}
template <int TB>
__device__ __forceinline__ void wg_rs256(float (&d)[128], uint32_t a0, uint32_t a1, uint32_t a2, uint32_t a3, uint64_t db) {
  asm volatile(
    "wgmma.mma_async.sync.aligned.m64n256k16.f32.bf16.bf16 {%0, %1, %2, %3, %4, %5, %6, %7, %8, %9, %10, %11, %12, %13, %14, %15, %16, %17, %18, %19, %20, %21, %22, %23, %24, %25, %26, %27, %28, %29, %30, %31, %32, %33, %34, %35, %36, %37, %38, %39, %40, %41, %42, %43, %44, %45, %46, %47, %48, %49, %50, %51, %52, %53, %54, %55, %56, %57, %58, %59, %60, %61, %62, %63, %64, %65, %66, %67, %68, %69, %70, %71, %72, %73, %74, %75, %76, %77, %78, %79, %80, %81, %82, %83, %84, %85, %86, %87, %88, %89, %90, %91, %92, %93, %94, %95, %96, %97, %98, %99, %100, %101, %102, %103, %104, %105, %106, %107, %108, %109, %110, %111, %112, %113, %114, %115, %116, %117, %118, %119, %120, %121, %122, %123, %124, %125, %126, %127}, {%128, %129, %130, %131}, %132, 1, 1, 1, %133;"
    : "+f"(d[0]), "+f"(d[1]), "+f"(d[2]), "+f"(d[3]), "+f"(d[4]), "+f"(d[5]), "+f"(d[6]), "+f"(d[7]), "+f"(d[8]), "+f"(d[9]), "+f"(d[10]), "+f"(d[11]), "+f"(d[12]), "+f"(d[13]), "+f"(d[14]), "+f"(d[15]), "+f"(d[16]), "+f"(d[17]), "+f"(d[18]), "+f"(d[19]), "+f"(d[20]), "+f"(d[21]), "+f"(d[22]), "+f"(d[23]), "+f"(d[24]), "+f"(d[25]), "+f"(d[26]), "+f"(d[27]), "+f"(d[28]), "+f"(d[29]), "+f"(d[30]), "+f"(d[31]), "+f"(d[32]), "+f"(d[33]), "+f"(d[34]), "+f"(d[35]), "+f"(d[36]), "+f"(d[37]), "+f"(d[38]), "+f"(d[39]), "+f"(d[40]), "+f"(d[41]), "+f"(d[42]), "+f"(d[43]), "+f"(d[44]), "+f"(d[45]), "+f"(d[46]), "+f"(d[47]), "+f"(d[48]), "+f"(d[49]), "+f"(d[50]), "+f"(d[51]), "+f"(d[52]), "+f"(d[53]), "+f"(d[54]), "+f"(d[55]), "+f"(d[56]), "+f"(d[57]), "+f"(d[58]), "+f"(d[59]), "+f"(d[60]), "+f"(d[61]), "+f"(d[62]), "+f"(d[63]), "+f"(d[64]), "+f"(d[65]), "+f"(d[66]), "+f"(d[67]), "+f"(d[68]), "+f"(d[69]), "+f"(d[70]), "+f"(d[71]), "+f"(d[72]), "+f"(d[73]), "+f"(d[74]), "+f"(d[75]), "+f"(d[76]), "+f"(d[77]), "+f"(d[78]), "+f"(d[79]), "+f"(d[80]), "+f"(d[81]), "+f"(d[82]), "+f"(d[83]), "+f"(d[84]), "+f"(d[85]), "+f"(d[86]), "+f"(d[87]), "+f"(d[88]), "+f"(d[89]), "+f"(d[90]), "+f"(d[91]), "+f"(d[92]), "+f"(d[93]), "+f"(d[94]), "+f"(d[95]), "+f"(d[96]), "+f"(d[97]), "+f"(d[98]), "+f"(d[99]), "+f"(d[100]), "+f"(d[101]), "+f"(d[102]), "+f"(d[103]), "+f"(d[104]), "+f"(d[105]), "+f"(d[106]), "+f"(d[107]), "+f"(d[108]), "+f"(d[109]), "+f"(d[110]), "+f"(d[111]), "+f"(d[112]), "+f"(d[113]), "+f"(d[114]), "+f"(d[115]), "+f"(d[116]), "+f"(d[117]), "+f"(d[118]), "+f"(d[119]), "+f"(d[120]), "+f"(d[121]), "+f"(d[122]), "+f"(d[123]), "+f"(d[124]), "+f"(d[125]), "+f"(d[126]), "+f"(d[127])
    : "r"(a0), "r"(a1), "r"(a2), "r"(a3), "l"(db), "n"(TB));
}
template <int TB>
__device__ __forceinline__ void wg_rs32(float (&d)[16], uint32_t a0, uint32_t a1, uint32_t a2, uint32_t a3, uint64_t db) {
  asm volatile(
    "wgmma.mma_async.sync.aligned.m64n32k16.f32.bf16.bf16 {%0, %1, %2, %3, %4, %5, %6, %7, %8, %9, %10, %11, %12, %13, %14, %15}, {%16, %17, %18, %19}, %20, 1, 1, 1, %21;"
    : "+f"(d[0]), "+f"(d[1]), "+f"(d[2]), "+f"(d[3]), "+f"(d[4]), "+f"(d[5]), "+f"(d[6]), "+f"(d[7]), "+f"(d[8]), "+f"(d[9]), "+f"(d[10]), "+f"(d[11]), "+f"(d[12]), "+f"(d[13]), "+f"(d[14]), "+f"(d[15])
    : "r"(a0), "r"(a1), "r"(a2), "r"(a3), "l"(db), "n"(TB));
}
template <int TB>
__device__ __forceinline__ void wg_cv128(float (&d)[64], uint32_t a0, uint32_t a1, uint32_t a2, uint32_t a3, uint64_t db) {
  asm volatile(
    "wgmma.mma_async.sync.aligned.m64n128k16.f32.bf16.bf16 {%0, %1, %2, %3, %4, %5, %6, %7, %8, %9, %10, %11, %12, %13, %14, %15, %16, %17, %18, %19, %20, %21, %22, %23, %24, %25, %26, %27, %28, %29, %30, %31, %32, %33, %34, %35, %36, %37, %38, %39, %40, %41, %42, %43, %44, %45, %46, %47, %48, %49, %50, %51, %52, %53, %54, %55, %56, %57, %58, %59, %60, %61, %62, %63}, {%64, %65, %66, %67}, %68, 1, 1, 1, %69;"
    : "+f"(d[0]), "+f"(d[1]), "+f"(d[2]), "+f"(d[3]), "+f"(d[4]), "+f"(d[5]), "+f"(d[6]), "+f"(d[7]), "+f"(d[8]), "+f"(d[9]), "+f"(d[10]), "+f"(d[11]), "+f"(d[12]), "+f"(d[13]), "+f"(d[14]), "+f"(d[15]), "+f"(d[16]), "+f"(d[17]), "+f"(d[18]), "+f"(d[19]), "+f"(d[20]), "+f"(d[21]), "+f"(d[22]), "+f"(d[23]), "+f"(d[24]), "+f"(d[25]), "+f"(d[26]), "+f"(d[27]), "+f"(d[28]), "+f"(d[29]), "+f"(d[30]), "+f"(d[31]), "+f"(d[32]), "+f"(d[33]), "+f"(d[34]), "+f"(d[35]), "+f"(d[36]), "+f"(d[37]), "+f"(d[38]), "+f"(d[39]), "+f"(d[40]), "+f"(d[41]), "+f"(d[42]), "+f"(d[43]), "+f"(d[44]), "+f"(d[45]), "+f"(d[46]), "+f"(d[47]), "+f"(d[48]), "+f"(d[49]), "+f"(d[50]), "+f"(d[51]), "+f"(d[52]), "+f"(d[53]), "+f"(d[54]), "+f"(d[55]), "+f"(d[56]), "+f"(d[57]), "+f"(d[58]), "+f"(d[59]), "+f"(d[60]), "+f"(d[61]), "+f"(d[62]), "+f"(d[63])
    : "r"(a0), "r"(a1), "r"(a2), "r"(a3), "l"(db), "n"(TB));
}
template <int TB>
__device__ __forceinline__ void wg_cv96(float (&d)[48], uint32_t a0, uint32_t a1, uint32_t a2, uint32_t a3, uint64_t db) {
  asm volatile(
    "wgmma.mma_async.sync.aligned.m64n96k16.f32.bf16.bf16 {%0, %1, %2, %3, %4, %5, %6, %7, %8, %9, %10, %11, %12, %13, %14, %15, %16, %17, %18, %19, %20, %21, %22, %23, %24, %25, %26, %27, %28, %29, %30, %31, %32, %33, %34, %35, %36, %37, %38, %39, %40, %41, %42, %43, %44, %45, %46, %47}, {%48, %49, %50, %51}, %52, 1, 1, 1, %53;"
    : "+f"(d[0]), "+f"(d[1]), "+f"(d[2]), "+f"(d[3]), "+f"(d[4]), "+f"(d[5]), "+f"(d[6]), "+f"(d[7]), "+f"(d[8]), "+f"(d[9]), "+f"(d[10]), "+f"(d[11]), "+f"(d[12]), "+f"(d[13]), "+f"(d[14]), "+f"(d[15]), "+f"(d[16]), "+f"(d[17]), "+f"(d[18]), "+f"(d[19]), "+f"(d[20]), "+f"(d[21]), "+f"(d[22]), "+f"(d[23]), "+f"(d[24]), "+f"(d[25]), "+f"(d[26]), "+f"(d[27]), "+f"(d[28]), "+f"(d[29]), "+f"(d[30]), "+f"(d[31]), "+f"(d[32]), "+f"(d[33]), "+f"(d[34]), "+f"(d[35]), "+f"(d[36]), "+f"(d[37]), "+f"(d[38]), "+f"(d[39]), "+f"(d[40]), "+f"(d[41]), "+f"(d[42]), "+f"(d[43]), "+f"(d[44]), "+f"(d[45]), "+f"(d[46]), "+f"(d[47])
    : "r"(a0), "r"(a1), "r"(a2), "r"(a3), "l"(db), "n"(TB));
}
template <int TB>
__device__ __forceinline__ void wg_cv64(float (&d)[32], uint32_t a0, uint32_t a1, uint32_t a2, uint32_t a3, uint64_t db) {
  asm volatile(
    "wgmma.mma_async.sync.aligned.m64n64k16.f32.bf16.bf16 {%0, %1, %2, %3, %4, %5, %6, %7, %8, %9, %10, %11, %12, %13, %14, %15, %16, %17, %18, %19, %20, %21, %22, %23, %24, %25, %26, %27, %28, %29, %30, %31}, {%32, %33, %34, %35}, %36, 1, 1, 1, %37;"
    : "+f"(d[0]), "+f"(d[1]), "+f"(d[2]), "+f"(d[3]), "+f"(d[4]), "+f"(d[5]), "+f"(d[6]), "+f"(d[7]), "+f"(d[8]), "+f"(d[9]), "+f"(d[10]), "+f"(d[11]), "+f"(d[12]), "+f"(d[13]), "+f"(d[14]), "+f"(d[15]), "+f"(d[16]), "+f"(d[17]), "+f"(d[18]), "+f"(d[19]), "+f"(d[20]), "+f"(d[21]), "+f"(d[22]), "+f"(d[23]), "+f"(d[24]), "+f"(d[25]), "+f"(d[26]), "+f"(d[27]), "+f"(d[28]), "+f"(d[29]), "+f"(d[30]), "+f"(d[31])
    : "r"(a0), "r"(a1), "r"(a2), "r"(a3), "l"(db), "n"(TB));
}
template <int TB>
__device__ __forceinline__ void wg_rs256_init(float (&d)[128], uint32_t a0, uint32_t a1, uint32_t a2, uint32_t a3, uint64_t db) {
  asm volatile(
    "wgmma.mma_async.sync.aligned.m64n256k16.f32.bf16.bf16 {%0, %1, %2, %3, %4, %5, %6, %7, %8, %9, %10, %11, %12, %13, %14, %15, %16, %17, %18, %19, %20, %21, %22, %23, %24, %25, %26, %27, %28, %29, %30, %31, %32, %33, %34, %35, %36, %37, %38, %39, %40, %41, %42, %43, %44, %45, %46, %47, %48, %49, %50, %51, %52, %53, %54, %55, %56, %57, %58, %59, %60, %61, %62, %63, %64, %65, %66, %67, %68, %69, %70, %71, %72, %73, %74, %75, %76, %77, %78, %79, %80, %81, %82, %83, %84, %85, %86, %87, %88, %89, %90, %91, %92, %93, %94, %95, %96, %97, %98, %99, %100, %101, %102, %103, %104, %105, %106, %107, %108, %109, %110, %111, %112, %113, %114, %115, %116, %117, %118, %119, %120, %121, %122, %123, %124, %125, %126, %127}, {%128, %129, %130, %131}, %132, 0, 1, 1, %133;"
    : "=f"(d[0]), "=f"(d[1]), "=f"(d[2]), "=f"(d[3]), "=f"(d[4]), "=f"(d[5]), "=f"(d[6]), "=f"(d[7]), "=f"(d[8]), "=f"(d[9]), "=f"(d[10]), "=f"(d[11]), "=f"(d[12]), "=f"(d[13]), "=f"(d[14]), "=f"(d[15]), "=f"(d[16]), "=f"(d[17]), "=f"(d[18]), "=f"(d[19]), "=f"(d[20]), "=f"(d[21]), "=f"(d[22]), "=f"(d[23]), "=f"(d[24]), "=f"(d[25]), "=f"(d[26]), "=f"(d[27]), "=f"(d[28]), "=f"(d[29]), "=f"(d[30]), "=f"(d[31]), "=f"(d[32]), "=f"(d[33]), "=f"(d[34]), "=f"(d[35]), "=f"(d[36]), "=f"(d[37]), "=f"(d[38]), "=f"(d[39]), "=f"(d[40]), "=f"(d[41]), "=f"(d[42]), "=f"(d[43]), "=f"(d[44]), "=f"(d[45]), "=f"(d[46]), "=f"(d[47]), "=f"(d[48]), "=f"(d[49]), "=f"(d[50]), "=f"(d[51]), "=f"(d[52]), "=f"(d[53]), "=f"(d[54]), "=f"(d[55]), "=f"(d[56]), "=f"(d[57]), "=f"(d[58]), "=f"(d[59]), "=f"(d[60]), "=f"(d[61]), "=f"(d[62]), "=f"(d[63]), "=f"(d[64]), "=f"(d[65]), "=f"(d[66]), "=f"(d[67]), "=f"(d[68]), "=f"(d[69]), "=f"(d[70]), "=f"(d[71]), "=f"(d[72]), "=f"(d[73]), "=f"(d[74]), "=f"(d[75]), "=f"(d[76]), "=f"(d[77]), "=f"(d[78]), "=f"(d[79]), "=f"(d[80]), "=f"(d[81]), "=f"(d[82]), "=f"(d[83]), "=f"(d[84]), "=f"(d[85]), "=f"(d[86]), "=f"(d[87]), "=f"(d[88]), "=f"(d[89]), "=f"(d[90]), "=f"(d[91]), "=f"(d[92]), "=f"(d[93]), "=f"(d[94]), "=f"(d[95]), "=f"(d[96]), "=f"(d[97]), "=f"(d[98]), "=f"(d[99]), "=f"(d[100]), "=f"(d[101]), "=f"(d[102]), "=f"(d[103]), "=f"(d[104]), "=f"(d[105]), "=f"(d[106]), "=f"(d[107]), "=f"(d[108]), "=f"(d[109]), "=f"(d[110]), "=f"(d[111]), "=f"(d[112]), "=f"(d[113]), "=f"(d[114]), "=f"(d[115]), "=f"(d[116]), "=f"(d[117]), "=f"(d[118]), "=f"(d[119]), "=f"(d[120]), "=f"(d[121]), "=f"(d[122]), "=f"(d[123]), "=f"(d[124]), "=f"(d[125]), "=f"(d[126]), "=f"(d[127])
    : "r"(a0), "r"(a1), "r"(a2), "r"(a3), "l"(db), "n"(TB));
}
template <int TB>
__device__ __forceinline__ void wg_rs32_init(float (&d)[16], uint32_t a0, uint32_t a1, uint32_t a2, uint32_t a3, uint64_t db) {
  asm volatile(
    "wgmma.mma_async.sync.aligned.m64n32k16.f32.bf16.bf16 {%0, %1, %2, %3, %4, %5, %6, %7, %8, %9, %10, %11, %12, %13, %14, %15}, {%16, %17, %18, %19}, %20, 0, 1, 1, %21;"
    : "=f"(d[0]), "=f"(d[1]), "=f"(d[2]), "=f"(d[3]), "=f"(d[4]), "=f"(d[5]), "=f"(d[6]), "=f"(d[7]), "=f"(d[8]), "=f"(d[9]), "=f"(d[10]), "=f"(d[11]), "=f"(d[12]), "=f"(d[13]), "=f"(d[14]), "=f"(d[15])
    : "r"(a0), "r"(a1), "r"(a2), "r"(a3), "l"(db), "n"(TB));
}

#define FULLW() mbar_wait(bar + B_FULL + 8 * slot, ph)
#define TEXPR cexp2(P.x * g128, P.w * g1)
#define RINGPOS 1
#define EMPTYW() mbar_wait(bar + B_EMPTY + 8 * slot, ph)
constexpr int NST = 7, SLOT = 9216;
constexpr uint32_t SM_XN = 0, SM_HIN = 147456, SM_RING = 163840, SM_BAR = SM_RING + 7 * SLOT;
constexpr uint32_t SM_KD = SM_BAR + 256, SMEM_BYTES = SM_KD + 3840;
constexpr uint32_t B_FULL = 0, B_EMPTY = 56, B_XN = 112, B_K2048 = 176, B_HF = 184, B_HE = 200, B_CV = 216, B_PT = 224, B_YT = 232, B_SG = 240, B_X = 248;
constexpr uint32_t PR_LN = 65536, PR_PAR = 98304, PR_K0 = SM_HIN + 12288;
constexpr uint32_t T_U = 0, T_KP = 17408, T_K0 = 51200, T_YT = 0, T_STG = 65536, T_PART = SM_HIN;
constexpr uint32_t U_BYTES = U_LEN * 2, KP_BYTES = KP_LEN * 4, IMG = 18432;

struct Params {
  CUtensorMap xn, gate, up, dn, dn5, dp, dp5, x, x5, y, y5, out, out5;
  const __nv_bfloat16 *xp, *logA, *Aim, *Cre, *Cim, *logdt, *Dsk;
};

__device__ __forceinline__ float us2f(uint32_t v) { return __uint_as_float(v << 16); }
struct KgIn { uint32_t la, ai, cr, ci, ldt, dsk; };
__device__ __forceinline__ void kgen_load(const Params& p, int ch0, int tid, KgIn& in) {
  const int e = ch0 * (NM_ / 2) + tid;
  in.la = __ldg((const uint32_t*)p.logA + e); in.ai = __ldg((const uint32_t*)p.Aim + e);
  in.cr = __ldg((const uint32_t*)p.Cre + e); in.ci = __ldg((const uint32_t*)p.Cim + e);
  in.ldt = __ldg((const unsigned short*)p.logdt + ch0 + (tid >> 6)); in.dsk = __ldg((const unsigned short*)p.Dsk + ch0 + (tid >> 6));
}
struct KgState { float acc[5][4]; float v; };
struct cf { float r, i; };
__device__ __forceinline__ cf cmul(cf a, cf b) { return {fmaf(a.r, b.r, -(a.i * b.i)), fmaf(a.r, b.i, a.i * b.r)}; }
__device__ __forceinline__ cf csq(cf a) { return {fmaf(a.r, a.r, -(a.i * a.i)), (a.r + a.r) * a.i}; }
__device__ __forceinline__ cf cexp2(float lm, float th) {
  float m; asm("ex2.approx.ftz.f32 %0, %1;" : "=f"(m) : "f"(lm));
  return {m * __cosf(th), m * __sinf(th)};
}
__device__ __forceinline__ float turns(float w) { return (w - rintf(w)) * 6.283185307179586f; }
__device__ __forceinline__ void kgen_params(unsigned char* sm, int tid, KgIn in, KgState& st) {
  const int warp = tid >> 5, lane = tid & 31;
  float4* par = (float4*)(sm + PR_PAR + warp * 6144) + lane;
  const float dt = bf_round(expf(bf_lo(in.ldt)));
  float v = 0.f;
#pragma unroll 1
  for (int r = 0; r < 2; r++) {
    const float x = -bf_round(expf(bf_lo(in.la))) * dt * 1.4426950408889634f;
    const float w = bf_lo(in.ai) * dt * 0.15915494309189535f;
    const cf c = {2.f * bf_lo(in.cr) * dt, 2.f * bf_lo(in.ci) * dt};
    const cf e2 = cexp2(2.f * x, turns(2.f * w)), e64 = cexp2(64.f * x, turns(64.f * w));
    const cf e4 = csq(e2), e6 = cmul(e2, e4), e128 = csq(e64), e256 = csq(e128), e512 = csq(e256), e1024 = csq(e512);
    const cf c1 = cmul(c, e128), c256 = cmul(c, e256), c512 = cmul(c, e512), c4 = cmul(c, e1024);
    const cf c516 = cmul(c512, e4), c258 = cmul(c256, e2), c260 = cmul(c256, e4), c262 = cmul(c256, e6);
    v += fmaf(c4.r, e1024.r, -(c4.i * e1024.i));
    par[0] = make_float4(x, turns(w), turns(8.f * w), turns(128.f * w));
    par[64] = make_float4(c.r, c.i, c1.r, c1.i);
    par[128] = make_float4(c4.r, c4.i, e64.r, e64.i);
    par[192] = make_float4(c512.r, c512.i, c516.r, c516.i);
    par[256] = make_float4(c256.r, c256.i, c258.r, c258.i);
    par[320] = make_float4(c260.r, c260.i, c262.r, c262.i);
    par += 32;
    in.la >>= 16; in.ai >>= 16; in.cr >>= 16; in.ci >>= 16;
  }
#pragma unroll
  for (int o = 16; o; o >>= 1) v += __shfl_xor_sync(0xffffffffu, v, o);
  __syncwarp();
#pragma unroll
  for (int t = 0; t < 5; t++) { st.acc[t][0] = st.acc[t][1] = st.acc[t][2] = st.acc[t][3] = 0.f; }
  if (lane == 0 && !(warp & 1)) st.acc[0][0] = bf_lo(in.dsk);
  st.v = v;
}
__device__ __forceinline__ void kgen_steps(unsigned char* sm, int tid, KgState& st) {
  const int warp = tid >> 5, lane = tid & 31, g = lane >> 2, q = lane & 3;
  const float4* par = (const float4*)(sm + PR_PAR + warp * 6144) + q;
  const float2* p3 = (const float2*)(par + 192) + (g & 1);
  const float2* p2 = (const float2*)(par + 256 + 64 * ((g >> 1) & 1)) + (g & 1);
  const float g1 = (float)g, g8 = 8.f * g1, g128 = 128.f * g1;
  const int l1 = 4 * (g >> 1) + q, l2 = 4 * (g >> 2) + q;
#pragma unroll 4
  for (int ks = 0; ks < 16; ks++) {
    const float4 P = par[4 * ks], Q = par[64 + 4 * ks], R = par[128 + 4 * ks];
    const float2 c3 = p3[8 * ks], c2 = p2[8 * ks];
    const cf e = cexp2(P.x * g1, P.y * g1), a1 = cexp2(P.x * g8, P.z * g1), t = TEXPR;
    const cf a2 = cmul(a1, cf{R.z, R.w});
    const cf t1 = {__shfl_sync(0xffffffffu, t.r, l1), __shfl_sync(0xffffffffu, t.i, l1)};
    const cf t2 = {__shfl_sync(0xffffffffu, t.r, l2), __shfl_sync(0xffffffffu, t.i, l2)};
    auto mma = [&](float (&d)[4], cf u, float cr, float ci) {
      const float b0 = fmaf(u.r, cr, -(u.i * ci)), b1 = fmaf(-u.r, ci, -(u.i * cr));
      asm("mma.sync.aligned.m16n8k8.row.col.f32.tf32.tf32.f32 {%0,%1,%2,%3}, {%4,%5,%6,%7}, {%8,%9}, {%0,%1,%2,%3};"
          : "+f"(d[0]), "+f"(d[1]), "+f"(d[2]), "+f"(d[3])
          : "r"(__float_as_uint(a1.r)), "r"(__float_as_uint(a2.r)), "r"(__float_as_uint(a1.i)), "r"(__float_as_uint(a2.i)),
            "r"(__float_as_uint(b0)), "r"(__float_as_uint(b1)));
    };
    mma(st.acc[0], e, Q.x, Q.y);
    mma(st.acc[1], e, Q.z, Q.w);
    mma(st.acc[4], t, R.x, R.y);
    mma(st.acc[2], t2, c2.x, c2.y);
    mma(st.acc[3], t1, c3.x, c3.y);
  }
}
__device__ __forceinline__ void kgen_finish(unsigned char* sm, unsigned short* kd, unsigned short* k2048, int tid, KgState& st) {
  const int warp = tid >> 5, lane = tid & 31, g = lane >> 2, q = lane & 3;
  float4* red = (float4*)(sm + SM_HIN + (warp >> 1) * 3072) + lane;
  if (warp & 1) {
#pragma unroll
    for (int t = 0; t < 5; t++) red[t * 32] = make_float4(st.acc[t][0], st.acc[t][1], st.acc[t][2], st.acc[t][3]);
    red[160].x = st.v;
  }
  named_bar(3, 256);
  if (!(warp & 1)) {
    uint32_t lo[5], hi[5];
#pragma unroll
    for (int t = 0; t < 5; t++) {
      const float4 r = red[t * 32];
      lo[t] = pack_bf16(st.acc[t][0] + r.x, st.acc[t][1] + r.y); hi[t] = pack_bf16(st.acc[t][2] + r.z, st.acc[t][3] + r.w);
    }
    *k2048 = (unsigned short)pack_bf16(st.v + red[160].x, 0.f);
    uint32_t* kw = (uint32_t*)kd;
    kw[lane] = lo[0]; kw[32 + lane] = hi[0]; kw[64 + lane] = lo[1]; kw[96 + lane] = hi[1];
    kw[128 + 2 * g + (q & 1) + 32 * (q >> 1)] = lo[2]; kw[144 + 2 * g + (q & 1) + 32 * (q >> 1)] = hi[2];
    kw[192 + g + 16 * q] = lo[3]; kw[200 + g + 16 * q] = hi[3];
    kd[512 + g + 32 * q] = (unsigned short)lo[4]; kd[528 + g + 32 * q] = (unsigned short)(lo[4] >> 16);
    kd[520 + g + 32 * q] = (unsigned short)hi[4]; kd[536 + g + 32 * q] = (unsigned short)(hi[4] >> 16);
  }
}
constexpr int kd_index(int l) {
  if (l < 256) return l;
  const int sh = l < 512 ? 1 : l < 1024 ? 2 : 3;
  return ((l + (1 << (sh - 1)) - 1 + ((l >> sh) & 1)) >> sh) + 128 * sh;
}
struct KTab { unsigned int e[512 * 4]; };
constexpr KTab make_ktab() {
  KTab t = {};
  for (int it = 0; it < 511; it++) {
    const int l0 = 4 * it, b1 = kd_index(l0) & ~1;
    const unsigned int np = 0x54 + 0x22 * (l0 ? kd_index(l0 - 1) - b1 : 0);
    unsigned int n[4] = {0, 0, 0, 0};
    for (int k = 0; k < 4; k++) n[k] = 0x10 + 0x22 * (kd_index(l0 + k) - b1);
    t.e[4 * it] = 2 * b1 | ((b1 < 638 ? 4u : 0u) << 16);
    t.e[4 * it + 1] = (n[0] + 0x44) | (np << 8) | (n[1] << 16) | (n[0] << 24);
    t.e[4 * it + 2] = n[2] | (n[1] << 8) | (n[3] << 16) | (n[2] << 24);
    t.e[4 * it + 3] = l0 ? 0xffffffffu : 0xffffu;
  }
  return t;
}
__device__ __align__(16) const KTab g_ktab = make_ktab();
template <int NT>
__device__ __forceinline__ void kexpand(uint32_t sb, uint32_t k0, uint32_t k1, uint32_t k2048, int tid, uint4 e) {
#pragma unroll 1
  for (int it = tid; it < 511; it += NT) {
    const uint4 en = __ldg((const uint4*)g_ktab.e + min(it + NT, 511));
    const uint32_t o = e.x & 0xffffu, o2 = o + (e.x >> 16), dst = sb + T_KP + 64 + 16 * it;
#pragma unroll
    for (int c = 0; c < 4; c++) {
      const uint32_t a = c ? k1 + 1280 * (c - 1) : k0;
      const uint32_t x0 = lds32(a + o - 4), x1 = lds32(a + o), x2 = lds32(a + o2);
      sts128(dst + c * KP_BYTES, make_uint4(__byte_perm(x0, x1, e.y) & e.w, __byte_perm(x1, x2, e.y >> 16), __byte_perm(x1, x2, e.z), __byte_perm(x1, x2, e.z >> 16)));
    }
    e = en;
  }
  if (tid < 36) {
    const int c = tid / 9, i = tid - 9 * c;
    uint4 v = make_uint4(0u, 0u, 0u, 0u);
    if (i == 4) {
      uint32_t z, y;
      asm volatile("ld.shared.u16 %0, [%1];" : "=r"(z) : "r"(k2048 + 2 * c) : "memory");
      asm volatile("ld.shared.u16 %0, [%1];" : "=r"(y) : "r"((c ? k1 + 1280 * (c - 1) : k0) + 1278) : "memory");
      v = make_uint4(z | (y << 16), z * 0x10001u, z * 0x10001u, z * 0x10001u);
    }
    sts128(sb + T_KP + c * KP_BYTES + 16 * (i < 4 ? i : 511 + i), v);
  }
}

template <int NR>
__device__ __forceinline__ void conv_mma(float (&d)[NR], const uint32_t* a, uint64_t db) {
  if constexpr (NR == 64) wg_cv128<0>(d, a[0], a[1], a[2], a[3], db);
  else if constexpr (NR == 48) wg_cv96<0>(d, a[0], a[1], a[2], a[3], db);
  else if constexpr (NR == 32) wg_cv64<0>(d, a[0], a[1], a[2], a[3], db);
  else wg_rs32<0>(d, a[0], a[1], a[2], a[3], db);
}
__device__ __forceinline__ void conv_load(uint32_t (&a)[8], uint32_t o) {
#pragma unroll
  for (int c = 0; c < 2; c++) {
    a[4 * c + 0] = lds32(o + c * KP_BYTES); a[4 * c + 1] = lds32(o + c * KP_BYTES + 512);
    a[4 * c + 2] = lds32(o + c * KP_BYTES - 32); a[4 * c + 3] = lds32(o + c * KP_BYTES + 480);
  }
}
template <int NR>
__device__ __forceinline__ void conv_phase(float (&dA)[NR], float (&dB)[NR], uint32_t (&a)[4][8], uint32_t kp, uint64_t dU) {
#pragma unroll 1
  for (int i = 0; i < 2; i++) {
#pragma unroll
    for (int k = 0; k < 4; k++) {
      wg_fence();
      conv_mma<NR>(dA, a[k], dU - 2 * k); conv_mma<NR>(dB, a[k] + 4, dU - 2 * k + (U_BYTES >> 4));
      wg_commit();
      wg_wait<1>();
      if (k == 2 && i) kp += 64 * 24;
      conv_load(a[(k + 2) & 3], kp + 64 * (k + 2));
    }
    kp += 256;
    dU -= 8;
  }
  wg_wait<0>();
  reg_fence(dA); reg_fence(dB);
}
template <int NR>
__device__ __forceinline__ void upper_copy(float (&dst)[NR - 16], const float (&src)[NR]) {
#pragma unroll
  for (int i = 0; i < NR - 16; i++) asm volatile("mov.b32 %0, %1;" : "=f"(dst[i]) : "f"(src[i + 16]));
}
__device__ __forceinline__ void conv2(uint32_t sb, int wg, int w, int lane, int ch, int cnt) {
  const int g = lane >> 2, q = lane & 3;
  float dA[64], dB[64];
  uint32_t a[4][8];
  const uint32_t kp = sb + T_KP + 2 * wg * KP_BYTES + 4 * (16 + 256 * (w >> 1) + 8 * (w & 1) + g - 2 * q);
  const uint64_t dU = mk_desc(sb + T_U + 2 * wg * U_BYTES + 256, 16, 256, 3);
#pragma unroll
  for (int i = 0; i < 64; i++) { dA[i] = 0.f; dB[i] = 0.f; }
  conv_load(a[0], kp); conv_load(a[1], kp + 64);
  conv_phase<64>(dA, dB, a, kp, dU);
  float eA[48], eB[48];
  upper_copy<64>(eA, dA); upper_copy<64>(eB, dB);
  conv_phase<48>(eA, eB, a, kp + 2048, dU);
  float fA[32], fB[32];
  upper_copy<48>(fA, eA); upper_copy<48>(fB, eB);
  conv_phase<32>(fA, fB, a, kp + 4096, dU);
  float gA[16], gB[16];
  upper_copy<32>(gA, fA); upper_copy<32>(gB, fB);
  conv_phase<16>(gA, gB, a, kp + 6144, dU);
#pragma unroll
  for (int i = 0; i < 16; i++) {
    dA[16 + i] = eA[i]; dA[32 + i] = fA[i]; dA[48 + i] = gA[i];
    dB[16 + i] = eB[i]; dB[32 + i] = fB[i]; dB[48 + i] = gB[i];
  }
  PROF_T(53);
  float z[2][16][2];
#pragma unroll
  for (int m = 0; m < 16; m++)
#pragma unroll
    for (int e = 0; e < 2; e++) {
      z[0][m][e] = m ? dA[4 * m + e] + dA[4 * m - 2 + e] : dA[e];
      z[1][m][e] = m ? dB[4 * m + e] + dB[4 * m - 2 + e] : dB[e];
    }
  named_bar(1 + wg, 128);
  const uint32_t xb = sb + T_KP + 2 * wg * KP_BYTES;
  const uint32_t xw = xb + (w * 32 + lane) * 16, xr = xb + ((w ^ 2) * 32 + lane) * 16;
  float k[2][8][2];
  if (w < 2) {
#pragma unroll
    for (int c = 0; c < 2; c++)
#pragma unroll
      for (int m = 0; m < 8; m += 2) {
        sts128(xw + (4 * c + (m >> 1)) * 2048, make_uint4(__float_as_uint(z[c][8 + m][0]), __float_as_uint(z[c][8 + m][1]), __float_as_uint(z[c][9 + m][0]), __float_as_uint(z[c][9 + m][1])));
        k[c][m][0] = z[c][m][0]; k[c][m][1] = z[c][m][1]; k[c][m + 1][0] = z[c][m + 1][0]; k[c][m + 1][1] = z[c][m + 1][1];
      }
  } else {
#pragma unroll
    for (int c = 0; c < 2; c++)
#pragma unroll
      for (int m = 0; m < 8; m += 2) {
        sts128(xw + (4 * c + (m >> 1)) * 2048, m ? make_uint4(__float_as_uint(z[c][m - 2][0]), __float_as_uint(z[c][m - 2][1]), __float_as_uint(z[c][m - 1][0]), __float_as_uint(z[c][m - 1][1])) : make_uint4(0u, 0u, 0u, 0u));
        k[c][m][0] = z[c][6 + m][0]; k[c][m][1] = z[c][6 + m][1]; k[c][m + 1][0] = z[c][7 + m][0]; k[c][m + 1][1] = z[c][7 + m][1];
      }
  }
  named_bar(1 + wg, 128);
  const uint32_t yb = sb + T_U + 2 * wg * U_BYTES;
#pragma unroll
  for (int c = 0; c < 2; c++)
#pragma unroll
    for (int m = 0; m < 8; m += 4) {
      const uint4 u = lds128(xr + (4 * c + (m >> 1)) * 2048), v = lds128(xr + (4 * c + (m >> 1) + 1) * 2048);
      stmatrix_x4_t(yb + c * 4096 + (64 * (w >> 1) + 8 * m + lane) * 32 + 16 * (w & 1),
                    pack_bf16(k[c][m][0] + __uint_as_float(u.x), k[c][m][1] + __uint_as_float(u.y)), pack_bf16(k[c][m + 1][0] + __uint_as_float(u.z), k[c][m + 1][1] + __uint_as_float(u.w)),
                    pack_bf16(k[c][m + 2][0] + __uint_as_float(v.x), k[c][m + 2][1] + __uint_as_float(v.y)), pack_bf16(k[c][m + 3][0] + __uint_as_float(v.z), k[c][m + 3][1] + __uint_as_float(v.w)));
    }
  fence_async_smem();
  named_bar(1 + wg, 128);
  if (w == 0 && lane == 0) {
    PROF_T(54);
    bulk_s2g(g_y + (size_t)ch * L_, yb, 8192);
    bulk_commit_wait();
    PROF_T(55);
    cnt_add_done(cnt);
  }
  __syncwarp();
}

__global__ void __cluster_dims__(2, 1, 1) __launch_bounds__(384, 1) fused_kernel(const __grid_constant__ Params p) {
  extern __shared__ __align__(1024) unsigned char smem_raw[];
  const uint32_t sb = smem_u32(smem_raw);
  const uint32_t bar = sb + SM_BAR;
  const uint32_t vb = blockIdx.x;
  const int j = vb & 1, pair = vb >> 1, mt = pair & 15, sp = pair >> 4;
  const bool spare = pair >= 64;
  const int warp = __shfl_sync(0xffffffffu, threadIdx.x >> 5, 0), wg = warp >> 2, w = warp & 3;
  const int row0 = mt * 128 + (2 * sp + j) * 16;
  const int f0 = sp * 1152;
  const long long t_start = clock64();
  KgIn kin;
  if (wg < 2) kgen_load(p, spare ? 512 + ((int)vb - 128) * 16 : vb * 4, threadIdx.x, kin);
  if (threadIdx.x >= 288 && threadIdx.x < 301) prefetch_map(&p.xn + (threadIdx.x - 288));
  if (threadIdx.x == 256) {
    mbar_init(bar + B_X, 1);
    if (!spare) {
      mbar_expect_tx(bar + B_X, 16 * D_ * 2);
      bulk_g2s(sb + PR_LN, p.xp + (size_t)row0 * D_, 16 * D_ * 2, bar + B_X);
    }
#pragma unroll
    for (int i = 0; i < 30; i++) if (i != 22) mbar_init(bar + 8 * i, (i >= 7 && i < 14) ? 8 : (i == 27 && !spare) ? 4 : 1);
    mbar_init(bar + B_SG, 2);
    mbar_expect_tx(bar + B_HF, 8192); mbar_expect_tx(bar + B_HF + 8, 8192);
    asm volatile("fence.mbarrier_init.release.cluster;" ::: "memory");
  }
  __syncthreads();
  asm volatile("barrier.cluster.arrive.relaxed.aligned;" ::: "memory");

  if (wg == 2) {
    const int t = threadIdx.x & 127, lane = t & 31;
    const bool el = elect_one();
    if (!spare) {
      const uint32_t ra = sb + PR_LN + (t >> 3) * (D_ * 2) + (t & 7) * 16;
      if (w == 1 && el) {
#pragma unroll 1
        for (int u = 0; u < NST; u++) {
          const uint32_t dst = sb + SM_RING + u * SLOT, fb = bar + B_FULL + 8 * u;
          mbar_expect_tx(fb, 8192);
          tma_2d(dst, &p.gate, f0 + 64 * j, 32 * u, fb);
          tma_2d(dst + 4096, &p.up, f0 + 64 * j, 32 * u, fb);
        }
      }
      mbar_wait(bar + B_X, 0);
      PROF_T(61);
      uint4 v[9];
#pragma unroll
      for (int i = 0; i < 9; i++) v[i] = lds128(ra + i * 128);
      uint32_t* u = (uint32_t*)v;
      float s = 0.f, s2 = 0.f, q = 0.f, q2 = 0.f;
#pragma unroll
      for (int i = 0; i < 36; i++) { s += bf_lo(u[i]); s2 += bf_hi(u[i]); }
      s += s2;
#pragma unroll
      for (int o = 4; o; o >>= 1) s += __shfl_xor_sync(0xffffffffu, s, o);
      s *= (1.0f / D_);
#pragma unroll
      for (int i = 0; i < 36; i++) {
        const float a = bf_lo(u[i]) - s, b = bf_hi(u[i]) - s;
        q = fmaf(a, a, q); q2 = fmaf(b, b, q2);
      }
      q += q2;
#pragma unroll
      for (int o = 4; o; o >>= 1) q += __shfl_xor_sync(0xffffffffu, q, o);
      const float mb = bf_round(s);
      const float rinv = 1.0f / bf_round(sqrtf(bf_round(bf_round(q * (1.0f / D_)) + 1e-5f)));
#pragma unroll
      for (int i = 0; i < 36; i++) {
        const uint32_t d = pack_bf16(bf_lo(u[i]) - mb, bf_hi(u[i]) - mb);
        u[i] = pack_bf16(bf_lo(d) * rinv, bf_hi(d) * rinv);
      }
#pragma unroll
      for (int i = 0; i < 9; i++) sts128(ra + i * 128, v[i]);
      fence_async_smem();
      named_bar(5, 128);
      PROF_T(62);
      if (w == 0 && el) bulk_s2g(g_xn + (size_t)row0 * D_, sb + PR_LN, 16 * D_ * 2);
    }
    asm volatile("barrier.cluster.wait.aligned;" ::: "memory");
    asm volatile("setmaxnreg.dec.sync.aligned.u32 24;");
    if (w == 0) {
      if (!spare) {
        if (el) {
          bulk_commit_wait();
          cnt_add_done(C_LN + mt);
        }
        __syncwarp();
        PROF_T(63);
        cnt_wait(C_LN + mt, 8);
        PROF_T(67);
        fence_async_all();
#pragma unroll 1
        for (int kb = 0; kb < 6; kb++) {
          if (el) {
            mbar_expect_tx(bar + B_XN + 8 * kb, 16384);
            tma_2d(sb + SM_XN + kb * 16384, &p.xn, kb * 64, mt * 128, bar + B_XN + 8 * kb);
          }
        }
        named_bar(4, 384);
        PROF_T(69);
        uint32_t slot = 0, ph = 0;
#pragma unroll 1
        for (int c = 0; c <= 9; c++) {
          const int fc = f0 + c * 128;
          if (c < 9) {
            for (int u = c ? 0 : NST; u < 18; u++) {
              EMPTYW();
              if (el) {
                const uint32_t dst = sb + SM_RING + slot * SLOT, fb = bar + B_FULL + 8 * slot;
                mbar_expect_tx(fb, 8192);
                tma_2d(dst, &p.gate, fc + 64 * j, 32 * u, fb);
                tma_2d(dst + 4096, &p.up, fc + 64 * j, 32 * u, fb);
                if (c == 0 && u < 10) {
                  const int kb = u - 1;
                  if (kb < 8) mbar_expect_tx(bar + B_XN + 8 * kb, kb < 7 ? 16384 : 32768);
                  tma_2d(sb + SM_XN + kb * 16384, &p.xn, kb * 64, mt * 128, bar + B_XN + 8 * min(kb, 7));
                }
              }
              if (++slot == NST) { slot = 0; ph ^= 1; }
            }
          }
          const int fp = (fc - 128 + 64 * (1 - j)) >> 3, fo = fc + 64 * j;
#pragma unroll
          for (int i = 0; i < 8; i++) {
            const bool isP = i < 4;
            const int u = i & 3;
            if (isP ? (c == 0) : (c == 9)) continue;
            EMPTYW();
            if (el) {
              const uint32_t dst = sb + SM_RING + slot * SLOT, fb = bar + B_FULL + 8 * slot;
              mbar_expect_tx(fb, 9216);
              if (isP) {
                tma_5d(dst, &p.dp, 0, 0, fp + 4 * (u >> 1), 2 * (u & 1), 4 * j, fb);
                tma_4d(dst + 8192, &p.dp5, 512 + 32 * j, 0, fp + 4 * (u >> 1), 2 * (u & 1), fb);
              } else {
                tma_3d(dst, &p.dn, 0, fo + 16 * u, 4 * j, fb);
                tma_2d(dst + 8192, &p.dn5, 512 + 32 * j, fo + 16 * u, fb);
              }
            }
            if (++slot == NST) { slot = 0; ph ^= 1; }
          }
        }
        const int ch0 = vb * 4;
        cnt_wait(C_U, 384);
        fence_async_all();
        if (el) {
          mbar_expect_tx(bar + B_CV, 4 * U_BYTES);
          bulk_g2s(sb + T_U, g_u + (size_t)ch0 * U_LEN, 4 * U_BYTES, bar + B_CV);
        }
        unsigned char* img = g_part + (size_t)(2 * mt + j) * 16 * IMG;
        mbar_wait(bar + B_SG, 0);
        PROF_T(71);
        if (lane < 15) {
          const int qi = lane / 5, pc = lane - 5 * qi, r = (sp + 1 + qi) & 3;
          bulk_s2g(img + (r * 4 + sp) * IMG + pc * 4096, sb + T_STG + pc * 16384 + (r >> 1) * 8192 + (r & 1) * (pc < 4 ? 4096 : 2048), pc < 4 ? 4096 : 2048);
          bulk_commit_wait();
        } else if (lane == 15) {
          mbar_expect_tx(bar + B_PT, 4 * IMG);
#pragma unroll 1
          for (int i = 0; i < 4; i++) tma_2d(sb + T_PART + 3 * IMG + i * 4096, &p.x, 256 * j + 64 * i, mt * 128 + 32 * sp, bar + B_PT);
          tma_2d(sb + T_PART + 3 * IMG + 16384, &p.x5, 512 + 32 * j, mt * 128 + 32 * sp, bar + B_PT);
        }
        __syncwarp();
        PROF_T(72);
        if (el) cnt_add_done(C_PART + 2 * mt + j);
        PROF_T(73);
        cnt_wait(C_PART + 2 * mt + j, 4);
        fence_async_all();
        PROF_T(74);
        if (lane < 3) bulk_g2s(sb + T_PART + lane * IMG, img + (sp * 4 + ((sp + 1 + lane) & 3)) * IMG, IMG, bar + B_PT);
        cnt_wait(C_Y5, 32);
        cnt_wait(C_Y + (ch0 >> 8), 128);
        cnt_wait(C_Y + j, 128);
        PROF_T(75);
        fence_async_all();
        if (el) {
          mbar_expect_tx(bar + B_YT, IMG);
          tma_2d(sb + T_YT, &p.y, mt * 128 + 32 * sp, 256 * j, bar + B_YT);
          tma_2d(sb + T_YT + 16384, &p.y5, mt * 128 + 32 * sp, 512 + 32 * j, bar + B_YT);
        }
        cnt_wait(C_Y + (j ^ 1), 128);
      } else {
        named_bar(7, 288);
        cnt_wait(C_U, 384);
        fence_async_all();
#pragma unroll 1
        for (int grp = 0; grp < 4; grp++) {
          const int ch0 = 512 + ((int)vb - 128) * 16 + grp * 4;
          if (grp) mbar_wait(bar + B_SG, (grp - 1) & 1);
          if (el) {
            mbar_expect_tx(bar + B_CV, 4 * U_BYTES);
            bulk_g2s(sb + T_U, g_u + (size_t)ch0 * U_LEN, 4 * U_BYTES, bar + B_CV);
          }
        }
      }
      PROF_T(79);
      PROF_DUMP();
      unsigned int old = 0;
      if (el) old = atomicAdd(g_cnt + C_DONE * 32, 1u) + 1;
      if (__any_sync(0xffffffffu, old == gridDim.x)) { g_cnt[lane * 32] = 0u; g_cnt[(lane + 32) * 32] = 0u; }
    } else {
      if (!spare) {
        named_bar(4, 384);
        uint4 k0v = make_uint4(0u, 0u, 0u, 0u);
        if (t < 112) k0v = lds128(sb + PR_K0 + (t - 32) * 16);
        named_bar(8, 96);
        if (t == 32) { mbar_arrive_remote(mapa(bar + B_HE, j ^ 1)); mbar_arrive_remote(mapa(bar + B_HE + 8, j ^ 1)); }
#pragma unroll 1
        for (int i = 0; i < 8; i++) mbar_wait(bar + B_XN + 8 * i, 0);
        const int tok = 8 * ((lane & 7) >> 1) + 2 * (lane >> 3) + (lane & 1);
#pragma unroll 1
        for (int it = w - 1; it < 36; it += 3) {
          const int oc = 9 * (2 * sp + j) + (it >> 2), tg = it & 3;
          uint4 v;
          ldmatrix_x4_t(sb + SM_XN + (oc >> 3) * 16384 + (32 * tg + tok) * 128 + (((oc ^ tok) & 7) << 4), v.x, v.y, v.z, v.w);
          ((uint4*)(g_u + (size_t)(8 * oc + (lane >> 2)) * U_LEN + 128 + mt * 128))[(4 * tg + (lane & 3)) ^ (tg >> 1)] = v;
        }
        __syncwarp();
        if (lane == 0) { fence_async_all(); cnt_add(C_U); }
        const uint4 e0 = __ldg((const uint4*)g_ktab.e + (t - 32));
        named_bar(9, 352);
        if (t < 112) sts128(sb + T_K0 + (t - 32) * 16, k0v);
        named_bar(8, 96);
        kexpand<96>(sb, sb + T_K0, sb + SM_KD, bar + B_K2048, t - 32, e0);
        __syncwarp();
        if (lane == 0) mbar_arrive(bar + B_CV);
      }
    }
  } else {
    const int t = threadIdx.x & 127, lane = t & 31;
    KgState kst;
    kgen_params(smem_raw, threadIdx.x, kin, kst);
    if (!spare) {
      PROF_T(60);
      kgen_steps(smem_raw, threadIdx.x, kst);
      PROF_T(51);
      kgen_finish(smem_raw, (unsigned short*)(smem_raw + (warp < 2 ? PR_K0 : SM_KD + ((warp >> 1) - 1) * 1280)),
                  (unsigned short*)(smem_raw + SM_BAR + B_K2048) + (warp >> 1), threadIdx.x, kst);
      named_arrive(4, 384);
    } else {
      const int c0 = 512 + ((int)vb - 128) * 16;
#pragma unroll 1
      for (int grp = 0; grp < 4; grp++) {
        if (grp) { kgen_load(p, c0 + grp * 4, threadIdx.x, kin); kgen_params(smem_raw, threadIdx.x, kin, kst); }
        kgen_steps(smem_raw, threadIdx.x, kst);
        kgen_finish(smem_raw, (unsigned short*)(smem_raw + SM_RING + (grp * 4 + (warp >> 1)) * 1280),
                    (unsigned short*)(smem_raw + SM_KD) + grp * 4 + (warp >> 1), threadIdx.x, kst);
        named_bar(3, 256);
      }
      named_arrive(7, 288);
    }
    PROF_T(41);
    asm volatile("barrier.cluster.wait.aligned;" ::: "memory");
    asm volatile("setmaxnreg.inc.sync.aligned.u32 240;");
    if (!spare) {
      const bool leader = (t == 0);
      float O1[128], O2[16];
      uint32_t slot = 0, ph = 0, prev = 0;
      const uint32_t hin = sb + SM_HIN + wg * 8192;
      const uint32_t r_hin = mapa(hin + (16 * w + (lane >> 2)) * 128 + (((lane & 3) ^ (lane >> 2)) << 4), j ^ 1);
      const uint32_t r_hf = mapa(bar + B_HF + 8 * wg, j ^ 1), r_he = mapa(bar + B_HE + 8 * wg, j ^ 1);
      const uint64_t dA0 = mk_desc(sb + SM_XN + wg * 8192, 16, 1024, 1);
      const uint64_t dH0 = mk_desc(hin, 16, 1024, 1);
      const uint64_t dG0 = mk_desc(sb + SM_RING, 4096, 1024, 1);
      const uint64_t dW0 = mk_desc(sb + SM_RING, 2048, 1024, 1);
      const uint64_t dX0 = mk_desc(sb + SM_RING + 8192, 512, 512, 2);
      auto adv = [&]() { prev = slot; if (++slot == NST) { slot = 0; ph ^= 1; } };
      auto release = [&](uint32_t s) { if (lane == 0) mbar_arrive(bar + B_EMPTY + 8 * s); };
      auto peer_begin = [&](int cp) {
        mbar_wait(bar + B_HF + 8 * wg, cp & 1);
        if (leader && cp < 8) mbar_expect_tx(bar + B_HF + 8 * wg, 8192);
        fence_async_smem();
      };
      auto peer_unit = [&](int u) {
        wg_fence();
        wg_ss256<1>(O1, dH0 + 2 * u, dW0 + (uint64_t)(slot * (SLOT >> 4)));
        wg_ss32<1>(O2, dH0 + 2 * u, dX0 + (uint64_t)(slot * (SLOT >> 4)));
        wg_commit();
      };
      auto chunk = [&](auto first_c, const int c) {
        constexpr bool FIRST = decltype(first_c)::value;
        float S[64];
        {
          if (FIRST) mbar_wait(bar + B_XN, 0);
          FULLW();
          if (FIRST) { PROF_T(42); PROF_G(2); }
          const uint64_t db = dG0 + (uint64_t)(slot * (SLOT >> 4));
          wg_fence();
          wg_ss128_init<1>(S, dA0, db);
          wg_ss128<1>(S, dA0 + 2, db + 128);
          wg_commit();
          adv();
        }
#pragma unroll 1
        for (int u = 1; u < 18; u++) {
          if (FIRST && !(u & 1) && u < 16) mbar_wait(bar + B_XN + 8 * (u >> 1), 0);
          FULLW();
          const uint64_t da = dA0 + (uint64_t)((u >> 1) * 1024 + (u & 1) * 4);
          const uint64_t db = dG0 + (uint64_t)(slot * (SLOT >> 4));
          wg_fence();
          wg_ss128<1>(S, da, db);
          wg_ss128<1>(S, da + 2, db + 128);
          wg_commit();
          if constexpr (!FIRST) { if (u == 12) peer_begin(c - 1); }
          wg_wait<1>();
          release(prev);
          if (c == 8 && u == 8) named_arrive(9, 352);
          adv();
        }
        uint32_t H[16];
        if constexpr (FIRST) { wg_wait<0>(); release(prev); }
        uint32_t rs = prev;
        auto rel_next = [&]() { release(rs); if (++rs == NST) rs = 0; };
        auto P = [&](int u) {
          FULLW();
          peer_unit(u);
          if (u) { wg_wait<2>(); rel_next(); }
          adv();
        };
        auto E = [&](int u) {
#pragma unroll
          for (int i = 8 * u; i < 8 * u + 8; i++) asm volatile("" : "+f"(S[i]), "+f"(S[32 + i])::"memory");
#pragma unroll
          for (int g = 2 * u; g < 2 * u + 2; g++) {
            H[2 * g] = pack_bf16(geglu(S[4 * g], S[32 + 4 * g]), geglu(S[4 * g + 1], S[33 + 4 * g]));
            H[2 * g + 1] = pack_bf16(geglu(S[4 * g + 2], S[34 + 4 * g]), geglu(S[4 * g + 3], S[35 + 4 * g]));
          }
#pragma unroll
          for (int i = 4 * u; i < 4 * u + 4; i++) asm volatile("" : "+r"(H[i])::"memory");
        };
        auto O = [&](int u) {
          FULLW();
          wg_fence();
          if (FIRST && u == 0) {
            wg_rs256_init<1>(O1, H[0], H[1], H[2], H[3], dW0 + (uint64_t)(slot * (SLOT >> 4)));
            wg_rs32_init<1>(O2, H[0], H[1], H[2], H[3], dX0 + (uint64_t)(slot * (SLOT >> 4)));
            rs = slot;
          } else {
            wg_rs256<1>(O1, H[4 * u], H[4 * u + 1], H[4 * u + 2], H[4 * u + 3], dW0 + (uint64_t)(slot * (SLOT >> 4)));
            wg_rs32<1>(O2, H[4 * u], H[4 * u + 1], H[4 * u + 2], H[4 * u + 3], dX0 + (uint64_t)(slot * (SLOT >> 4)));
          }
          wg_commit();
          if (u == 3) {
            mbar_wait(bar + B_HE + 8 * wg, c & 1);
            st_async_v4(r_hin, H[0], H[2], H[4], H[6], r_hf);
            st_async_v4(r_hin ^ 64, H[8], H[10], H[12], H[14], r_hf);
            st_async_v4(r_hin + 1024, H[1], H[3], H[5], H[7], r_hf);
            st_async_v4((r_hin ^ 64) + 1024, H[9], H[11], H[13], H[15], r_hf);
          }
          if (!FIRST || u >= 2) { wg_wait<2>(); rel_next(); }
          if (u == 1) { if constexpr (!FIRST) { if (leader) mbar_arrive_remote(r_he); } }
          if (u == 3) { wg_wait<1>(); rel_next(); wg_wait<0>(); rel_next(); }
          adv();
        };
        if constexpr (FIRST) { E(0); O(0); E(1); O(1); E(2); O(2); E(3); O(3); }
        else { P(0); P(1); E(0); P(2); E(1); P(3); O(0); E(2); O(1); O(2); E(3); O(3); }
        PROF_T(4 + 4 * c);
      };
      chunk(std::true_type{}, 0);
#pragma unroll 1
      for (int c = 1; c < 9; c++) chunk(std::false_type{}, c);
      peer_begin(8);
#pragma unroll 1
      for (int u = 0; u < 4; u++) { FULLW(); peer_unit(u); adv(); }
      wg_wait<0>();
      reg_fence(O1); reg_fence(O2);
      PROF_T(40); PROF_G(3);
      const int mi = lane >> 3, li = lane & 7;
      {
        const int row = 16 * w + 8 * (mi & 1) + li;
        const uint32_t stg = sb + T_STG + wg * 8192 + row * 128;
#pragma unroll
        for (int g = 0; g < 32; g += 2)
          stmatrix_x4(stg + (g >> 3) * 16384 + ((((g & 7) + (mi >> 1)) ^ li) << 4), pack_bf16(O1[4 * g], O1[4 * g + 1]), pack_bf16(O1[4 * g + 2], O1[4 * g + 3]),
                      pack_bf16(O1[4 * g + 4], O1[4 * g + 5]), pack_bf16(O1[4 * g + 6], O1[4 * g + 7]));
#pragma unroll
        for (int g = 0; g < 4; g += 2)
          stmatrix_x4(stg + 65536 - row * 64 + (((g + (mi >> 1)) ^ (li >> 1)) << 4), pack_bf16(O2[4 * g], O2[4 * g + 1]), pack_bf16(O2[4 * g + 2], O2[4 * g + 3]),
                      pack_bf16(O2[4 * g + 4], O2[4 * g + 5]), pack_bf16(O2[4 * g + 6], O2[4 * g + 7]));
        fence_async_smem();
        named_bar(1 + wg, 128);
        if (leader) mbar_arrive(bar + B_SG);
      }
      mbar_wait(bar + B_CV, 0);
      PROF_T(43);
      conv2(sb, wg, w, lane, vb * 4 + 2 * wg, C_Y + (vb >> 6));
      PROF_T(44); PROF_G(5);
      const int w8 = warp, row = 16 * (w8 & 1) + 8 * (mi & 1) + li;
      const uint32_t own = sb + T_STG + (sp >> 1) * 8192;
      const int nblk = w8 < 4 ? 5 : 4;
      named_bar(3, 256);
      mbar_wait(bar + B_PT, 0);
#pragma unroll 1
      for (int k = 0; k < nblk; k++) {
        const uint32_t o = k < 4 ? row * 128 + (((2 * k + (mi >> 1)) ^ li) << 4) : row * 64 + (((2 * (w8 >> 1) + (mi >> 1)) ^ (li >> 1)) << 4);
        const uint32_t oa = own + o + (k < 4 ? (w8 >> 1) * 16384 + (sp & 1) * 4096 : 65536 + (sp & 1) * 2048);
        const uint32_t pa = sb + T_PART + o + (k < 4 ? (w8 >> 1) * 4096 : 16384);
        uint32_t r[4];
        float f[8];
        ldmatrix_x4(oa, r);
#pragma unroll
        for (int i = 0; i < 4; i++) { f[2 * i] = bf_lo(r[i]); f[2 * i + 1] = bf_hi(r[i]); }
#pragma unroll
        for (int s = 0; s < 4; s++) {
          ldmatrix_x4(pa + s * IMG, r);
#pragma unroll
          for (int i = 0; i < 4; i++) { f[2 * i] += bf_lo(r[i]); f[2 * i + 1] += bf_hi(r[i]); }
        }
        stmatrix_x4(oa, pack_bf16(f[0], f[1]), pack_bf16(f[2], f[3]), pack_bf16(f[4], f[5]), pack_bf16(f[6], f[7]));
      }
      __syncwarp();
      PROF_T(56);
      mbar_wait(bar + B_YT, 0);
      PROF_T(45); PROF_G(6);
#pragma unroll 1
      for (int k = 0; k < nblk; k++) {
        const uint32_t o = k < 4 ? row * 128 + (((2 * k + (mi >> 1)) ^ li) << 4) : row * 64 + (((2 * (w8 >> 1) + (mi >> 1)) ^ (li >> 1)) << 4);
        const uint32_t oa = own + o + (k < 4 ? (w8 >> 1) * 16384 + (sp & 1) * 4096 : 65536 + (sp & 1) * 2048);
        const int chl = (k < 4 ? 64 * (w8 >> 1) + 16 * k : 256 + 16 * (w8 >> 1)) + 8 * (mi >> 1) + li;
        uint32_t r[4], y0, y1, y2, y3;
        ldmatrix_x4(oa, r);
        ldmatrix_x4_t(sb + T_YT + chl * 64 + (((2 * (w8 & 1) + (mi & 1)) ^ (li >> 1)) << 4), y0, y1, y2, y3);
        stmatrix_x4(oa, pack_bf16(bf_lo(r[0]) + bf_lo(y0), bf_hi(r[0]) + bf_hi(y0)), pack_bf16(bf_lo(r[1]) + bf_lo(y1), bf_hi(r[1]) + bf_hi(y1)),
                    pack_bf16(bf_lo(r[2]) + bf_lo(y2), bf_hi(r[2]) + bf_hi(y2)), pack_bf16(bf_lo(r[3]) + bf_lo(y3), bf_hi(r[3]) + bf_hi(y3)));
      }
      PROF_T(57);
      fence_async_smem();
      named_bar(3, 256);
      if (threadIdx.x < 5) {
        if (threadIdx.x < 4) tma_store_2d(&p.out, own + threadIdx.x * 16384 + (sp & 1) * 4096, 256 * j + 64 * threadIdx.x, mt * 128 + 32 * sp);
        else tma_store_2d(&p.out5, own + 65536 + (sp & 1) * 2048, 512 + 32 * j, mt * 128 + 32 * sp);
        asm volatile("cp.async.bulk.commit_group;" ::: "memory");
        asm volatile("cp.async.bulk.wait_group.read 0;" ::: "memory");
      }
      PROF_T(46); PROF_G(7);
      PROF_DUMP();
    } else {
#pragma unroll 1
      for (int grp = 0; grp < 4; grp++) {
        kexpand<256>(sb, sb + SM_RING + grp * 5120, sb + SM_RING + grp * 5120 + 1280, sb + SM_KD + 8 * grp, threadIdx.x, __ldg((const uint4*)g_ktab.e + threadIdx.x));
        named_bar(3, 256);
        mbar_wait(bar + B_CV, grp & 1);
        conv2(sb, wg, w, lane, 512 + ((int)vb - 128) * 16 + grp * 4 + 2 * wg, C_Y5);
        if (t == 0) mbar_arrive(bar + B_SG);
        named_bar(3, 256);
      }
      PROF_T(46);
      PROF_DUMP();
    }
  }
}

typedef CUresult (*PFN_enc)(CUtensorMap*, CUtensorMapDataType, cuuint32_t, void*, const cuuint64_t*, const cuuint64_t*, const cuuint32_t*,
                            const cuuint32_t*, CUtensorMapInterleave, CUtensorMapSwizzle, CUtensorMapL2promotion, CUtensorMapFloatOOBfill);

void enc(PFN_enc fn, CUtensorMap* m, void* ptr, int rank, const cuuint64_t* dims, const cuuint64_t* strides, const cuuint32_t* box, CUtensorMapSwizzle sw) {
  cuuint32_t es[5] = {1, 1, 1, 1, 1};
  fn(m, CU_TENSOR_MAP_DATA_TYPE_BFLOAT16, rank, ptr, dims, strides, box, es, CU_TENSOR_MAP_INTERLEAVE_NONE, sw,
     CU_TENSOR_MAP_L2_PROMOTION_L2_128B, CU_TENSOR_MAP_FLOAT_OOB_FILL_NONE);
}

}

extern "C" void kernel_launch(void* const* d_in, const int* in_sizes, int n_in, void* d_out, int out_size) {
  static Params pr;
  static void* key[5] = {nullptr, nullptr, nullptr, nullptr, nullptr};
  if (key[0] != d_in[8] || key[1] != d_in[9] || key[2] != d_in[10] || key[3] != d_in[0] || key[4] != d_out) {
    key[0] = d_in[8]; key[1] = d_in[9]; key[2] = d_in[10]; key[3] = d_in[0]; key[4] = d_out;
    void* fnp = nullptr; cudaDriverEntryPointQueryResult st;
    cudaGetDriverEntryPoint("cuTensorMapEncodeTiled", &fnp, cudaEnableDefault, &st);
    PFN_enc fn = (PFN_enc)fnp;
    void *p_xn, *p_y;
    cudaGetSymbolAddress(&p_xn, g_xn); cudaGetSymbolAddress(&p_y, g_y);
    { cuuint64_t d[2] = {D_, L_}, s[1] = {D_ * 2};
      { cuuint32_t b[2] = {64, 128}; enc(fn, &pr.xn, p_xn, 2, d, s, b, CU_TENSOR_MAP_SWIZZLE_128B); }
      { cuuint32_t b[2] = {64, 32}; enc(fn, &pr.x, d_in[0], 2, d, s, b, CU_TENSOR_MAP_SWIZZLE_128B); enc(fn, &pr.out, d_out, 2, d, s, b, CU_TENSOR_MAP_SWIZZLE_128B); }
      { cuuint32_t b[2] = {32, 32}; enc(fn, &pr.x5, d_in[0], 2, d, s, b, CU_TENSOR_MAP_SWIZZLE_64B); enc(fn, &pr.out5, d_out, 2, d, s, b, CU_TENSOR_MAP_SWIZZLE_64B); } }
    { cuuint64_t d[2] = {F_, D_}, s[1] = {F_ * 2}; cuuint32_t b[2] = {64, 32};
      enc(fn, &pr.gate, d_in[8], 2, d, s, b, CU_TENSOR_MAP_SWIZZLE_128B); enc(fn, &pr.up, d_in[9], 2, d, s, b, CU_TENSOR_MAP_SWIZZLE_128B); }
    { void* wd = d_in[10];
      { cuuint64_t d[3] = {64, F_, 9}, s[2] = {D_ * 2, 128}; cuuint32_t b[3] = {64, 16, 4}; enc(fn, &pr.dn, wd, 3, d, s, b, CU_TENSOR_MAP_SWIZZLE_128B); }
      { cuuint64_t d[2] = {D_, F_}, s[1] = {D_ * 2}; cuuint32_t b[2] = {32, 16}; enc(fn, &pr.dn5, wd, 2, d, s, b, CU_TENSOR_MAP_SWIZZLE_64B); }
      { cuuint64_t d[5] = {64, 2, F_ / 8, 4, 9}, s[4] = {D_ * 2, D_ * 16, D_ * 4, 128}; cuuint32_t b[5] = {64, 2, 4, 2, 4};
        enc(fn, &pr.dp, wd, 5, d, s, b, CU_TENSOR_MAP_SWIZZLE_128B); }
      { cuuint64_t d[4] = {D_, 2, F_ / 8, 4}, s[3] = {D_ * 2, D_ * 16, D_ * 4}; cuuint32_t b[4] = {32, 2, 4, 2};
        enc(fn, &pr.dp5, wd, 4, d, s, b, CU_TENSOR_MAP_SWIZZLE_64B); }
    }
    { cuuint64_t d[2] = {L_, D_}, s[1] = {L_ * 2};
      { cuuint32_t b[2] = {32, 256}; enc(fn, &pr.y, p_y, 2, d, s, b, CU_TENSOR_MAP_SWIZZLE_64B); }
      { cuuint32_t b[2] = {32, 32}; enc(fn, &pr.y5, p_y, 2, d, s, b, CU_TENSOR_MAP_SWIZZLE_64B); } }
    cudaFuncSetAttribute(fused_kernel, cudaFuncAttributeMaxDynamicSharedMemorySize, SMEM_BYTES);
  }
  const __nv_bfloat16* const* in = (const __nv_bfloat16* const*)d_in;
  pr.xp = in[0]; pr.logA = in[1]; pr.Aim = in[2]; pr.Cre = in[3]; pr.Cim = in[4]; pr.logdt = in[5]; pr.Dsk = in[6];
  fused_kernel<<<132, 384, SMEM_BYTES>>>(pr);
}
```

```cpp
#include <cuda_runtime.h>
#include <cuda_bf16.h>
#include <cuda.h>
#include <stdint.h>
#include <stdio.h>
#include <type_traits>
#define CV_BASEOFF 0

namespace {

constexpr int L_ = 2048, D_ = 576, F_ = 4608, NM_ = 128;
constexpr int KP_LEN = 2080;
constexpr int U_LEN = 2176;

__device__ __align__(1024) __nv_bfloat16 g_xn[L_ * D_];
__device__ __align__(1024) __nv_bfloat16 g_u[D_ * U_LEN];
__device__ __align__(1024) unsigned char g_part[32 * 16 * 18432];
__device__ __align__(1024) __nv_bfloat16 g_y[D_ * L_];
__device__ __align__(1024) unsigned int g_cnt[64 * 32];
constexpr int C_LN = 0, C_PART = 16, C_U = 48, C_Y = 49, C_Y5 = 57, C_DONE = 58;

#define PROF_T(idx) do {} while (0)
#define PROF_G(idx) do {} while (0)
#define PROF_DUMP() do {} while (0)
__device__ __forceinline__ uint32_t smem_u32(const void* p) { return (uint32_t)__cvta_generic_to_shared(p); }
__device__ __forceinline__ void mbar_init(uint32_t bar, uint32_t cnt) { asm volatile("mbarrier.init.shared::cta.b64 [%0], %1;" ::"r"(bar), "r"(cnt)); }
__device__ __forceinline__ void mbar_expect_tx(uint32_t bar, uint32_t bytes) { asm volatile("mbarrier.arrive.expect_tx.shared::cta.b64 _, [%0], %1;" ::"r"(bar), "r"(bytes) : "memory"); }
__device__ __forceinline__ void mbar_arrive(uint32_t bar) { asm volatile("mbarrier.arrive.shared::cta.b64 _, [%0];" ::"r"(bar) : "memory"); }
__device__ __forceinline__ void mbar_arrive_remote(uint32_t bar) { asm volatile("mbarrier.arrive.shared::cluster.b64 _, [%0];" ::"r"(bar) : "memory"); }
__device__ __forceinline__ bool mbar_try_wait(uint32_t bar, uint32_t parity) {
  uint32_t ok;
  asm volatile("{\n.reg .pred p;\nmbarrier.try_wait.parity.shared::cta.b64 p, [%1], %2;\nselp.u32 %0, 1, 0, p;\n}" : "=r"(ok) : "r"(bar), "r"(parity) : "memory");
  return ok;
}
__device__ __forceinline__ bool mbar_test(uint32_t bar, uint32_t parity) {
  uint32_t ok;
  asm volatile("{\n.reg .pred p;\nmbarrier.test_wait.parity.shared::cta.b64 p, [%1], %2;\nselp.u32 %0, 1, 0, p;\n}" : "=r"(ok) : "r"(bar), "r"(parity) : "memory");
  return ok;
}
__device__ __forceinline__ void mbar_wait(uint32_t bar, uint32_t parity) {
  asm volatile("{\n.reg .pred p, q;\n.reg .u32 n;\nmov.u32 n, 0;\nLW:\nmbarrier.try_wait.parity.shared::cta.b64 p, [%0], %1;\n"
               "add.u32 n, n, 1;\nsetp.lt.and.u32 q, n, 65536, !p;\n@q bra LW;\n}" ::"r"(bar), "r"(parity) : "memory");
}
__device__ __forceinline__ void mbar_spin(uint32_t bar, uint32_t parity) {
  asm volatile("{\n.reg .pred p, q;\n.reg .u32 n;\nmov.u32 n, 0;\nLW:\nmbarrier.test_wait.parity.shared::cta.b64 p, [%0], %1;\n"
               "add.u32 n, n, 1;\nsetp.lt.and.u32 q, n, 4194304, !p;\n@q bra LW;\n}" ::"r"(bar), "r"(parity) : "memory");
}
__device__ __forceinline__ bool elect_one() {
  uint32_t ok;
  asm volatile("{\n.reg .pred p;\nelect.sync _|p, 0xffffffff;\nselp.u32 %0, 1, 0, p;\n}" : "=r"(ok));
  return ok;
}
__device__ __forceinline__ void tma_2d(uint32_t dst, const CUtensorMap* map, int c0, int c1, uint32_t bar) {
  asm volatile("cp.async.bulk.tensor.2d.shared::cluster.global.mbarrier::complete_tx::bytes [%0], [%1, {%3, %4}], [%2];"
               ::"r"(dst), "l"(map), "r"(bar), "r"(c0), "r"(c1) : "memory");
}
__device__ __forceinline__ void tma_3d(uint32_t dst, const CUtensorMap* map, int c0, int c1, int c2, uint32_t bar) {
  asm volatile("cp.async.bulk.tensor.3d.shared::cluster.global.mbarrier::complete_tx::bytes [%0], [%1, {%3, %4, %5}], [%2];"
               ::"r"(dst), "l"(map), "r"(bar), "r"(c0), "r"(c1), "r"(c2) : "memory");
}
__device__ __forceinline__ void tma_4d(uint32_t dst, const CUtensorMap* map, int c0, int c1, int c2, int c3, uint32_t bar) {
  asm volatile("cp.async.bulk.tensor.4d.shared::cluster.global.mbarrier::complete_tx::bytes [%0], [%1, {%3, %4, %5, %6}], [%2];"
               ::"r"(dst), "l"(map), "r"(bar), "r"(c0), "r"(c1), "r"(c2), "r"(c3) : "memory");
}
__device__ __forceinline__ void tma_5d(uint32_t dst, const CUtensorMap* map, int c0, int c1, int c2, int c3, int c4, uint32_t bar) {
  asm volatile("cp.async.bulk.tensor.5d.shared::cluster.global.mbarrier::complete_tx::bytes [%0], [%1, {%3, %4, %5, %6, %7}], [%2];"
               ::"r"(dst), "l"(map), "r"(bar), "r"(c0), "r"(c1), "r"(c2), "r"(c3), "r"(c4) : "memory");
}
__device__ __forceinline__ void tma_store_3d(const CUtensorMap* map, uint32_t src, int c0, int c1, int c2) {
  asm volatile("cp.async.bulk.tensor.3d.global.shared::cta.bulk_group [%0, {%2, %3, %4}], [%1];"
               ::"l"(map), "r"(src), "r"(c0), "r"(c1), "r"(c2) : "memory");
}
__device__ __forceinline__ void bulk_g2s(uint32_t dst, const void* src, uint32_t bytes, uint32_t bar) {
  asm volatile("cp.async.bulk.shared::cluster.global.mbarrier::complete_tx::bytes [%0], [%1], %2, [%3];"
               ::"r"(dst), "l"(src), "r"(bytes), "r"(bar) : "memory");
}
__device__ __forceinline__ void prefetch_map(const CUtensorMap* m) { asm volatile("prefetch.tensormap [%0];" ::"l"(m) : "memory"); }
__device__ __forceinline__ uint32_t mapa(uint32_t addr, uint32_t rank) { uint32_t r; asm volatile("mapa.shared::cluster.u32 %0, %1, %2;" : "=r"(r) : "r"(addr), "r"(rank)); return r; }
__device__ __forceinline__ void cluster_sync() { asm volatile("barrier.cluster.arrive.release.aligned;\nbarrier.cluster.wait.acquire.aligned;" ::: "memory"); }
__device__ __forceinline__ void fence_async_smem() { asm volatile("fence.proxy.async.shared::cta;" ::: "memory"); }
__device__ __forceinline__ void wg_fence() { asm volatile("wgmma.fence.sync.aligned;" ::: "memory"); }
__device__ __forceinline__ void wg_commit() { asm volatile("wgmma.commit_group.sync.aligned;" ::: "memory"); }
template <int N> __device__ __forceinline__ void wg_wait() { asm volatile("wgmma.wait_group.sync.aligned %0;" ::"n"(N) : "memory"); }
template <int N> __device__ __forceinline__ void reg_fence(float (&d)[N]) {
#pragma unroll
  for (int i = 0; i < N; i++) asm volatile("" : "+f"(d[i])::"memory");
}
__device__ __forceinline__ void named_bar(int id, int n) { asm volatile("bar.sync %0, %1;" ::"r"(id), "r"(n) : "memory"); }
__device__ __forceinline__ uint64_t mk_desc(uint32_t addr, uint32_t lbo, uint32_t sbo, uint32_t sw) {
  return (uint64_t)((addr & 0x3FFFF) >> 4) | ((uint64_t)(lbo >> 4) << 16) | ((uint64_t)(sbo >> 4) << 32) | ((uint64_t)sw << 62);
}
__device__ __forceinline__ uint32_t pack_bf16(float lo, float hi) {
  uint32_t r; asm("cvt.rn.bf16x2.f32 %0, %1, %2;" : "=r"(r) : "f"(hi), "f"(lo)); return r;
}
__device__ __forceinline__ float bf_lo(uint32_t v) { return __uint_as_float(v << 16); }
__device__ __forceinline__ float bf_hi(uint32_t v) { return __uint_as_float(v & 0xffff0000u); }
__device__ __forceinline__ float bf_round(float x) { return __bfloat162float(__float2bfloat16_rn(x)); }
__device__ __forceinline__ void st_async_v4(uint32_t addr, uint32_t a, uint32_t b, uint32_t c, uint32_t d, uint32_t bar) {
  asm volatile("st.async.weak.shared::cluster.mbarrier::complete_tx::bytes.v4.b32 [%0], {%1, %2, %3, %4}, [%5];"
               ::"r"(addr), "r"(a), "r"(b), "r"(c), "r"(d), "r"(bar) : "memory");
}
__device__ __forceinline__ void stmatrix_x4_t(uint32_t addr, uint32_t a, uint32_t b, uint32_t c, uint32_t d) {
  asm volatile("stmatrix.sync.aligned.m8n8.x4.trans.shared.b16 [%0], {%1, %2, %3, %4};" ::"r"(addr), "r"(a), "r"(b), "r"(c), "r"(d) : "memory");
}
__device__ __forceinline__ void ldmatrix_x4_t(uint32_t addr, uint32_t& a, uint32_t& b, uint32_t& c, uint32_t& d) {
  asm volatile("ldmatrix.sync.aligned.m8n8.x4.trans.shared.b16 {%0, %1, %2, %3}, [%4];" : "=r"(a), "=r"(b), "=r"(c), "=r"(d) : "r"(addr) : "memory");
}
__device__ __forceinline__ uint32_t lds32(uint32_t addr) { uint32_t v; asm volatile("ld.shared.b32 %0, [%1];" : "=r"(v) : "r"(addr) : "memory"); return v; }
__device__ __forceinline__ float geglu(float g, float u) {
  float z = g * fmaf(g * g, 0.0356774081f, 0.7978845608f);
  float t; asm("tanh.approx.f32 %0, %1;" : "=f"(t) : "f"(z));
  return (g * u) * fmaf(t, 0.5f, 0.5f);
}

__device__ __forceinline__ uint4 lds128(uint32_t addr) { uint4 v; asm volatile("ld.shared.v4.b32 {%0,%1,%2,%3}, [%4];" : "=r"(v.x), "=r"(v.y), "=r"(v.z), "=r"(v.w) : "r"(addr) : "memory"); return v; }
__device__ __forceinline__ void sts32(uint32_t addr, uint32_t v) { asm volatile("st.shared.b32 [%0], %1;" ::"r"(addr), "r"(v) : "memory"); }
__device__ __forceinline__ void stmatrix_x4(uint32_t addr, uint32_t a, uint32_t b, uint32_t c, uint32_t d) {
  asm volatile("stmatrix.sync.aligned.m8n8.x4.shared.b16 [%0], {%1, %2, %3, %4};" ::"r"(addr), "r"(a), "r"(b), "r"(c), "r"(d) : "memory");
}
__device__ __forceinline__ void ldmatrix_x4(uint32_t addr, uint32_t (&r)[4]) {
  asm volatile("ldmatrix.sync.aligned.m8n8.x4.shared.b16 {%0, %1, %2, %3}, [%4];" : "=r"(r[0]), "=r"(r[1]), "=r"(r[2]), "=r"(r[3]) : "r"(addr) : "memory");
}
__device__ __forceinline__ void sts128(uint32_t addr, uint4 v) { asm volatile("st.shared.v4.b32 [%0], {%1,%2,%3,%4};" ::"r"(addr), "r"(v.x), "r"(v.y), "r"(v.z), "r"(v.w) : "memory"); }
__device__ __forceinline__ void bulk_s2g(void* dst, uint32_t src, uint32_t bytes) {
  asm volatile("cp.async.bulk.global.shared::cta.bulk_group [%0], [%1], %2;" ::"l"(dst), "r"(src), "r"(bytes) : "memory");
}
__device__ __forceinline__ void tma_store_2d(const CUtensorMap* map, uint32_t src, int c0, int c1) {
  asm volatile("cp.async.bulk.tensor.2d.global.shared::cta.bulk_group [%0, {%2, %3}], [%1];" ::"l"(map), "r"(src), "r"(c0), "r"(c1) : "memory");
}
__device__ __forceinline__ void bulk_commit_wait() {
  asm volatile("cp.async.bulk.commit_group;" ::: "memory");
  asm volatile("cp.async.bulk.wait_group 0;" ::: "memory");
}
__device__ __forceinline__ void named_arrive(int id, int n) { asm volatile("bar.arrive %0, %1;" ::"r"(id), "r"(n) : "memory"); }
__device__ __forceinline__ void fence_async_all() { asm volatile("fence.proxy.async.global;" ::: "memory"); }
__device__ __forceinline__ void cnt_add(int idx) {
  asm volatile("red.release.gpu.global.add.u32 [%0], 1;" ::"l"(g_cnt + idx * 32) : "memory");
}
__device__ __forceinline__ void cnt_add_done(int idx) {
  asm volatile("red.relaxed.gpu.global.add.u32 [%0], 1;" ::"l"(g_cnt + idx * 32) : "memory");
}
__device__ __forceinline__ void cnt_wait(int idx, uint32_t target) {
  const unsigned int* p = g_cnt + idx * 32;
#pragma unroll 1
  for (int it = 0; it < (1 << 18); it++) {
    uint32_t v; asm volatile("ld.acquire.gpu.global.u32 %0, [%1];" : "=r"(v) : "l"(p) : "memory");
    if (v >= target) break;
  }
}
__device__ __forceinline__ void prefetch_l2(const void* p, uint32_t bytes) { asm volatile("cp.async.bulk.prefetch.L2.global [%0], %1;" ::"l"(p), "r"(bytes) : "memory"); }

template <int TB>
__device__ __forceinline__ void wg_ss128_init(float (&d)[64], uint64_t da, uint64_t db) {
  asm volatile(
    "wgmma.mma_async.sync.aligned.m64n128k16.f32.bf16.bf16 {%0, %1, %2, %3, %4, %5, %6, %7, %8, %9, %10, %11, %12, %13, %14, %15, %16, %17, %18, %19, %20, %21, %22, %23, %24, %25, %26, %27, %28, %29, %30, %31, %32, %33, %34, %35, %36, %37, %38, %39, %40, %41, %42, %43, %44, %45, %46, %47, %48, %49, %50, %51, %52, %53, %54, %55, %56, %57, %58, %59, %60, %61, %62, %63}, %64, %65, 0, 1, 1, 0, %66;"
    : "=f"(d[0]), "=f"(d[1]), "=f"(d[2]), "=f"(d[3]), "=f"(d[4]), "=f"(d[5]), "=f"(d[6]), "=f"(d[7]), "=f"(d[8]), "=f"(d[9]), "=f"(d[10]), "=f"(d[11]), "=f"(d[12]), "=f"(d[13]), "=f"(d[14]), "=f"(d[15]), "=f"(d[16]), "=f"(d[17]), "=f"(d[18]), "=f"(d[19]), "=f"(d[20]), "=f"(d[21]), "=f"(d[22]), "=f"(d[23]), "=f"(d[24]), "=f"(d[25]), "=f"(d[26]), "=f"(d[27]), "=f"(d[28]), "=f"(d[29]), "=f"(d[30]), "=f"(d[31]), "=f"(d[32]), "=f"(d[33]), "=f"(d[34]), "=f"(d[35]), "=f"(d[36]), "=f"(d[37]), "=f"(d[38]), "=f"(d[39]), "=f"(d[40]), "=f"(d[41]), "=f"(d[42]), "=f"(d[43]), "=f"(d[44]), "=f"(d[45]), "=f"(d[46]), "=f"(d[47]), "=f"(d[48]), "=f"(d[49]), "=f"(d[50]), "=f"(d[51]), "=f"(d[52]), "=f"(d[53]), "=f"(d[54]), "=f"(d[55]), "=f"(d[56]), "=f"(d[57]), "=f"(d[58]), "=f"(d[59]), "=f"(d[60]), "=f"(d[61]), "=f"(d[62]), "=f"(d[63])
    : "l"(da), "l"(db), "n"(TB));
}
template <int TB>
__device__ __forceinline__ void wg_ss128(float (&d)[64], uint64_t da, uint64_t db) {
  asm volatile(
    "wgmma.mma_async.sync.aligned.m64n128k16.f32.bf16.bf16 {%0, %1, %2, %3, %4, %5, %6, %7, %8, %9, %10, %11, %12, %13, %14, %15, %16, %17, %18, %19, %20, %21, %22, %23, %24, %25, %26, %27, %28, %29, %30, %31, %32, %33, %34, %35, %36, %37, %38, %39, %40, %41, %42, %43, %44, %45, %46, %47, %48, %49, %50, %51, %52, %53, %54, %55, %56, %57, %58, %59, %60, %61, %62, %63}, %64, %65, 1, 1, 1, 0, %66;"
    : "+f"(d[0]), "+f"(d[1]), "+f"(d[2]), "+f"(d[3]), "+f"(d[4]), "+f"(d[5]), "+f"(d[6]), "+f"(d[7]), "+f"(d[8]), "+f"(d[9]), "+f"(d[10]), "+f"(d[11]), "+f"(d[12]), "+f"(d[13]), "+f"(d[14]), "+f"(d[15]), "+f"(d[16]), "+f"(d[17]), "+f"(d[18]), "+f"(d[19]), "+f"(d[20]), "+f"(d[21]), "+f"(d[22]), "+f"(d[23]), "+f"(d[24]), "+f"(d[25]), "+f"(d[26]), "+f"(d[27]), "+f"(d[28]), "+f"(d[29]), "+f"(d[30]), "+f"(d[31]), "+f"(d[32]), "+f"(d[33]), "+f"(d[34]), "+f"(d[35]), "+f"(d[36]), "+f"(d[37]), "+f"(d[38]), "+f"(d[39]), "+f"(d[40]), "+f"(d[41]), "+f"(d[42]), "+f"(d[43]), "+f"(d[44]), "+f"(d[45]), "+f"(d[46]), "+f"(d[47]), "+f"(d[48]), "+f"(d[49]), "+f"(d[50]), "+f"(d[51]), "+f"(d[52]), "+f"(d[53]), "+f"(d[54]), "+f"(d[55]), "+f"(d[56]), "+f"(d[57]), "+f"(d[58]), "+f"(d[59]), "+f"(d[60]), "+f"(d[61]), "+f"(d[62]), "+f"(d[63])
    : "l"(da), "l"(db), "n"(TB));
}
template <int TB>
__device__ __forceinline__ void wg_ss256(float (&d)[128], uint64_t da, uint64_t db) {
  asm volatile(
    "wgmma.mma_async.sync.aligned.m64n256k16.f32.bf16.bf16 {%0, %1, %2, %3, %4, %5, %6, %7, %8, %9, %10, %11, %12, %13, %14, %15, %16, %17, %18, %19, %20, %21, %22, %23, %24, %25, %26, %27, %28, %29, %30, %31, %32, %33, %34, %35, %36, %37, %38, %39, %40, %41, %42, %43, %44, %45, %46, %47, %48, %49, %50, %51, %52, %53, %54, %55, %56, %57, %58, %59, %60, %61, %62, %63, %64, %65, %66, %67, %68, %69, %70, %71, %72, %73, %74, %75, %76, %77, %78, %79, %80, %81, %82, %83, %84, %85, %86, %87, %88, %89, %90, %91, %92, %93, %94, %95, %96, %97, %98, %99, %100, %101, %102, %103, %104, %105, %106, %107, %108, %109, %110, %111, %112, %113, %114, %115, %116, %117, %118, %119, %120, %121, %122, %123, %124, %125, %126, %127}, %128, %129, 1, 1, 1, 0, %130;"
    : "+f"(d[0]), "+f"(d[1]), "+f"(d[2]), "+f"(d[3]), "+f"(d[4]), "+f"(d[5]), "+f"(d[6]), "+f"(d[7]), "+f"(d[8]), "+f"(d[9]), "+f"(d[10]), "+f"(d[11]), "+f"(d[12]), "+f"(d[13]), "+f"(d[14]), "+f"(d[15]), "+f"(d[16]), "+f"(d[17]), "+f"(d[18]), "+f"(d[19]), "+f"(d[20]), "+f"(d[21]), "+f"(d[22]), "+f"(d[23]), "+f"(d[24]), "+f"(d[25]), "+f"(d[26]), "+f"(d[27]), "+f"(d[28]), "+f"(d[29]), "+f"(d[30]), "+f"(d[31]), "+f"(d[32]), "+f"(d[33]), "+f"(d[34]), "+f"(d[35]), "+f"(d[36]), "+f"(d[37]), "+f"(d[38]), "+f"(d[39]), "+f"(d[40]), "+f"(d[41]), "+f"(d[42]), "+f"(d[43]), "+f"(d[44]), "+f"(d[45]), "+f"(d[46]), "+f"(d[47]), "+f"(d[48]), "+f"(d[49]), "+f"(d[50]), "+f"(d[51]), "+f"(d[52]), "+f"(d[53]), "+f"(d[54]), "+f"(d[55]), "+f"(d[56]), "+f"(d[57]), "+f"(d[58]), "+f"(d[59]), "+f"(d[60]), "+f"(d[61]), "+f"(d[62]), "+f"(d[63]), "+f"(d[64]), "+f"(d[65]), "+f"(d[66]), "+f"(d[67]), "+f"(d[68]), "+f"(d[69]), "+f"(d[70]), "+f"(d[71]), "+f"(d[72]), "+f"(d[73]), "+f"(d[74]), "+f"(d[75]), "+f"(d[76]), "+f"(d[77]), "+f"(d[78]), "+f"(d[79]), "+f"(d[80]), "+f"(d[81]), "+f"(d[82]), "+f"(d[83]), "+f"(d[84]), "+f"(d[85]), "+f"(d[86]), "+f"(d[87]), "+f"(d[88]), "+f"(d[89]), "+f"(d[90]), "+f"(d[91]), "+f"(d[92]), "+f"(d[93]), "+f"(d[94]), "+f"(d[95]), "+f"(d[96]), "+f"(d[97]), "+f"(d[98]), "+f"(d[99]), "+f"(d[100]), "+f"(d[101]), "+f"(d[102]), "+f"(d[103]), "+f"(d[104]), "+f"(d[105]), "+f"(d[106]), "+f"(d[107]), "+f"(d[108]), "+f"(d[109]), "+f"(d[110]), "+f"(d[111]), "+f"(d[112]), "+f"(d[113]), "+f"(d[114]), "+f"(d[115]), "+f"(d[116]), "+f"(d[117]), "+f"(d[118]), "+f"(d[119]), "+f"(d[120]), "+f"(d[121]), "+f"(d[122]), "+f"(d[123]), "+f"(d[124]), "+f"(d[125]), "+f"(d[126]), "+f"(d[127])
    : "l"(da), "l"(db), "n"(TB));
}
template <int TB>
__device__ __forceinline__ void wg_ss32(float (&d)[16], uint64_t da, uint64_t db) {
  asm volatile(
    "wgmma.mma_async.sync.aligned.m64n32k16.f32.bf16.bf16 {%0, %1, %2, %3, %4, %5, %6, %7, %8, %9, %10, %11, %12, %13, %14, %15}, %16, %17, 1, 1, 1, 0, %18;"
    : "+f"(d[0]), "+f"(d[1]), "+f"(d[2]), "+f"(d[3]), "+f"(d[4]), "+f"(d[5]), "+f"(d[6]), "+f"(d[7]), "+f"(d[8]), "+f"(d[9]), "+f"(d[10]), "+f"(d[11]), "+f"(d[12]), "+f"(d[13]), "+f"(d[14]), "+f"(d[15])
    : "l"(da), "l"(db), "n"(TB));
}
template <int TB>
__device__ __forceinline__ void wg_rs256(float (&d)[128], uint32_t a0, uint32_t a1, uint32_t a2, uint32_t a3, uint64_t db) {
  asm volatile(
    "wgmma.mma_async.sync.aligned.m64n256k16.f32.bf16.bf16 {%0, %1, %2, %3, %4, %5, %6, %7, %8, %9, %10, %11, %12, %13, %14, %15, %16, %17, %18, %19, %20, %21, %22, %23, %24, %25, %26, %27, %28, %29, %30, %31, %32, %33, %34, %35, %36, %37, %38, %39, %40, %41, %42, %43, %44, %45, %46, %47, %48, %49, %50, %51, %52, %53, %54, %55, %56, %57, %58, %59, %60, %61, %62, %63, %64, %65, %66, %67, %68, %69, %70, %71, %72, %73, %74, %75, %76, %77, %78, %79, %80, %81, %82, %83, %84, %85, %86, %87, %88, %89, %90, %91, %92, %93, %94, %95, %96, %97, %98, %99, %100, %101, %102, %103, %104, %105, %106, %107, %108, %109, %110, %111, %112, %113, %114, %115, %116, %117, %118, %119, %120, %121, %122, %123, %124, %125, %126, %127}, {%128, %129, %130, %131}, %132, 1, 1, 1, %133;"
    : "+f"(d[0]), "+f"(d[1]), "+f"(d[2]), "+f"(d[3]), "+f"(d[4]), "+f"(d[5]), "+f"(d[6]), "+f"(d[7]), "+f"(d[8]), "+f"(d[9]), "+f"(d[10]), "+f"(d[11]), "+f"(d[12]), "+f"(d[13]), "+f"(d[14]), "+f"(d[15]), "+f"(d[16]), "+f"(d[17]), "+f"(d[18]), "+f"(d[19]), "+f"(d[20]), "+f"(d[21]), "+f"(d[22]), "+f"(d[23]), "+f"(d[24]), "+f"(d[25]), "+f"(d[26]), "+f"(d[27]), "+f"(d[28]), "+f"(d[29]), "+f"(d[30]), "+f"(d[31]), "+f"(d[32]), "+f"(d[33]), "+f"(d[34]), "+f"(d[35]), "+f"(d[36]), "+f"(d[37]), "+f"(d[38]), "+f"(d[39]), "+f"(d[40]), "+f"(d[41]), "+f"(d[42]), "+f"(d[43]), "+f"(d[44]), "+f"(d[45]), "+f"(d[46]), "+f"(d[47]), "+f"(d[48]), "+f"(d[49]), "+f"(d[50]), "+f"(d[51]), "+f"(d[52]), "+f"(d[53]), "+f"(d[54]), "+f"(d[55]), "+f"(d[56]), "+f"(d[57]), "+f"(d[58]), "+f"(d[59]), "+f"(d[60]), "+f"(d[61]), "+f"(d[62]), "+f"(d[63]), "+f"(d[64]), "+f"(d[65]), "+f"(d[66]), "+f"(d[67]), "+f"(d[68]), "+f"(d[69]), "+f"(d[70]), "+f"(d[71]), "+f"(d[72]), "+f"(d[73]), "+f"(d[74]), "+f"(d[75]), "+f"(d[76]), "+f"(d[77]), "+f"(d[78]), "+f"(d[79]), "+f"(d[80]), "+f"(d[81]), "+f"(d[82]), "+f"(d[83]), "+f"(d[84]), "+f"(d[85]), "+f"(d[86]), "+f"(d[87]), "+f"(d[88]), "+f"(d[89]), "+f"(d[90]), "+f"(d[91]), "+f"(d[92]), "+f"(d[93]), "+f"(d[94]), "+f"(d[95]), "+f"(d[96]), "+f"(d[97]), "+f"(d[98]), "+f"(d[99]), "+f"(d[100]), "+f"(d[101]), "+f"(d[102]), "+f"(d[103]), "+f"(d[104]), "+f"(d[105]), "+f"(d[106]), "+f"(d[107]), "+f"(d[108]), "+f"(d[109]), "+f"(d[110]), "+f"(d[111]), "+f"(d[112]), "+f"(d[113]), "+f"(d[114]), "+f"(d[115]), "+f"(d[116]), "+f"(d[117]), "+f"(d[118]), "+f"(d[119]), "+f"(d[120]), "+f"(d[121]), "+f"(d[122]), "+f"(d[123]), "+f"(d[124]), "+f"(d[125]), "+f"(d[126]), "+f"(d[127])
    : "r"(a0), "r"(a1), "r"(a2), "r"(a3), "l"(db), "n"(TB));
}
template <int TB>
__device__ __forceinline__ void wg_rs32(float (&d)[16], uint32_t a0, uint32_t a1, uint32_t a2, uint32_t a3, uint64_t db) {
  asm volatile(
    "wgmma.mma_async.sync.aligned.m64n32k16.f32.bf16.bf16 {%0, %1, %2, %3, %4, %5, %6, %7, %8, %9, %10, %11, %12, %13, %14, %15}, {%16, %17, %18, %19}, %20, 1, 1, 1, %21;"
    : "+f"(d[0]), "+f"(d[1]), "+f"(d[2]), "+f"(d[3]), "+f"(d[4]), "+f"(d[5]), "+f"(d[6]), "+f"(d[7]), "+f"(d[8]), "+f"(d[9]), "+f"(d[10]), "+f"(d[11]), "+f"(d[12]), "+f"(d[13]), "+f"(d[14]), "+f"(d[15])
    : "r"(a0), "r"(a1), "r"(a2), "r"(a3), "l"(db), "n"(TB));
}
template <int TB>
__device__ __forceinline__ void wg_cv128(float (&d)[64], uint32_t a0, uint32_t a1, uint32_t a2, uint32_t a3, uint64_t db) {
  asm volatile(
    "wgmma.mma_async.sync.aligned.m64n128k16.f32.bf16.bf16 {%0, %1, %2, %3, %4, %5, %6, %7, %8, %9, %10, %11, %12, %13, %14, %15, %16, %17, %18, %19, %20, %21, %22, %23, %24, %25, %26, %27, %28, %29, %30, %31, %32, %33, %34, %35, %36, %37, %38, %39, %40, %41, %42, %43, %44, %45, %46, %47, %48, %49, %50, %51, %52, %53, %54, %55, %56, %57, %58, %59, %60, %61, %62, %63}, {%64, %65, %66, %67}, %68, 1, 1, 1, %69;"
    : "+f"(d[0]), "+f"(d[1]), "+f"(d[2]), "+f"(d[3]), "+f"(d[4]), "+f"(d[5]), "+f"(d[6]), "+f"(d[7]), "+f"(d[8]), "+f"(d[9]), "+f"(d[10]), "+f"(d[11]), "+f"(d[12]), "+f"(d[13]), "+f"(d[14]), "+f"(d[15]), "+f"(d[16]), "+f"(d[17]), "+f"(d[18]), "+f"(d[19]), "+f"(d[20]), "+f"(d[21]), "+f"(d[22]), "+f"(d[23]), "+f"(d[24]), "+f"(d[25]), "+f"(d[26]), "+f"(d[27]), "+f"(d[28]), "+f"(d[29]), "+f"(d[30]), "+f"(d[31]), "+f"(d[32]), "+f"(d[33]), "+f"(d[34]), "+f"(d[35]), "+f"(d[36]), "+f"(d[37]), "+f"(d[38]), "+f"(d[39]), "+f"(d[40]), "+f"(d[41]), "+f"(d[42]), "+f"(d[43]), "+f"(d[44]), "+f"(d[45]), "+f"(d[46]), "+f"(d[47]), "+f"(d[48]), "+f"(d[49]), "+f"(d[50]), "+f"(d[51]), "+f"(d[52]), "+f"(d[53]), "+f"(d[54]), "+f"(d[55]), "+f"(d[56]), "+f"(d[57]), "+f"(d[58]), "+f"(d[59]), "+f"(d[60]), "+f"(d[61]), "+f"(d[62]), "+f"(d[63])
    : "r"(a0), "r"(a1), "r"(a2), "r"(a3), "l"(db), "n"(TB));
}
template <int TB>
__device__ __forceinline__ void wg_cv96(float (&d)[48], uint32_t a0, uint32_t a1, uint32_t a2, uint32_t a3, uint64_t db) {
  asm volatile(
    "wgmma.mma_async.sync.aligned.m64n96k16.f32.bf16.bf16 {%0, %1, %2, %3, %4, %5, %6, %7, %8, %9, %10, %11, %12, %13, %14, %15, %16, %17, %18, %19, %20, %21, %22, %23, %24, %25, %26, %27, %28, %29, %30, %31, %32, %33, %34, %35, %36, %37, %38, %39, %40, %41, %42, %43, %44, %45, %46, %47}, {%48, %49, %50, %51}, %52, 1, 1, 1, %53;"
    : "+f"(d[0]), "+f"(d[1]), "+f"(d[2]), "+f"(d[3]), "+f"(d[4]), "+f"(d[5]), "+f"(d[6]), "+f"(d[7]), "+f"(d[8]), "+f"(d[9]), "+f"(d[10]), "+f"(d[11]), "+f"(d[12]), "+f"(d[13]), "+f"(d[14]), "+f"(d[15]), "+f"(d[16]), "+f"(d[17]), "+f"(d[18]), "+f"(d[19]), "+f"(d[20]), "+f"(d[21]), "+f"(d[22]), "+f"(d[23]), "+f"(d[24]), "+f"(d[25]), "+f"(d[26]), "+f"(d[27]), "+f"(d[28]), "+f"(d[29]), "+f"(d[30]), "+f"(d[31]), "+f"(d[32]), "+f"(d[33]), "+f"(d[34]), "+f"(d[35]), "+f"(d[36]), "+f"(d[37]), "+f"(d[38]), "+f"(d[39]), "+f"(d[40]), "+f"(d[41]), "+f"(d[42]), "+f"(d[43]), "+f"(d[44]), "+f"(d[45]), "+f"(d[46]), "+f"(d[47])
    : "r"(a0), "r"(a1), "r"(a2), "r"(a3), "l"(db), "n"(TB));
}
template <int TB>
__device__ __forceinline__ void wg_cv64(float (&d)[32], uint32_t a0, uint32_t a1, uint32_t a2, uint32_t a3, uint64_t db) {
  asm volatile(
    "wgmma.mma_async.sync.aligned.m64n64k16.f32.bf16.bf16 {%0, %1, %2, %3, %4, %5, %6, %7, %8, %9, %10, %11, %12, %13, %14, %15, %16, %17, %18, %19, %20, %21, %22, %23, %24, %25, %26, %27, %28, %29, %30, %31}, {%32, %33, %34, %35}, %36, 1, 1, 1, %37;"
    : "+f"(d[0]), "+f"(d[1]), "+f"(d[2]), "+f"(d[3]), "+f"(d[4]), "+f"(d[5]), "+f"(d[6]), "+f"(d[7]), "+f"(d[8]), "+f"(d[9]), "+f"(d[10]), "+f"(d[11]), "+f"(d[12]), "+f"(d[13]), "+f"(d[14]), "+f"(d[15]), "+f"(d[16]), "+f"(d[17]), "+f"(d[18]), "+f"(d[19]), "+f"(d[20]), "+f"(d[21]), "+f"(d[22]), "+f"(d[23]), "+f"(d[24]), "+f"(d[25]), "+f"(d[26]), "+f"(d[27]), "+f"(d[28]), "+f"(d[29]), "+f"(d[30]), "+f"(d[31])
    : "r"(a0), "r"(a1), "r"(a2), "r"(a3), "l"(db), "n"(TB));
}
template <int TB>
__device__ __forceinline__ void wg_cv128_init(float (&d)[64], uint32_t a0, uint32_t a1, uint32_t a2, uint32_t a3, uint64_t db) {
  asm volatile(
    "wgmma.mma_async.sync.aligned.m64n128k16.f32.bf16.bf16 {%0, %1, %2, %3, %4, %5, %6, %7, %8, %9, %10, %11, %12, %13, %14, %15, %16, %17, %18, %19, %20, %21, %22, %23, %24, %25, %26, %27, %28, %29, %30, %31, %32, %33, %34, %35, %36, %37, %38, %39, %40, %41, %42, %43, %44, %45, %46, %47, %48, %49, %50, %51, %52, %53, %54, %55, %56, %57, %58, %59, %60, %61, %62, %63}, {%64, %65, %66, %67}, %68, 0, 1, 1, %69;"
    : "=f"(d[0]), "=f"(d[1]), "=f"(d[2]), "=f"(d[3]), "=f"(d[4]), "=f"(d[5]), "=f"(d[6]), "=f"(d[7]), "=f"(d[8]), "=f"(d[9]), "=f"(d[10]), "=f"(d[11]), "=f"(d[12]), "=f"(d[13]), "=f"(d[14]), "=f"(d[15]), "=f"(d[16]), "=f"(d[17]), "=f"(d[18]), "=f"(d[19]), "=f"(d[20]), "=f"(d[21]), "=f"(d[22]), "=f"(d[23]), "=f"(d[24]), "=f"(d[25]), "=f"(d[26]), "=f"(d[27]), "=f"(d[28]), "=f"(d[29]), "=f"(d[30]), "=f"(d[31]), "=f"(d[32]), "=f"(d[33]), "=f"(d[34]), "=f"(d[35]), "=f"(d[36]), "=f"(d[37]), "=f"(d[38]), "=f"(d[39]), "=f"(d[40]), "=f"(d[41]), "=f"(d[42]), "=f"(d[43]), "=f"(d[44]), "=f"(d[45]), "=f"(d[46]), "=f"(d[47]), "=f"(d[48]), "=f"(d[49]), "=f"(d[50]), "=f"(d[51]), "=f"(d[52]), "=f"(d[53]), "=f"(d[54]), "=f"(d[55]), "=f"(d[56]), "=f"(d[57]), "=f"(d[58]), "=f"(d[59]), "=f"(d[60]), "=f"(d[61]), "=f"(d[62]), "=f"(d[63])
    : "r"(a0), "r"(a1), "r"(a2), "r"(a3), "l"(db), "n"(TB));
}
template <int TB>
__device__ __forceinline__ void wg_rs256_init(float (&d)[128], uint32_t a0, uint32_t a1, uint32_t a2, uint32_t a3, uint64_t db) {
  asm volatile(
    "wgmma.mma_async.sync.aligned.m64n256k16.f32.bf16.bf16 {%0, %1, %2, %3, %4, %5, %6, %7, %8, %9, %10, %11, %12, %13, %14, %15, %16, %17, %18, %19, %20, %21, %22, %23, %24, %25, %26, %27, %28, %29, %30, %31, %32, %33, %34, %35, %36, %37, %38, %39, %40, %41, %42, %43, %44, %45, %46, %47, %48, %49, %50, %51, %52, %53, %54, %55, %56, %57, %58, %59, %60, %61, %62, %63, %64, %65, %66, %67, %68, %69, %70, %71, %72, %73, %74, %75, %76, %77, %78, %79, %80, %81, %82, %83, %84, %85, %86, %87, %88, %89, %90, %91, %92, %93, %94, %95, %96, %97, %98, %99, %100, %101, %102, %103, %104, %105, %106, %107, %108, %109, %110, %111, %112, %113, %114, %115, %116, %117, %118, %119, %120, %121, %122, %123, %124, %125, %126, %127}, {%128, %129, %130, %131}, %132, 0, 1, 1, %133;"
    : "=f"(d[0]), "=f"(d[1]), "=f"(d[2]), "=f"(d[3]), "=f"(d[4]), "=f"(d[5]), "=f"(d[6]), "=f"(d[7]), "=f"(d[8]), "=f"(d[9]), "=f"(d[10]), "=f"(d[11]), "=f"(d[12]), "=f"(d[13]), "=f"(d[14]), "=f"(d[15]), "=f"(d[16]), "=f"(d[17]), "=f"(d[18]), "=f"(d[19]), "=f"(d[20]), "=f"(d[21]), "=f"(d[22]), "=f"(d[23]), "=f"(d[24]), "=f"(d[25]), "=f"(d[26]), "=f"(d[27]), "=f"(d[28]), "=f"(d[29]), "=f"(d[30]), "=f"(d[31]), "=f"(d[32]), "=f"(d[33]), "=f"(d[34]), "=f"(d[35]), "=f"(d[36]), "=f"(d[37]), "=f"(d[38]), "=f"(d[39]), "=f"(d[40]), "=f"(d[41]), "=f"(d[42]), "=f"(d[43]), "=f"(d[44]), "=f"(d[45]), "=f"(d[46]), "=f"(d[47]), "=f"(d[48]), "=f"(d[49]), "=f"(d[50]), "=f"(d[51]), "=f"(d[52]), "=f"(d[53]), "=f"(d[54]), "=f"(d[55]), "=f"(d[56]), "=f"(d[57]), "=f"(d[58]), "=f"(d[59]), "=f"(d[60]), "=f"(d[61]), "=f"(d[62]), "=f"(d[63]), "=f"(d[64]), "=f"(d[65]), "=f"(d[66]), "=f"(d[67]), "=f"(d[68]), "=f"(d[69]), "=f"(d[70]), "=f"(d[71]), "=f"(d[72]), "=f"(d[73]), "=f"(d[74]), "=f"(d[75]), "=f"(d[76]), "=f"(d[77]), "=f"(d[78]), "=f"(d[79]), "=f"(d[80]), "=f"(d[81]), "=f"(d[82]), "=f"(d[83]), "=f"(d[84]), "=f"(d[85]), "=f"(d[86]), "=f"(d[87]), "=f"(d[88]), "=f"(d[89]), "=f"(d[90]), "=f"(d[91]), "=f"(d[92]), "=f"(d[93]), "=f"(d[94]), "=f"(d[95]), "=f"(d[96]), "=f"(d[97]), "=f"(d[98]), "=f"(d[99]), "=f"(d[100]), "=f"(d[101]), "=f"(d[102]), "=f"(d[103]), "=f"(d[104]), "=f"(d[105]), "=f"(d[106]), "=f"(d[107]), "=f"(d[108]), "=f"(d[109]), "=f"(d[110]), "=f"(d[111]), "=f"(d[112]), "=f"(d[113]), "=f"(d[114]), "=f"(d[115]), "=f"(d[116]), "=f"(d[117]), "=f"(d[118]), "=f"(d[119]), "=f"(d[120]), "=f"(d[121]), "=f"(d[122]), "=f"(d[123]), "=f"(d[124]), "=f"(d[125]), "=f"(d[126]), "=f"(d[127])
    : "r"(a0), "r"(a1), "r"(a2), "r"(a3), "l"(db), "n"(TB));
}
template <int TB>
__device__ __forceinline__ void wg_rs32_init(float (&d)[16], uint32_t a0, uint32_t a1, uint32_t a2, uint32_t a3, uint64_t db) {
  asm volatile(
    "wgmma.mma_async.sync.aligned.m64n32k16.f32.bf16.bf16 {%0, %1, %2, %3, %4, %5, %6, %7, %8, %9, %10, %11, %12, %13, %14, %15}, {%16, %17, %18, %19}, %20, 0, 1, 1, %21;"
    : "=f"(d[0]), "=f"(d[1]), "=f"(d[2]), "=f"(d[3]), "=f"(d[4]), "=f"(d[5]), "=f"(d[6]), "=f"(d[7]), "=f"(d[8]), "=f"(d[9]), "=f"(d[10]), "=f"(d[11]), "=f"(d[12]), "=f"(d[13]), "=f"(d[14]), "=f"(d[15])
    : "r"(a0), "r"(a1), "r"(a2), "r"(a3), "l"(db), "n"(TB));
}

#define FULLW() mbar_wait(bar + B_FULL + 8 * slot, ph)
#define TEXPR cexp2(P.x * g128, P.w * g1)
#define RINGPOS 1
#define L2PROMO CU_TENSOR_MAP_L2_PROMOTION_L2_128B
#define EMPTYW() mbar_wait(bar + B_EMPTY + 8 * slot, ph)
constexpr int NST = 7, SLOT = 9216;
constexpr uint32_t SM_XN = 0, SM_HIN = 147456, SM_RING = 163840, SM_BAR = SM_RING + 7 * SLOT;
constexpr uint32_t SM_KD = SM_BAR + 256, SMEM_BYTES = SM_KD + 3840;
constexpr uint32_t B_FULL = 0, B_EMPTY = 56, B_XN = 112, B_K2048 = 176, B_HF = 184, B_HE = 200, B_CV = 216, B_PT = 224, B_YT = 232, B_SG = 240, B_X = 248;
constexpr uint32_t PR_LN = 65536, PR_PAR = 98304, PR_K0 = SM_HIN + 12288;
constexpr uint32_t T_U = 0, T_KP = 17408, T_K0 = 51200, T_X0 = 53248, T_X1 = SM_HIN + 4 * 18432, T_YT = 0, T_STG = 65536, T_PART = SM_HIN;
constexpr uint32_t U_BYTES = U_LEN * 2, KP_BYTES = KP_LEN * 4, IMG = 18432;

struct Params {
  CUtensorMap xn, gate, up, dn, dn5, dp, dp5, x, x5, y, y5, out, out5;
  unsigned char role[72];
  const __nv_bfloat16 *wd, *xp, *logA, *Aim, *Cre, *Cim, *logdt, *Dsk;
};

__device__ __forceinline__ float us2f(uint32_t v) { return __uint_as_float(v << 16); }
struct KgIn { uint32_t la, ai, cr, ci, ldt, dsk; };
__device__ __forceinline__ void kgen_load(const Params& p, int ch0, int tid, KgIn& in) {
  const int e = ch0 * (NM_ / 2) + tid;
  in.la = __ldg((const uint32_t*)p.logA + e); in.ai = __ldg((const uint32_t*)p.Aim + e);
  in.cr = __ldg((const uint32_t*)p.Cre + e); in.ci = __ldg((const uint32_t*)p.Cim + e);
  in.ldt = __ldg((const unsigned short*)p.logdt + ch0 + (tid >> 6)); in.dsk = __ldg((const unsigned short*)p.Dsk + ch0 + (tid >> 6));
}
struct KgState { float acc[5][4]; float v; };
struct cf { float r, i; };
__device__ __forceinline__ cf cmul(cf a, cf b) { return {fmaf(a.r, b.r, -(a.i * b.i)), fmaf(a.r, b.i, a.i * b.r)}; }
__device__ __forceinline__ cf csq(cf a) { return {fmaf(a.r, a.r, -(a.i * a.i)), (a.r + a.r) * a.i}; }
__device__ __forceinline__ cf cexp2(float lm, float th) {
  float m; asm("ex2.approx.ftz.f32 %0, %1;" : "=f"(m) : "f"(lm));
  return {m * __cosf(th), m * __sinf(th)};
}
__device__ __forceinline__ float turns(float w) { return (w - rintf(w)) * 6.283185307179586f; }
__device__ __forceinline__ void kgen_params(unsigned char* sm, int tid, KgIn in, KgState& st) {
  const int warp = tid >> 5, lane = tid & 31;
  float4* par = (float4*)(sm + PR_PAR + warp * 6144) + lane;
  const float dt = bf_round(expf(bf_lo(in.ldt)));
  float v = 0.f;
#pragma unroll 1
  for (int r = 0; r < 2; r++) {
    const float x = -bf_round(expf(bf_lo(in.la))) * dt * 1.4426950408889634f;
    const float w = bf_lo(in.ai) * dt * 0.15915494309189535f;
    const cf c = {2.f * bf_lo(in.cr) * dt, 2.f * bf_lo(in.ci) * dt};
    const cf e2 = cexp2(2.f * x, turns(2.f * w)), e64 = cexp2(64.f * x, turns(64.f * w));
    const cf e4 = csq(e2), e6 = cmul(e2, e4), e128 = csq(e64), e256 = csq(e128), e512 = csq(e256), e1024 = csq(e512);
    const cf c1 = cmul(c, e128), c256 = cmul(c, e256), c512 = cmul(c, e512), c4 = cmul(c, e1024);
    const cf c516 = cmul(c512, e4), c258 = cmul(c256, e2), c260 = cmul(c256, e4), c262 = cmul(c256, e6);
    v += fmaf(c4.r, e1024.r, -(c4.i * e1024.i));
    par[0] = make_float4(x, turns(w), turns(8.f * w), turns(128.f * w));
    par[64] = make_float4(c.r, c.i, c1.r, c1.i);
    par[128] = make_float4(c4.r, c4.i, e64.r, e64.i);
    par[192] = make_float4(c512.r, c512.i, c516.r, c516.i);
    par[256] = make_float4(c256.r, c256.i, c258.r, c258.i);
    par[320] = make_float4(c260.r, c260.i, c262.r, c262.i);
    par += 32;
    in.la >>= 16; in.ai >>= 16; in.cr >>= 16; in.ci >>= 16;
  }
#pragma unroll
  for (int o = 16; o; o >>= 1) v += __shfl_xor_sync(0xffffffffu, v, o);
  __syncwarp();
#pragma unroll
  for (int t = 0; t < 5; t++) { st.acc[t][0] = st.acc[t][1] = st.acc[t][2] = st.acc[t][3] = 0.f; }
  if (lane == 0 && !(warp & 1)) st.acc[0][0] = bf_lo(in.dsk);
  st.v = v;
}
__device__ __forceinline__ void kgen_steps(unsigned char* sm, int tid, KgState& st) {
  const int warp = tid >> 5, lane = tid & 31, g = lane >> 2, q = lane & 3;
  const float4* par = (const float4*)(sm + PR_PAR + warp * 6144) + q;
  const float2* p3 = (const float2*)(par + 192) + (g & 1);
  const float2* p2 = (const float2*)(par + 256 + 64 * ((g >> 1) & 1)) + (g & 1);
  const float g1 = (float)g, g8 = 8.f * g1, g128 = 128.f * g1;
  const int l1 = 4 * (g >> 1) + q, l2 = 4 * (g >> 2) + q;
#pragma unroll 4
  for (int ks = 0; ks < 16; ks++) {
    const float4 P = par[4 * ks], Q = par[64 + 4 * ks], R = par[128 + 4 * ks];
    const float2 c3 = p3[8 * ks], c2 = p2[8 * ks];
    const cf e = cexp2(P.x * g1, P.y * g1), a1 = cexp2(P.x * g8, P.z * g1), t = TEXPR;
    const cf a2 = cmul(a1, cf{R.z, R.w});
    const cf t1 = {__shfl_sync(0xffffffffu, t.r, l1), __shfl_sync(0xffffffffu, t.i, l1)};
    const cf t2 = {__shfl_sync(0xffffffffu, t.r, l2), __shfl_sync(0xffffffffu, t.i, l2)};
    auto mma = [&](float (&d)[4], cf u, float cr, float ci) {
      const float b0 = fmaf(u.r, cr, -(u.i * ci)), b1 = fmaf(-u.r, ci, -(u.i * cr));
      asm("mma.sync.aligned.m16n8k8.row.col.f32.tf32.tf32.f32 {%0,%1,%2,%3}, {%4,%5,%6,%7}, {%8,%9}, {%0,%1,%2,%3};"
          : "+f"(d[0]), "+f"(d[1]), "+f"(d[2]), "+f"(d[3])
          : "r"(__float_as_uint(a1.r)), "r"(__float_as_uint(a2.r)), "r"(__float_as_uint(a1.i)), "r"(__float_as_uint(a2.i)),
            "r"(__float_as_uint(b0)), "r"(__float_as_uint(b1)));
    };
    mma(st.acc[0], e, Q.x, Q.y);
    mma(st.acc[1], e, Q.z, Q.w);
    mma(st.acc[4], t, R.x, R.y);
    mma(st.acc[2], t2, c2.x, c2.y);
    mma(st.acc[3], t1, c3.x, c3.y);
  }
}
__device__ __forceinline__ void kgen_finish(unsigned char* sm, unsigned short* kd, unsigned short* k2048, int tid, KgState& st) {
  const int warp = tid >> 5, lane = tid & 31, g = lane >> 2, q = lane & 3;
  float4* red = (float4*)(sm + SM_HIN + (warp >> 1) * 3072) + lane;
  if (warp & 1) {
#pragma unroll
    for (int t = 0; t < 5; t++) red[t * 32] = make_float4(st.acc[t][0], st.acc[t][1], st.acc[t][2], st.acc[t][3]);
    red[160].x = st.v;
  }
  named_bar(3, 256);
  if (!(warp & 1)) {
    uint32_t lo[5], hi[5];
#pragma unroll
    for (int t = 0; t < 5; t++) {
      const float4 r = red[t * 32];
      lo[t] = pack_bf16(st.acc[t][0] + r.x, st.acc[t][1] + r.y); hi[t] = pack_bf16(st.acc[t][2] + r.z, st.acc[t][3] + r.w);
    }
    *k2048 = (unsigned short)pack_bf16(st.v + red[160].x, 0.f);
    uint32_t* kw = (uint32_t*)kd;
    kw[lane] = lo[0]; kw[32 + lane] = hi[0]; kw[64 + lane] = lo[1]; kw[96 + lane] = hi[1];
    kw[128 + 2 * g + (q & 1) + 32 * (q >> 1)] = lo[2]; kw[144 + 2 * g + (q & 1) + 32 * (q >> 1)] = hi[2];
    kw[192 + g + 16 * q] = lo[3]; kw[200 + g + 16 * q] = hi[3];
    kd[512 + g + 32 * q] = (unsigned short)lo[4]; kd[528 + g + 32 * q] = (unsigned short)(lo[4] >> 16);
    kd[520 + g + 32 * q] = (unsigned short)hi[4]; kd[536 + g + 32 * q] = (unsigned short)(hi[4] >> 16);
  }
}
constexpr int kd_index(int l) {
  if (l < 256) return l;
  const int sh = l < 512 ? 1 : l < 1024 ? 2 : 3;
  return ((l + (1 << (sh - 1)) - 1 + ((l >> sh) & 1)) >> sh) + 128 * sh;
}
struct KTab { unsigned int e[512 * 4]; };
constexpr KTab make_ktab() {
  KTab t = {};
  for (int it = 0; it < 511; it++) {
    const int l0 = 4 * it, b1 = kd_index(l0) & ~1;
    const unsigned int np = 0x54 + 0x22 * (l0 ? kd_index(l0 - 1) - b1 : 0);
    unsigned int n[4] = {0, 0, 0, 0};
    for (int k = 0; k < 4; k++) n[k] = 0x10 + 0x22 * (kd_index(l0 + k) - b1);
    t.e[4 * it] = 2 * b1 | ((b1 < 638 ? 4u : 0u) << 16);
    t.e[4 * it + 1] = (n[0] + 0x44) | (np << 8) | (n[1] << 16) | (n[0] << 24);
    t.e[4 * it + 2] = n[2] | (n[1] << 8) | (n[3] << 16) | (n[2] << 24);
    t.e[4 * it + 3] = l0 ? 0xffffffffu : 0xffffu;
  }
  return t;
}
__device__ __align__(16) const KTab g_ktab = make_ktab();
template <int NT>
__device__ __forceinline__ void kexpand(uint32_t sb, uint32_t k0, uint32_t k1, uint32_t k2048, int tid, uint4 e) {
#pragma unroll 1
  for (int it = tid; it < 511; it += NT) {
    const uint4 en = __ldg((const uint4*)g_ktab.e + min(it + NT, 511));
    const uint32_t o = e.x & 0xffffu, o2 = o + (e.x >> 16), dst = sb + T_KP + 64 + 16 * it;
#pragma unroll
    for (int c = 0; c < 4; c++) {
      const uint32_t a = c ? k1 + 1280 * (c - 1) : k0;
      const uint32_t x0 = lds32(a + o - 4), x1 = lds32(a + o), x2 = lds32(a + o2);
      sts128(dst + c * KP_BYTES, make_uint4(__byte_perm(x0, x1, e.y) & e.w, __byte_perm(x1, x2, e.y >> 16), __byte_perm(x1, x2, e.z), __byte_perm(x1, x2, e.z >> 16)));
    }
    e = en;
  }
  if (tid < 36) {
    const int c = tid / 9, i = tid - 9 * c;
    uint4 v = make_uint4(0u, 0u, 0u, 0u);
    if (i == 4) {
      uint32_t z, y;
      asm volatile("ld.shared.u16 %0, [%1];" : "=r"(z) : "r"(k2048 + 2 * c) : "memory");
      asm volatile("ld.shared.u16 %0, [%1];" : "=r"(y) : "r"((c ? k1 + 1280 * (c - 1) : k0) + 1278) : "memory");
      v = make_uint4(z | (y << 16), z * 0x10001u, z * 0x10001u, z * 0x10001u);
    }
    sts128(sb + T_KP + c * KP_BYTES + 16 * (i < 4 ? i : 511 + i), v);
  }
}

template <int NR>
__device__ __forceinline__ void conv_mma(float (&d)[NR], const uint32_t* a, uint64_t db) {
  if constexpr (NR == 64) wg_cv128<0>(d, a[0], a[1], a[2], a[3], db);
  else if constexpr (NR == 48) wg_cv96<0>(d, a[0], a[1], a[2], a[3], db);
  else if constexpr (NR == 32) wg_cv64<0>(d, a[0], a[1], a[2], a[3], db);
  else wg_rs32<0>(d, a[0], a[1], a[2], a[3], db);
}
__device__ __forceinline__ void conv_load(uint32_t (&a)[8], uint32_t o) {
#pragma unroll
  for (int c = 0; c < 2; c++) {
    a[4 * c + 0] = lds32(o + c * KP_BYTES); a[4 * c + 1] = lds32(o + c * KP_BYTES + 512);
    a[4 * c + 2] = lds32(o + c * KP_BYTES - 32); a[4 * c + 3] = lds32(o + c * KP_BYTES + 480);
  }
}
template <int NR>
__device__ __forceinline__ void conv_phase(float (&dA)[NR], float (&dB)[NR], uint32_t (&a)[4][8], uint32_t kp, uint64_t dU) {
#pragma unroll 1
  for (int i = 0; i < 2; i++) {
#pragma unroll
    for (int k = 0; k < 4; k++) {
      wg_fence();
      conv_mma<NR>(dA, a[k], dU - 2 * k); conv_mma<NR>(dB, a[k] + 4, dU - 2 * k + (U_BYTES >> 4));
      wg_commit();
      wg_wait<1>();
      if (k == 2 && i) kp += 64 * 24;
      conv_load(a[(k + 2) & 3], kp + 64 * (k + 2));
    }
    kp += 256;
    dU -= 8;
  }
  wg_wait<0>();
  reg_fence(dA); reg_fence(dB);
}
template <int NR>
__device__ __forceinline__ void upper_copy(float (&dst)[NR - 16], const float (&src)[NR]) {
#pragma unroll
  for (int i = 0; i < NR - 16; i++) asm volatile("mov.b32 %0, %1;" : "=f"(dst[i]) : "f"(src[i + 16]));
}
__device__ __forceinline__ void conv2(uint32_t sb, int wg, int w, int lane) {
  const int g = lane >> 2, q = lane & 3;
  float dA[64], dB[64];
  uint32_t a[4][8];
  const uint32_t kp = sb + T_KP + 2 * wg * KP_BYTES + 4 * (16 + 256 * (w >> 1) + 8 * (w & 1) + g - 2 * q);
  const uint64_t dU = mk_desc(sb + T_U + 2 * wg * U_BYTES + 256, 16, 256, 3);
#pragma unroll
  for (int i = 0; i < 64; i++) { dA[i] = 0.f; dB[i] = 0.f; }
  conv_load(a[0], kp); conv_load(a[1], kp + 64);
  conv_phase<64>(dA, dB, a, kp, dU);
  float eA[48], eB[48];
  upper_copy<64>(eA, dA); upper_copy<64>(eB, dB);
  conv_phase<48>(eA, eB, a, kp + 2048, dU);
  float fA[32], fB[32];
  upper_copy<48>(fA, eA); upper_copy<48>(fB, eB);
  conv_phase<32>(fA, fB, a, kp + 4096, dU);
  float gA[16], gB[16];
  upper_copy<32>(gA, fA); upper_copy<32>(gB, fB);
  conv_phase<16>(gA, gB, a, kp + 6144, dU);
#pragma unroll
  for (int i = 0; i < 16; i++) {
    dA[16 + i] = eA[i]; dA[32 + i] = fA[i]; dA[48 + i] = gA[i];
    dB[16 + i] = eB[i]; dB[32 + i] = fB[i]; dB[48 + i] = gB[i];
  }
  PROF_T(53);
  float z[2][16][2];
#pragma unroll
  for (int m = 0; m < 16; m++)
#pragma unroll
    for (int e = 0; e < 2; e++) {
      z[0][m][e] = m ? dA[4 * m + e] + dA[4 * m - 2 + e] : dA[e];
      z[1][m][e] = m ? dB[4 * m + e] + dB[4 * m - 2 + e] : dB[e];
    }
  const uint32_t xb = sb + T_X0 + wg * 8192, xc = wg ? T_X1 - T_X0 - 8192 : 4096;
  const uint32_t xw = xb + (w * 32 + lane) * 16, xr = xb + ((w ^ 2) * 32 + lane) * 16;
  float k[2][8][2];
  if (w < 2) {
#pragma unroll
    for (int c = 0; c < 2; c++)
#pragma unroll
      for (int m = 0; m < 8; m += 4) {
        sts128(xw + c * xc + (m >> 2) * 2048, make_uint4(pack_bf16(z[c][8 + m][0], z[c][8 + m][1]), pack_bf16(z[c][9 + m][0], z[c][9 + m][1]),
                                                          pack_bf16(z[c][10 + m][0], z[c][10 + m][1]), pack_bf16(z[c][11 + m][0], z[c][11 + m][1])));
#pragma unroll
        for (int i = 0; i < 4; i++) { k[c][m + i][0] = z[c][m + i][0]; k[c][m + i][1] = z[c][m + i][1]; }
      }
  } else {
#pragma unroll
    for (int c = 0; c < 2; c++)
#pragma unroll
      for (int m = 0; m < 8; m += 4) {
        sts128(xw + c * xc + (m >> 2) * 2048, make_uint4(m ? pack_bf16(z[c][m - 2][0], z[c][m - 2][1]) : 0u, m ? pack_bf16(z[c][m - 1][0], z[c][m - 1][1]) : 0u,
                                                          pack_bf16(z[c][m][0], z[c][m][1]), pack_bf16(z[c][m + 1][0], z[c][m + 1][1])));
#pragma unroll
        for (int i = 0; i < 4; i++) { k[c][m + i][0] = z[c][6 + m + i][0]; k[c][m + i][1] = z[c][6 + m + i][1]; }
      }
  }
  named_bar(1 + wg, 128);
  const uint32_t yb = sb + T_U + 2 * wg * U_BYTES;
#pragma unroll
  for (int c = 0; c < 2; c++)
#pragma unroll
    for (int m = 0; m < 8; m += 4) {
      const uint4 u = lds128(xr + c * xc + (m >> 2) * 2048);
      stmatrix_x4_t(yb + c * 4096 + (64 * (w >> 1) + 8 * m + lane) * 32 + 16 * (w & 1),
                    pack_bf16(k[c][m][0] + bf_lo(u.x), k[c][m][1] + bf_hi(u.x)), pack_bf16(k[c][m + 1][0] + bf_lo(u.y), k[c][m + 1][1] + bf_hi(u.y)),
                    pack_bf16(k[c][m + 2][0] + bf_lo(u.z), k[c][m + 2][1] + bf_hi(u.z)), pack_bf16(k[c][m + 3][0] + bf_lo(u.w), k[c][m + 3][1] + bf_hi(u.w)));
    }
  fence_async_smem();
  named_arrive(10 + wg, 160);
}
__device__ __forceinline__ void conv_ship(uint32_t sb, uint32_t bar, int wg, int ch, int cnt, bool el) {
  named_bar(10 + wg, 160);
  if (el) {
    bulk_s2g(g_y + (size_t)ch * L_, sb + T_U + 2 * wg * U_BYTES, 8192);
    bulk_commit_wait();
    cnt_add_done(cnt);
    mbar_arrive(bar + B_SG);
  }
  __syncwarp();
}

__global__ void __cluster_dims__(2, 1, 1) __launch_bounds__(384, 1) fused_kernel(const __grid_constant__ Params p) {
  extern __shared__ __align__(1024) unsigned char smem_raw[];
  const uint32_t sb = smem_u32(smem_raw);
  const uint32_t bar = sb + SM_BAR;
  const uint32_t vb = blockIdx.x;
  const int j = vb & 1, pair = vb >> 1, mt = pair & 15, sp = pair >> 4;
  const bool spare = pair >= 64;
  const int warp = __shfl_sync(0xffffffffu, threadIdx.x >> 5, 0), wg = warp >> 2, w = warp & 3;
  const int row0 = mt * 128 + (2 * sp + j) * 16;
  const int f0 = sp * 1152;
  const long long t_start = clock64();
  KgIn kin;
  if (wg < 2) kgen_load(p, spare ? 512 + ((int)vb - 128) * 16 : vb * 4, threadIdx.x, kin);
  if (threadIdx.x >= 288 && threadIdx.x < 301) prefetch_map(&p.xn + (threadIdx.x - 288));
  if (threadIdx.x == 256) {
    mbar_init(bar + B_X, 1);
    if (!spare) {
      mbar_expect_tx(bar + B_X, 16 * D_ * 2);
      bulk_g2s(sb + PR_LN, p.xp + (size_t)row0 * D_, 16 * D_ * 2, bar + B_X);
    }
#pragma unroll
    for (int i = 0; i < 30; i++) if (i != 22) mbar_init(bar + 8 * i, (i >= 7 && i < 14) ? 8 : (i == 27 && !spare) ? 4 : 1);
    mbar_init(bar + B_SG, 2);
    mbar_expect_tx(bar + B_HF, 8192); mbar_expect_tx(bar + B_HF + 8, 8192);
    asm volatile("fence.mbarrier_init.release.cluster;" ::: "memory");
  }
  __syncthreads();
  asm volatile("barrier.cluster.arrive.relaxed.aligned;" ::: "memory");

  if (wg == 2) {
    const int t = threadIdx.x & 127, lane = t & 31;
    const bool el = elect_one();
    if (!spare) {
      const uint32_t ra = sb + PR_LN + (t >> 3) * (D_ * 2) + (t & 7) * 16;
      if (w == 1 && el) {
#pragma unroll 1
        for (int u = 0; u < NST; u++) {
          const uint32_t dst = sb + SM_RING + u * SLOT, fb = bar + B_FULL + 8 * u;
          mbar_expect_tx(fb, 8192);
          tma_2d(dst, &p.gate, f0 + 64 * j, 32 * u, fb);
          tma_2d(dst + 4096, &p.up, f0 + 64 * j, 32 * u, fb);
        }
      }
      mbar_wait(bar + B_X, 0);
      PROF_T(61);
      uint4 v[9];
#pragma unroll
      for (int i = 0; i < 9; i++) v[i] = lds128(ra + i * 128);
      uint32_t* u = (uint32_t*)v;
      const float x0 = bf_lo(__shfl_sync(0xffffffffu, u[0], lane & 24));
      float s = 0.f, s2 = 0.f, q = 0.f, q2 = 0.f;
#pragma unroll
      for (int i = 0; i < 36; i++) {
        const float a = bf_lo(u[i]) - x0, b = bf_hi(u[i]) - x0;
        s += a; s2 += b; q = fmaf(a, a, q); q2 = fmaf(b, b, q2);
      }
      s += s2; q += q2;
#pragma unroll
      for (int o = 4; o; o >>= 1) { s += __shfl_xor_sync(0xffffffffu, s, o); q += __shfl_xor_sync(0xffffffffu, q, o); }
      s *= (1.0f / D_);
      const __nv_bfloat162 mb = __float2bfloat162_rn(s + x0);
      const float rinv = 1.0f / bf_round(sqrtf(bf_round(bf_round(fmaxf(fmaf(-s, s, q * (1.0f / D_)), 0.f)) + 1e-5f)));
#pragma unroll
      for (int i = 0; i < 36; i++) {
        const __nv_bfloat162 d2 = __hsub2(*(const __nv_bfloat162*)&u[i], mb);
        const uint32_t d = *(const uint32_t*)&d2;
        u[i] = pack_bf16(bf_lo(d) * rinv, bf_hi(d) * rinv);
      }
#pragma unroll
      for (int i = 0; i < 9; i++) sts128(ra + i * 128, v[i]);
      fence_async_smem();
      named_bar(5, 128);
      PROF_T(62);
      if (w == 0 && el) bulk_s2g(g_xn + (size_t)row0 * D_, sb + PR_LN, 16 * D_ * 2);
    }
    asm volatile("barrier.cluster.wait.aligned;" ::: "memory");
    asm volatile("setmaxnreg.dec.sync.aligned.u32 24;");
    if (w == 0) {
      if (!spare) {
        if (el) {
          bulk_commit_wait();
          cnt_add_done(C_LN + mt);
        }
        __syncwarp();
        PROF_T(63);
        cnt_wait(C_LN + mt, 8);
        PROF_T(67);
        fence_async_all();
#pragma unroll 1
        for (int kb = 0; kb < 6; kb++) {
          if (el) {
            mbar_expect_tx(bar + B_XN + 8 * kb, 16384);
            tma_2d(sb + SM_XN + kb * 16384, &p.xn, kb * 64, mt * 128, bar + B_XN + 8 * kb);
          }
        }
        named_bar(4, 384);
        PROF_T(69);
        uint32_t slot = 0, ph = 0;
#pragma unroll 1
        for (int c = 0; c <= 9; c++) {
          const int fc = f0 + c * 128;
          if (c < 9) {
            for (int u = c ? 0 : NST; u < 18; u++) {
              EMPTYW();
              if (el) {
                const uint32_t dst = sb + SM_RING + slot * SLOT, fb = bar + B_FULL + 8 * slot;
                mbar_expect_tx(fb, 8192);
                tma_2d(dst, &p.gate, fc + 64 * j, 32 * u, fb);
                tma_2d(dst + 4096, &p.up, fc + 64 * j, 32 * u, fb);
                if (c == 0 && u < 10) {
                  const int kb = u - 1;
                  if (kb < 8) mbar_expect_tx(bar + B_XN + 8 * kb, kb < 7 ? 16384 : 32768);
                  tma_2d(sb + SM_XN + kb * 16384, &p.xn, kb * 64, mt * 128, bar + B_XN + 8 * min(kb, 7));
                }
              }
              if (++slot == NST) { slot = 0; ph ^= 1; }
            }
          }
          const int fp = (fc - 128 + 64 * (1 - j)) >> 3, fo = fc + 64 * j;
#pragma unroll
          for (int i = 0; i < 8; i++) {
            const bool isP = i < 4;
            const int u = i & 3;
            if (isP ? (c == 0) : (c == 9)) continue;
            EMPTYW();
            if (el) {
              const uint32_t dst = sb + SM_RING + slot * SLOT, fb = bar + B_FULL + 8 * slot;
              mbar_expect_tx(fb, 9216);
              if (isP) {
                tma_5d(dst, &p.dp, 0, 0, fp + 4 * (u >> 1), 2 * (u & 1), 4 * j, fb);
                tma_4d(dst + 8192, &p.dp5, 512 + 32 * j, 0, fp + 4 * (u >> 1), 2 * (u & 1), fb);
              } else {
                tma_3d(dst, &p.dn, 0, fo + 16 * u, 4 * j, fb);
                tma_2d(dst + 8192, &p.dn5, 512 + 32 * j, fo + 16 * u, fb);
              }
            }
            if (++slot == NST) { slot = 0; ph ^= 1; }
          }
        }
        const int ch0 = vb * 4;
        cnt_wait(C_U, 384);
        fence_async_all();
        if (el) {
          mbar_expect_tx(bar + B_CV, 4 * U_BYTES);
          bulk_g2s(sb + T_U, g_u + (size_t)ch0 * U_LEN, 4 * U_BYTES, bar + B_CV);
        }
        unsigned char* img = g_part + (size_t)(2 * mt + j) * 16 * IMG;
        mbar_wait(bar + B_SG, 0);
        PROF_T(71);
        if (lane < 6) {
          const int r = (sp + 1 + (lane >> 1)) & 3;
          if (lane & 1) bulk_s2g(img + (r * 4 + sp) * IMG + 16384, sb + T_STG + 65536 + (r >> 1) * 8192 + (r & 1) * 2048, 2048);
          else bulk_s2g(img + (r * 4 + sp) * IMG, sb + T_STG + r * 16384, 16384);
          bulk_commit_wait();
        } else if (lane == 6) {
          mbar_expect_tx(bar + B_PT, 3 * IMG);
          mbar_expect_tx(bar + B_X, IMG);
          tma_2d(sb + T_PART + 3 * IMG, &p.x, 256 * j + 64 * sp, mt * 128, bar + B_X);
          tma_2d(sb + T_PART + 3 * IMG + 16384, &p.x5, 512 + 32 * j, mt * 128 + 32 * sp, bar + B_X);
        }
        __syncwarp();
        PROF_T(72);
        if (el) cnt_add_done(C_PART + 2 * mt + j);
        cnt_wait(C_PART + 2 * mt + j, 4);
        fence_async_all();
        PROF_T(74);
        if (lane < 3) bulk_g2s(sb + T_PART + lane * IMG, img + (sp * 4 + ((sp + 1 + lane) & 3)) * IMG, IMG, bar + B_PT);
        cnt_wait(C_Y5, 32);
        mbar_wait(bar + B_SG, 1);
        if (el) {
          mbar_expect_tx(bar + B_YT, IMG);
          tma_2d(sb + T_YT + 16384, &p.y5, mt * 128 + 32 * sp, 512 + 32 * j, bar + B_YT);
        }
        cnt_wait(C_Y + 4 * j + sp, 32);
        PROF_T(75);
        fence_async_all();
        if (el) {
          tma_2d(sb + T_YT, &p.y, mt * 128, 256 * j + 64 * sp, bar + B_YT);
          tma_2d(sb + T_YT + 8192, &p.y, mt * 128 + 64, 256 * j + 64 * sp, bar + B_YT);
        }
      } else {
        named_bar(7, 288);
        cnt_wait(C_U, 384);
        fence_async_all();
#pragma unroll 1
        for (int grp = 0; grp < 4; grp++) {
          const int ch0 = 512 + ((int)vb - 128) * 16 + grp * 4;
          if (grp) mbar_wait(bar + B_SG, (grp - 1) & 1);
          if (el) {
            mbar_expect_tx(bar + B_CV, 4 * U_BYTES);
            bulk_g2s(sb + T_U, g_u + (size_t)ch0 * U_LEN, 4 * U_BYTES, bar + B_CV);
          }
        }
      }
      PROF_T(79);
      PROF_DUMP();
      unsigned int old = 0;
      if (el) old = atomicAdd(g_cnt + C_DONE * 32, 1u) + 1;
      if (__any_sync(0xffffffffu, old == gridDim.x)) { g_cnt[lane * 32] = 0u; g_cnt[(lane + 32) * 32] = 0u; }
    } else {
      if (!spare) {
        named_bar(4, 384);
        uint4 k0v = make_uint4(0u, 0u, 0u, 0u);
        if (t < 112) k0v = lds128(sb + PR_K0 + (t - 32) * 16);
        named_bar(8, 96);
        if (t == 32) { mbar_arrive_remote(mapa(bar + B_HE, j ^ 1)); mbar_arrive_remote(mapa(bar + B_HE + 8, j ^ 1)); }
#pragma unroll 1
        for (int i = 0; i < 8; i++) mbar_wait(bar + B_XN + 8 * i, 0);
        const int tok = 8 * ((lane & 7) >> 1) + 2 * (lane >> 3) + (lane & 1);
#pragma unroll 1
        for (int it = w - 1; it < 36; it += 3) {
          const int oc = 9 * (2 * sp + j) + (it >> 2), tg = it & 3;
          uint4 v;
          ldmatrix_x4_t(sb + SM_XN + (oc >> 3) * 16384 + (32 * tg + tok) * 128 + (((oc ^ tok) & 7) << 4), v.x, v.y, v.z, v.w);
          ((uint4*)(g_u + (size_t)(8 * oc + (lane >> 2)) * U_LEN + 128 + mt * 128))[(4 * tg + (lane & 3)) ^ (tg >> 1)] = v;
        }
        __syncwarp();
        if (lane == 0) { fence_async_all(); cnt_add(C_U); }
        const uint4 e0 = __ldg((const uint4*)g_ktab.e + (t - 32));
        named_bar(9, 352);
        if (t < 112) sts128(sb + T_K0 + (t - 32) * 16, k0v);
        named_bar(8, 96);
        kexpand<96>(sb, sb + T_K0, sb + SM_KD, bar + B_K2048, t - 32, e0);
        __syncwarp();
        if (lane == 0) mbar_arrive(bar + B_CV);
        if (w < 3) conv_ship(sb, bar, w - 1, vb * 4 + 2 * (w - 1), C_Y + (vb >> 4), el);
      } else if (w < 3) {
#pragma unroll 1
        for (int grp = 0; grp < 4; grp++) conv_ship(sb, bar, w - 1, 512 + ((int)vb - 128) * 16 + grp * 4 + 2 * (w - 1), C_Y5, el);
      }
    }
  } else {
    const int t = threadIdx.x & 127, lane = t & 31;
    KgState kst;
    kgen_params(smem_raw, threadIdx.x, kin, kst);
    if (!spare) {
      PROF_T(60);
      kgen_steps(smem_raw, threadIdx.x, kst);
      PROF_T(51);
      kgen_finish(smem_raw, (unsigned short*)(smem_raw + (warp < 2 ? PR_K0 : SM_KD + ((warp >> 1) - 1) * 1280)),
                  (unsigned short*)(smem_raw + SM_BAR + B_K2048) + (warp >> 1), threadIdx.x, kst);
      named_arrive(4, 384);
    } else {
      const int c0 = 512 + ((int)vb - 128) * 16;
#pragma unroll 1
      for (int grp = 0; grp < 4; grp++) {
        if (grp) { kgen_load(p, c0 + grp * 4, threadIdx.x, kin); kgen_params(smem_raw, threadIdx.x, kin, kst); }
        kgen_steps(smem_raw, threadIdx.x, kst);
        kgen_finish(smem_raw, (unsigned short*)(smem_raw + SM_RING + (grp * 4 + (warp >> 1)) * 1280),
                    (unsigned short*)(smem_raw + SM_KD) + grp * 4 + (warp >> 1), threadIdx.x, kst);
        named_bar(3, 256);
      }
      named_arrive(7, 288);
    }
    PROF_T(41);
    asm volatile("barrier.cluster.wait.aligned;" ::: "memory");
    asm volatile("setmaxnreg.inc.sync.aligned.u32 240;");
    if (!spare) {
      const bool leader = (t == 0);
      float O1[128], O2[16];
      uint32_t slot = 0, ph = 0, prev = 0;
      const uint32_t hin = sb + SM_HIN + wg * 8192;
      const uint32_t r_hin = mapa(hin + (16 * w + (lane >> 2)) * 128 + (((lane & 3) ^ (lane >> 2)) << 4), j ^ 1);
      const uint32_t r_hf = mapa(bar + B_HF + 8 * wg, j ^ 1), r_he = mapa(bar + B_HE + 8 * wg, j ^ 1);
      const uint64_t dA0 = mk_desc(sb + SM_XN + wg * 8192, 16, 1024, 1);
      const uint64_t dH0 = mk_desc(hin, 16, 1024, 1);
      const uint64_t dG0 = mk_desc(sb + SM_RING, 4096, 1024, 1);
      const uint64_t dW0 = mk_desc(sb + SM_RING, 2048, 1024, 1);
      const uint64_t dX0 = mk_desc(sb + SM_RING + 8192, 512, 512, 2);
      auto adv = [&]() { prev = slot; if (++slot == NST) { slot = 0; ph ^= 1; } };
      auto release = [&](uint32_t s) { if (lane == 0) mbar_arrive(bar + B_EMPTY + 8 * s); };
      auto peer_begin = [&](int cp) {
        mbar_wait(bar + B_HF + 8 * wg, cp & 1);
        if (leader && cp < 8) mbar_expect_tx(bar + B_HF + 8 * wg, 8192);
        fence_async_smem();
      };
      auto peer_unit = [&](int u) {
        wg_fence();
        wg_ss256<1>(O1, dH0 + 2 * u, dW0 + (uint64_t)(slot * (SLOT >> 4)));
        wg_ss32<1>(O2, dH0 + 2 * u, dX0 + (uint64_t)(slot * (SLOT >> 4)));
        wg_commit();
      };
      auto chunk = [&](auto first_c, const int c) {
        constexpr bool FIRST = decltype(first_c)::value;
        float S[64];
        {
          if (FIRST) mbar_wait(bar + B_XN, 0);
          FULLW();
          if (FIRST) { PROF_T(42); PROF_G(2); }
          const uint64_t db = dG0 + (uint64_t)(slot * (SLOT >> 4));
          wg_fence();
          wg_ss128_init<1>(S, dA0, db);
          wg_ss128<1>(S, dA0 + 2, db + 128);
          wg_commit();
          adv();
        }
#pragma unroll 1
        for (int u = 1; u < 18; u++) {
          if (FIRST && !(u & 1) && u < 16) mbar_wait(bar + B_XN + 8 * (u >> 1), 0);
          FULLW();
          const uint64_t da = dA0 + (uint64_t)((u >> 1) * 1024 + (u & 1) * 4);
          const uint64_t db = dG0 + (uint64_t)(slot * (SLOT >> 4));
          wg_fence();
          wg_ss128<1>(S, da, db);
          wg_ss128<1>(S, da + 2, db + 128);
          wg_commit();
          if constexpr (!FIRST) { if (u == 12) peer_begin(c - 1); }
          wg_wait<1>();
          release(prev);
          if (c == 8 && u == 8) named_arrive(9, 352);
          adv();
        }
        uint32_t H[16];
        if constexpr (FIRST) { wg_wait<0>(); release(prev); }
        uint32_t rs = prev;
        auto rel_next = [&]() { release(rs); if (++rs == NST) rs = 0; };
        auto P = [&](int u) {
          FULLW();
          peer_unit(u);
          if (u) { wg_wait<2>(); rel_next(); }
          adv();
        };
        auto E = [&](int u) {
#pragma unroll
          for (int i = 8 * u; i < 8 * u + 8; i++) asm volatile("" : "+f"(S[i]), "+f"(S[32 + i])::"memory");
#pragma unroll
          for (int g = 2 * u; g < 2 * u + 2; g++) {
            H[2 * g] = pack_bf16(geglu(S[4 * g], S[32 + 4 * g]), geglu(S[4 * g + 1], S[33 + 4 * g]));
            H[2 * g + 1] = pack_bf16(geglu(S[4 * g + 2], S[34 + 4 * g]), geglu(S[4 * g + 3], S[35 + 4 * g]));
          }
#pragma unroll
          for (int i = 4 * u; i < 4 * u + 4; i++) asm volatile("" : "+r"(H[i])::"memory");
        };
        auto O = [&](int u) {
          FULLW();
          wg_fence();
          if (FIRST && u == 0) {
            wg_rs256_init<1>(O1, H[0], H[1], H[2], H[3], dW0 + (uint64_t)(slot * (SLOT >> 4)));
            wg_rs32_init<1>(O2, H[0], H[1], H[2], H[3], dX0 + (uint64_t)(slot * (SLOT >> 4)));
            rs = slot;
          } else {
            wg_rs256<1>(O1, H[4 * u], H[4 * u + 1], H[4 * u + 2], H[4 * u + 3], dW0 + (uint64_t)(slot * (SLOT >> 4)));
            wg_rs32<1>(O2, H[4 * u], H[4 * u + 1], H[4 * u + 2], H[4 * u + 3], dX0 + (uint64_t)(slot * (SLOT >> 4)));
          }
          wg_commit();
          if (u == 3) {
            mbar_wait(bar + B_HE + 8 * wg, c & 1);
            st_async_v4(r_hin, H[0], H[2], H[4], H[6], r_hf);
            st_async_v4(r_hin ^ 64, H[8], H[10], H[12], H[14], r_hf);
            st_async_v4(r_hin + 1024, H[1], H[3], H[5], H[7], r_hf);
            st_async_v4((r_hin ^ 64) + 1024, H[9], H[11], H[13], H[15], r_hf);
          }
          if (!FIRST || u >= 2) { wg_wait<2>(); rel_next(); }
          if (u == 1) { if constexpr (!FIRST) { if (leader) mbar_arrive_remote(r_he); } }
          if (u == 3) { wg_wait<1>(); rel_next(); wg_wait<0>(); rel_next(); }
          adv();
        };
        if constexpr (FIRST) { E(0); O(0); E(1); O(1); E(2); O(2); E(3); O(3); }
        else { P(0); P(1); E(0); P(2); E(1); P(3); O(0); E(2); O(1); O(2); E(3); O(3); }
        PROF_T(4 + 4 * c);
      };
      chunk(std::true_type{}, 0);
#pragma unroll 1
      for (int c = 1; c < 9; c++) chunk(std::false_type{}, c);
      peer_begin(8);
#pragma unroll 1
      for (int u = 0; u < 4; u++) { FULLW(); peer_unit(u); adv(); }
      wg_wait<0>();
      reg_fence(O1); reg_fence(O2);
      PROF_T(40); PROF_G(3);
      const int mi = lane >> 3, li = lane & 7;
      {
        const int row = 16 * w + 8 * (mi & 1) + li;
        const uint32_t stg = sb + T_STG + wg * 8192 + row * 128;
#pragma unroll
        for (int g = 0; g < 32; g += 2)
          stmatrix_x4(stg + (g >> 3) * 16384 + ((((g & 7) + (mi >> 1)) ^ li) << 4), pack_bf16(O1[4 * g], O1[4 * g + 1]), pack_bf16(O1[4 * g + 2], O1[4 * g + 3]),
                      pack_bf16(O1[4 * g + 4], O1[4 * g + 5]), pack_bf16(O1[4 * g + 6], O1[4 * g + 7]));
#pragma unroll
        for (int g = 0; g < 4; g += 2)
          stmatrix_x4(stg + 65536 - row * 64 + (((g + (mi >> 1)) ^ (li >> 1)) << 4), pack_bf16(O2[4 * g], O2[4 * g + 1]), pack_bf16(O2[4 * g + 2], O2[4 * g + 3]),
                      pack_bf16(O2[4 * g + 4], O2[4 * g + 5]), pack_bf16(O2[4 * g + 6], O2[4 * g + 7]));
        fence_async_smem();
        named_bar(1 + wg, 128);
        if (leader) mbar_arrive(bar + B_SG);
      }
      mbar_wait(bar + B_CV, 0);
      PROF_T(43);
      conv2(sb, wg, w, lane);
      PROF_T(44); PROF_G(5);
      const uint32_t rowi = 8 * (mi & 1) + li;
      const uint32_t own_m = sb + T_STG + sp * 16384, own_t = sb + T_STG + 65536 - 16384 + (sp >> 1) * 8192 + (sp & 1) * 2048;
      auto off = [&](int k) -> uint32_t {
        return k < 4 ? (16 * warp + rowi) * 128 + (((2 * k + (mi >> 1)) ^ li) << 4) : 16384 + (16 * warp + rowi) * 64 + (((2 * (k - 4) + (mi >> 1)) ^ (li >> 1)) << 4);
      };
      float f[6][8];
#pragma unroll
      for (int k = 0; k < 6; k++)
#pragma unroll
        for (int i = 0; i < 8; i++) f[k][i] = 0.f;
      named_bar(3, 256);
#pragma unroll 1
      for (int rep = 0; rep < 2; rep++) {
      mbar_wait(bar + (rep ? B_PT : B_X), rep ^ 1);
#pragma unroll 1
      for (int s = 2 * rep; s < 2 + 3 * rep; s++) {
        const uint32_t am = s ? sb + T_PART + (4 - s) * IMG : own_m, at = s ? am : own_t;
#pragma unroll
        for (int k = 0; k < 6; k++) {
          if (k >= 4 && warp >= 2) break;
          uint32_t r[4];
          ldmatrix_x4((k < 4 ? am : at) + off(k), r);
#pragma unroll
          for (int i = 0; i < 4; i++) { f[k][2 * i] += bf_lo(r[i]); f[k][2 * i + 1] += bf_hi(r[i]); }
        }
      }
      if (rep) { PROF_T(56); mbar_wait(bar + B_YT, 0); PROF_T(45); PROF_G(6); }
#pragma unroll
      for (int k = 0; k < 6; k++) {
        if (k >= 4 && warp >= 2) break;
        const uint32_t ya = k < 4 ? (warp >> 2) * 8192 + (16 * k + 8 * (mi >> 1) + li) * 128 + (((2 * (warp & 3) + (mi & 1)) ^ li) << 4)
                                  : 16384 + (16 * (k - 4) + 8 * (mi >> 1) + li) * 64 + (((2 * warp + (mi & 1)) ^ (li >> 1)) << 4);
        uint32_t y0, y1, y2, y3;
        ldmatrix_x4_t(sb + T_YT + ya, y0, y1, y2, y3);
        stmatrix_x4((k < 4 ? own_m : own_t) + off(k), pack_bf16(f[k][0] + bf_lo(y0), f[k][1] + bf_hi(y0)), pack_bf16(f[k][2] + bf_lo(y1), f[k][3] + bf_hi(y1)),
                    pack_bf16(f[k][4] + bf_lo(y2), f[k][5] + bf_hi(y2)), pack_bf16(f[k][6] + bf_lo(y3), f[k][7] + bf_hi(y3)));
      }
      fence_async_smem();
      __syncwarp();
      }
      PROF_T(57);
      if (lane == 0) {
        tma_store_2d(&p.out, own_m + warp * 2048, 256 * j + 64 * sp, mt * 128 + 16 * warp);
        if (warp < 2) tma_store_2d(&p.out5, own_t + 16384 + warp * 1024, 512 + 32 * j, mt * 128 + 32 * sp + 16 * warp);
        asm volatile("cp.async.bulk.commit_group;" ::: "memory");
        asm volatile("cp.async.bulk.wait_group.read 0;" ::: "memory");
      }
      PROF_T(46); PROF_G(7);
      PROF_DUMP();
    } else {
#pragma unroll 1
      for (int grp = 0; grp < 4; grp++) {
        kexpand<256>(sb, sb + SM_RING + grp * 5120, sb + SM_RING + grp * 5120 + 1280, sb + SM_KD + 8 * grp, threadIdx.x, __ldg((const uint4*)g_ktab.e + threadIdx.x));
        named_bar(3, 256);
        mbar_wait(bar + B_CV, grp & 1);
        conv2(sb, wg, w, lane);
        named_bar(3, 256);
      }
      PROF_T(46);
      PROF_DUMP();
    }
  }
}

typedef CUresult (*PFN_enc)(CUtensorMap*, CUtensorMapDataType, cuuint32_t, void*, const cuuint64_t*, const cuuint64_t*, const cuuint32_t*,
                            const cuuint32_t*, CUtensorMapInterleave, CUtensorMapSwizzle, CUtensorMapL2promotion, CUtensorMapFloatOOBfill);

void enc(PFN_enc fn, CUtensorMap* m, void* ptr, int rank, const cuuint64_t* dims, const cuuint64_t* strides, const cuuint32_t* box, CUtensorMapSwizzle sw) {
  cuuint32_t es[5] = {1, 1, 1, 1, 1};
  fn(m, CU_TENSOR_MAP_DATA_TYPE_BFLOAT16, rank, ptr, dims, strides, box, es, CU_TENSOR_MAP_INTERLEAVE_NONE, sw,
     L2PROMO, CU_TENSOR_MAP_FLOAT_OOB_FILL_NONE);
}

}

extern "C" void kernel_launch(void* const* d_in, const int* in_sizes, int n_in, void* d_out, int out_size) {
  static Params pr;
  static void* key[5] = {nullptr, nullptr, nullptr, nullptr, nullptr};
  if (key[0] != d_in[8] || key[1] != d_in[9] || key[2] != d_in[10] || key[3] != d_in[0] || key[4] != d_out) {
    key[0] = d_in[8]; key[1] = d_in[9]; key[2] = d_in[10]; key[3] = d_in[0]; key[4] = d_out;
    void* fnp = nullptr; cudaDriverEntryPointQueryResult st;
    cudaGetDriverEntryPoint("cuTensorMapEncodeTiled", &fnp, cudaEnableDefault, &st);
    PFN_enc fn = (PFN_enc)fnp;
    void *p_xn, *p_y;
    cudaGetSymbolAddress(&p_xn, g_xn); cudaGetSymbolAddress(&p_y, g_y);
    { cuuint64_t d[2] = {D_, L_}, s[1] = {D_ * 2};
      { cuuint32_t b[2] = {64, 128}; enc(fn, &pr.xn, p_xn, 2, d, s, b, CU_TENSOR_MAP_SWIZZLE_128B); }
      { cuuint32_t b[2] = {64, 128}; enc(fn, &pr.x, d_in[0], 2, d, s, b, CU_TENSOR_MAP_SWIZZLE_128B); }
      { cuuint32_t b[2] = {64, 16}; enc(fn, &pr.out, d_out, 2, d, s, b, CU_TENSOR_MAP_SWIZZLE_128B); }
      { cuuint32_t b[2] = {32, 32}; enc(fn, &pr.x5, d_in[0], 2, d, s, b, CU_TENSOR_MAP_SWIZZLE_64B); }
      { cuuint32_t b[2] = {32, 16}; enc(fn, &pr.out5, d_out, 2, d, s, b, CU_TENSOR_MAP_SWIZZLE_64B); } }
    { cuuint64_t d[2] = {F_, D_}, s[1] = {F_ * 2}; cuuint32_t b[2] = {64, 32};
      enc(fn, &pr.gate, d_in[8], 2, d, s, b, CU_TENSOR_MAP_SWIZZLE_128B); enc(fn, &pr.up, d_in[9], 2, d, s, b, CU_TENSOR_MAP_SWIZZLE_128B); }
    { void* wd = d_in[10];
      { cuuint64_t d[3] = {64, F_, 9}, s[2] = {D_ * 2, 128}; cuuint32_t b[3] = {64, 16, 4}; enc(fn, &pr.dn, wd, 3, d, s, b, CU_TENSOR_MAP_SWIZZLE_128B); }
      { cuuint64_t d[2] = {D_, F_}, s[1] = {D_ * 2}; cuuint32_t b[2] = {32, 16}; enc(fn, &pr.dn5, wd, 2, d, s, b, CU_TENSOR_MAP_SWIZZLE_64B); }
      { cuuint64_t d[5] = {64, 2, F_ / 8, 4, 9}, s[4] = {D_ * 2, D_ * 16, D_ * 4, 128}; cuuint32_t b[5] = {64, 2, 4, 2, 4};
        enc(fn, &pr.dp, wd, 5, d, s, b, CU_TENSOR_MAP_SWIZZLE_128B); }
      { cuuint64_t d[4] = {D_, 2, F_ / 8, 4}, s[3] = {D_ * 2, D_ * 16, D_ * 4}; cuuint32_t b[4] = {32, 2, 4, 2};
        enc(fn, &pr.dp5, wd, 4, d, s, b, CU_TENSOR_MAP_SWIZZLE_64B); }
    }
    { cuuint64_t d[2] = {L_, D_}, s[1] = {L_ * 2};
      { cuuint32_t b[2] = {64, 64}; enc(fn, &pr.y, p_y, 2, d, s, b, CU_TENSOR_MAP_SWIZZLE_128B); }
      { cuuint32_t b[2] = {32, 32}; enc(fn, &pr.y5, p_y, 2, d, s, b, CU_TENSOR_MAP_SWIZZLE_64B); } }
    {
      const int g2s[9] = {3, 0, 0, 1, 1, 2, 2, 3, 3};
      int cnt[4] = {0, 0, 0, 0}, sparec = 64;
      for (int pass = 0; pass < 2; pass++)
        for (int k = 0; k < 66; k++) {
          const int t = k < 4 ? 62 + k : k - 4;
          const int gpc = t < 32 ? t % 8 : t < 60 ? 1 + (t - 32) % 7 : t < 62 ? t - 54 : 8;
          if ((gpc == 8) != (pass == 1)) continue;
          const int s = g2s[gpc];
          pr.role[k] = cnt[s] < 16 ? (unsigned char)(s * 16 + cnt[s]++) : (unsigned char)sparec++;
        }
    }
    cudaFuncSetAttribute(fused_kernel, cudaFuncAttributeMaxDynamicSharedMemorySize, SMEM_BYTES);
  }
  const __nv_bfloat16* const* in = (const __nv_bfloat16* const*)d_in;
  pr.wd = in[10]; pr.xp = in[0]; pr.logA = in[1]; pr.Aim = in[2]; pr.Cre = in[3]; pr.Cim = in[4]; pr.logdt = in[5]; pr.Dsk = in[6];
  fused_kernel<<<132, 384, SMEM_BYTES>>>(pr);
}
```

```cpp
#include <cuda_runtime.h>
#include <cuda_bf16.h>
#include <cuda.h>
#include <stdint.h>
#include <stdio.h>
#include <type_traits>

namespace {

constexpr int L_ = 2048, D_ = 576, F_ = 4608, NM_ = 128;
constexpr int KP_LEN = 2080;
constexpr int U_LEN = 2176;

__device__ __align__(1024) __nv_bfloat16 g_xn[L_ * D_];
__device__ __align__(1024) __nv_bfloat16 g_u[D_ * L_];
__device__ __align__(1024) unsigned char g_part[32 * 16 * 18432];
__device__ __align__(1024) __nv_bfloat16 g_y[D_ * L_];
__device__ __align__(1024) unsigned int g_cnt[64 * 32];
constexpr int C_LN = 0, C_PART = 16, C_U = 48, C_Y = 49, C_Y5 = 57, C_DONE = 58;

#define PROF_T(idx) do {} while (0)
#define PROF_G(idx) do {} while (0)
__device__ __forceinline__ uint32_t smem_u32(const void* p) { return (uint32_t)__cvta_generic_to_shared(p); }
__device__ __forceinline__ void mbar_init(uint32_t bar, uint32_t cnt) { asm volatile("mbarrier.init.shared::cta.b64 [%0], %1;" ::"r"(bar), "r"(cnt)); }
__device__ __forceinline__ void mbar_expect_tx(uint32_t bar, uint32_t bytes) { asm volatile("mbarrier.arrive.expect_tx.shared::cta.b64 _, [%0], %1;" ::"r"(bar), "r"(bytes) : "memory"); }
__device__ __forceinline__ void mbar_arrive(uint32_t bar) { asm volatile("mbarrier.arrive.shared::cta.b64 _, [%0];" ::"r"(bar) : "memory"); }
__device__ __forceinline__ void mbar_arrive_remote(uint32_t bar) { asm volatile("mbarrier.arrive.shared::cluster.b64 _, [%0];" ::"r"(bar) : "memory"); }
__device__ __forceinline__ void mbar_wait(uint32_t bar, uint32_t parity) {
  asm volatile("{\n.reg .pred p, q;\n.reg .u32 n;\nmov.u32 n, 0;\nLW:\nmbarrier.try_wait.parity.shared::cta.b64 p, [%0], %1;\n"
               "add.u32 n, n, 1;\nsetp.lt.and.u32 q, n, 65536, !p;\n@q bra LW;\n}" ::"r"(bar), "r"(parity) : "memory");
}
__device__ __forceinline__ bool elect_one() {
  uint32_t ok;
  asm volatile("{\n.reg .pred p;\nelect.sync _|p, 0xffffffff;\nselp.u32 %0, 1, 0, p;\n}" : "=r"(ok));
  return ok;
}
__device__ __forceinline__ void tma_2d(uint32_t dst, const CUtensorMap* map, int c0, int c1, uint32_t bar) {
  asm volatile("cp.async.bulk.tensor.2d.shared::cluster.global.mbarrier::complete_tx::bytes [%0], [%1, {%3, %4}], [%2];"
               ::"r"(dst), "l"(map), "r"(bar), "r"(c0), "r"(c1) : "memory");
}
__device__ __forceinline__ void tma_3d(uint32_t dst, const CUtensorMap* map, int c0, int c1, int c2, uint32_t bar) {
  asm volatile("cp.async.bulk.tensor.3d.shared::cluster.global.mbarrier::complete_tx::bytes [%0], [%1, {%3, %4, %5}], [%2];"
               ::"r"(dst), "l"(map), "r"(bar), "r"(c0), "r"(c1), "r"(c2) : "memory");
}
__device__ __forceinline__ void tma_4d(uint32_t dst, const CUtensorMap* map, int c0, int c1, int c2, int c3, uint32_t bar) {
  asm volatile("cp.async.bulk.tensor.4d.shared::cluster.global.mbarrier::complete_tx::bytes [%0], [%1, {%3, %4, %5, %6}], [%2];"
               ::"r"(dst), "l"(map), "r"(bar), "r"(c0), "r"(c1), "r"(c2), "r"(c3) : "memory");
}
__device__ __forceinline__ void tma_5d(uint32_t dst, const CUtensorMap* map, int c0, int c1, int c2, int c3, int c4, uint32_t bar) {
  asm volatile("cp.async.bulk.tensor.5d.shared::cluster.global.mbarrier::complete_tx::bytes [%0], [%1, {%3, %4, %5, %6, %7}], [%2];"
               ::"r"(dst), "l"(map), "r"(bar), "r"(c0), "r"(c1), "r"(c2), "r"(c3), "r"(c4) : "memory");
}
__device__ __forceinline__ void bulk_g2s(uint32_t dst, const void* src, uint32_t bytes, uint32_t bar) {
  asm volatile("cp.async.bulk.shared::cluster.global.mbarrier::complete_tx::bytes [%0], [%1], %2, [%3];"
               ::"r"(dst), "l"(src), "r"(bytes), "r"(bar) : "memory");
}
__device__ __forceinline__ void prefetch_map(const CUtensorMap* m) { asm volatile("prefetch.tensormap [%0];" ::"l"(m) : "memory"); }
__device__ __forceinline__ uint32_t mapa(uint32_t addr, uint32_t rank) { uint32_t r; asm volatile("mapa.shared::cluster.u32 %0, %1, %2;" : "=r"(r) : "r"(addr), "r"(rank)); return r; }
__device__ __forceinline__ void fence_async_smem() { asm volatile("fence.proxy.async.shared::cta;" ::: "memory"); }
__device__ __forceinline__ void wg_fence() { asm volatile("wgmma.fence.sync.aligned;" ::: "memory"); }
__device__ __forceinline__ void wg_commit() { asm volatile("wgmma.commit_group.sync.aligned;" ::: "memory"); }
template <int N> __device__ __forceinline__ void wg_wait() { asm volatile("wgmma.wait_group.sync.aligned %0;" ::"n"(N) : "memory"); }
template <int N> __device__ __forceinline__ void reg_fence(float (&d)[N]) {
#pragma unroll
  for (int i = 0; i < N; i++) asm volatile("" : "+f"(d[i])::"memory");
}
__device__ __forceinline__ void named_bar(int id, int n) { asm volatile("bar.sync %0, %1;" ::"r"(id), "r"(n) : "memory"); }
__device__ __forceinline__ uint64_t mk_desc(uint32_t addr, uint32_t lbo, uint32_t sbo, uint32_t sw) {
  return (uint64_t)((addr & 0x3FFFF) >> 4) | ((uint64_t)(lbo >> 4) << 16) | ((uint64_t)(sbo >> 4) << 32) | ((uint64_t)sw << 62);
}
__device__ __forceinline__ uint32_t pack_bf16(float lo, float hi) {
  uint32_t r; asm("cvt.rn.bf16x2.f32 %0, %1, %2;" : "=r"(r) : "f"(hi), "f"(lo)); return r;
}
__device__ __forceinline__ float bf_lo(uint32_t v) { return __uint_as_float(v << 16); }
__device__ __forceinline__ float bf_hi(uint32_t v) { return __uint_as_float(v & 0xffff0000u); }
__device__ __forceinline__ float bf_round(float x) { return __bfloat162float(__float2bfloat16_rn(x)); }
__device__ __forceinline__ void st_async_v4(uint32_t addr, uint32_t a, uint32_t b, uint32_t c, uint32_t d, uint32_t bar) {
  asm volatile("st.async.weak.shared::cluster.mbarrier::complete_tx::bytes.v4.b32 [%0], {%1, %2, %3, %4}, [%5];"
               ::"r"(addr), "r"(a), "r"(b), "r"(c), "r"(d), "r"(bar) : "memory");
}
__device__ __forceinline__ void stmatrix_x4_t(uint32_t addr, uint32_t a, uint32_t b, uint32_t c, uint32_t d) {
  asm volatile("stmatrix.sync.aligned.m8n8.x4.trans.shared.b16 [%0], {%1, %2, %3, %4};" ::"r"(addr), "r"(a), "r"(b), "r"(c), "r"(d) : "memory");
}
__device__ __forceinline__ void ldmatrix_x4_t(uint32_t addr, uint32_t& a, uint32_t& b, uint32_t& c, uint32_t& d) {
  asm volatile("ldmatrix.sync.aligned.m8n8.x4.trans.shared.b16 {%0, %1, %2, %3}, [%4];" : "=r"(a), "=r"(b), "=r"(c), "=r"(d) : "r"(addr) : "memory");
}
__device__ __forceinline__ uint32_t lds32(uint32_t addr) { uint32_t v; asm volatile("ld.shared.b32 %0, [%1];" : "=r"(v) : "r"(addr) : "memory"); return v; }
__device__ __forceinline__ float geglu(float g, float u) {
  float z = g * fmaf(g * g, 0.0356774081f, 0.7978845608f);
  float t; asm("tanh.approx.f32 %0, %1;" : "=f"(t) : "f"(z));
  return (g * u) * fmaf(t, 0.5f, 0.5f);
}

__device__ __forceinline__ uint4 lds128(uint32_t addr) { uint4 v; asm volatile("ld.shared.v4.b32 {%0,%1,%2,%3}, [%4];" : "=r"(v.x), "=r"(v.y), "=r"(v.z), "=r"(v.w) : "r"(addr) : "memory"); return v; }
__device__ __forceinline__ void stmatrix_x4(uint32_t addr, uint32_t a, uint32_t b, uint32_t c, uint32_t d) {
  asm volatile("stmatrix.sync.aligned.m8n8.x4.shared.b16 [%0], {%1, %2, %3, %4};" ::"r"(addr), "r"(a), "r"(b), "r"(c), "r"(d) : "memory");
}
__device__ __forceinline__ void ldmatrix_x4(uint32_t addr, uint32_t (&r)[4]) {
  asm volatile("ldmatrix.sync.aligned.m8n8.x4.shared.b16 {%0, %1, %2, %3}, [%4];" : "=r"(r[0]), "=r"(r[1]), "=r"(r[2]), "=r"(r[3]) : "r"(addr) : "memory");
}
__device__ __forceinline__ void sts128(uint32_t addr, uint4 v) { asm volatile("st.shared.v4.b32 [%0], {%1,%2,%3,%4};" ::"r"(addr), "r"(v.x), "r"(v.y), "r"(v.z), "r"(v.w) : "memory"); }
__device__ __forceinline__ void bulk_s2g(void* dst, uint32_t src, uint32_t bytes) {
  asm volatile("cp.async.bulk.global.shared::cta.bulk_group [%0], [%1], %2;" ::"l"(dst), "r"(src), "r"(bytes) : "memory");
}
__device__ __forceinline__ void tma_store_2d(const CUtensorMap* map, uint32_t src, int c0, int c1) {
  asm volatile("cp.async.bulk.tensor.2d.global.shared::cta.bulk_group [%0, {%2, %3}], [%1];" ::"l"(map), "r"(src), "r"(c0), "r"(c1) : "memory");
}
__device__ __forceinline__ void bulk_commit_wait() {
  asm volatile("cp.async.bulk.commit_group;" ::: "memory");
  asm volatile("cp.async.bulk.wait_group 0;" ::: "memory");
}
__device__ __forceinline__ void named_arrive(int id, int n) { asm volatile("bar.arrive %0, %1;" ::"r"(id), "r"(n) : "memory"); }
__device__ __forceinline__ void fence_async_all() { asm volatile("fence.proxy.async.global;" ::: "memory"); }
__device__ __forceinline__ void cnt_add(int idx) {
  asm volatile("red.release.gpu.global.add.u32 [%0], 1;" ::"l"(g_cnt + idx * 32) : "memory");
}
__device__ __forceinline__ void cnt_add_done(int idx) {
  asm volatile("red.relaxed.gpu.global.add.u32 [%0], 1;" ::"l"(g_cnt + idx * 32) : "memory");
}
__device__ __forceinline__ void cnt_wait(int idx, uint32_t target) {
  const unsigned int* p = g_cnt + idx * 32;
#pragma unroll 1
  for (int it = 0; it < (1 << 18); it++) {
    uint32_t v; asm volatile("ld.acquire.gpu.global.u32 %0, [%1];" : "=r"(v) : "l"(p) : "memory");
    if (v >= target) break;
  }
}

template <int TB>
__device__ __forceinline__ void wg_ss128_init(float (&d)[64], uint64_t da, uint64_t db) {
  asm volatile(
    "wgmma.mma_async.sync.aligned.m64n128k16.f32.bf16.bf16 {%0, %1, %2, %3, %4, %5, %6, %7, %8, %9, %10, %11, %12, %13, %14, %15, %16, %17, %18, %19, %20, %21, %22, %23, %24, %25, %26, %27, %28, %29, %30, %31, %32, %33, %34, %35, %36, %37, %38, %39, %40, %41, %42, %43, %44, %45, %46, %47, %48, %49, %50, %51, %52, %53, %54, %55, %56, %57, %58, %59, %60, %61, %62, %63}, %64, %65, 0, 1, 1, 0, %66;"
    : "=f"(d[0]), "=f"(d[1]), "=f"(d[2]), "=f"(d[3]), "=f"(d[4]), "=f"(d[5]), "=f"(d[6]), "=f"(d[7]), "=f"(d[8]), "=f"(d[9]), "=f"(d[10]), "=f"(d[11]), "=f"(d[12]), "=f"(d[13]), "=f"(d[14]), "=f"(d[15]), "=f"(d[16]), "=f"(d[17]), "=f"(d[18]), "=f"(d[19]), "=f"(d[20]), "=f"(d[21]), "=f"(d[22]), "=f"(d[23]), "=f"(d[24]), "=f"(d[25]), "=f"(d[26]), "=f"(d[27]), "=f"(d[28]), "=f"(d[29]), "=f"(d[30]), "=f"(d[31]), "=f"(d[32]), "=f"(d[33]), "=f"(d[34]), "=f"(d[35]), "=f"(d[36]), "=f"(d[37]), "=f"(d[38]), "=f"(d[39]), "=f"(d[40]), "=f"(d[41]), "=f"(d[42]), "=f"(d[43]), "=f"(d[44]), "=f"(d[45]), "=f"(d[46]), "=f"(d[47]), "=f"(d[48]), "=f"(d[49]), "=f"(d[50]), "=f"(d[51]), "=f"(d[52]), "=f"(d[53]), "=f"(d[54]), "=f"(d[55]), "=f"(d[56]), "=f"(d[57]), "=f"(d[58]), "=f"(d[59]), "=f"(d[60]), "=f"(d[61]), "=f"(d[62]), "=f"(d[63])
    : "l"(da), "l"(db), "n"(TB));
}
template <int TB>
__device__ __forceinline__ void wg_ss128(float (&d)[64], uint64_t da, uint64_t db) {
  asm volatile(
    "wgmma.mma_async.sync.aligned.m64n128k16.f32.bf16.bf16 {%0, %1, %2, %3, %4, %5, %6, %7, %8, %9, %10, %11, %12, %13, %14, %15, %16, %17, %18, %19, %20, %21, %22, %23, %24, %25, %26, %27, %28, %29, %30, %31, %32, %33, %34, %35, %36, %37, %38, %39, %40, %41, %42, %43, %44, %45, %46, %47, %48, %49, %50, %51, %52, %53, %54, %55, %56, %57, %58, %59, %60, %61, %62, %63}, %64, %65, 1, 1, 1, 0, %66;"
    : "+f"(d[0]), "+f"(d[1]), "+f"(d[2]), "+f"(d[3]), "+f"(d[4]), "+f"(d[5]), "+f"(d[6]), "+f"(d[7]), "+f"(d[8]), "+f"(d[9]), "+f"(d[10]), "+f"(d[11]), "+f"(d[12]), "+f"(d[13]), "+f"(d[14]), "+f"(d[15]), "+f"(d[16]), "+f"(d[17]), "+f"(d[18]), "+f"(d[19]), "+f"(d[20]), "+f"(d[21]), "+f"(d[22]), "+f"(d[23]), "+f"(d[24]), "+f"(d[25]), "+f"(d[26]), "+f"(d[27]), "+f"(d[28]), "+f"(d[29]), "+f"(d[30]), "+f"(d[31]), "+f"(d[32]), "+f"(d[33]), "+f"(d[34]), "+f"(d[35]), "+f"(d[36]), "+f"(d[37]), "+f"(d[38]), "+f"(d[39]), "+f"(d[40]), "+f"(d[41]), "+f"(d[42]), "+f"(d[43]), "+f"(d[44]), "+f"(d[45]), "+f"(d[46]), "+f"(d[47]), "+f"(d[48]), "+f"(d[49]), "+f"(d[50]), "+f"(d[51]), "+f"(d[52]), "+f"(d[53]), "+f"(d[54]), "+f"(d[55]), "+f"(d[56]), "+f"(d[57]), "+f"(d[58]), "+f"(d[59]), "+f"(d[60]), "+f"(d[61]), "+f"(d[62]), "+f"(d[63])
    : "l"(da), "l"(db), "n"(TB));
}
template <int TB>
__device__ __forceinline__ void wg_ss256(float (&d)[128], uint64_t da, uint64_t db) {
  asm volatile(
    "wgmma.mma_async.sync.aligned.m64n256k16.f32.bf16.bf16 {%0, %1, %2, %3, %4, %5, %6, %7, %8, %9, %10, %11, %12, %13, %14, %15, %16, %17, %18, %19, %20, %21, %22, %23, %24, %25, %26, %27, %28, %29, %30, %31, %32, %33, %34, %35, %36, %37, %38, %39, %40, %41, %42, %43, %44, %45, %46, %47, %48, %49, %50, %51, %52, %53, %54, %55, %56, %57, %58, %59, %60, %61, %62, %63, %64, %65, %66, %67, %68, %69, %70, %71, %72, %73, %74, %75, %76, %77, %78, %79, %80, %81, %82, %83, %84, %85, %86, %87, %88, %89, %90, %91, %92, %93, %94, %95, %96, %97, %98, %99, %100, %101, %102, %103, %104, %105, %106, %107, %108, %109, %110, %111, %112, %113, %114, %115, %116, %117, %118, %119, %120, %121, %122, %123, %124, %125, %126, %127}, %128, %129, 1, 1, 1, 0, %130;"
    : "+f"(d[0]), "+f"(d[1]), "+f"(d[2]), "+f"(d[3]), "+f"(d[4]), "+f"(d[5]), "+f"(d[6]), "+f"(d[7]), "+f"(d[8]), "+f"(d[9]), "+f"(d[10]), "+f"(d[11]), "+f"(d[12]), "+f"(d[13]), "+f"(d[14]), "+f"(d[15]), "+f"(d[16]), "+f"(d[17]), "+f"(d[18]), "+f"(d[19]), "+f"(d[20]), "+f"(d[21]), "+f"(d[22]), "+f"(d[23]), "+f"(d[24]), "+f"(d[25]), "+f"(d[26]), "+f"(d[27]), "+f"(d[28]), "+f"(d[29]), "+f"(d[30]), "+f"(d[31]), "+f"(d[32]), "+f"(d[33]), "+f"(d[34]), "+f"(d[35]), "+f"(d[36]), "+f"(d[37]), "+f"(d[38]), "+f"(d[39]), "+f"(d[40]), "+f"(d[41]), "+f"(d[42]), "+f"(d[43]), "+f"(d[44]), "+f"(d[45]), "+f"(d[46]), "+f"(d[47]), "+f"(d[48]), "+f"(d[49]), "+f"(d[50]), "+f"(d[51]), "+f"(d[52]), "+f"(d[53]), "+f"(d[54]), "+f"(d[55]), "+f"(d[56]), "+f"(d[57]), "+f"(d[58]), "+f"(d[59]), "+f"(d[60]), "+f"(d[61]), "+f"(d[62]), "+f"(d[63]), "+f"(d[64]), "+f"(d[65]), "+f"(d[66]), "+f"(d[67]), "+f"(d[68]), "+f"(d[69]), "+f"(d[70]), "+f"(d[71]), "+f"(d[72]), "+f"(d[73]), "+f"(d[74]), "+f"(d[75]), "+f"(d[76]), "+f"(d[77]), "+f"(d[78]), "+f"(d[79]), "+f"(d[80]), "+f"(d[81]), "+f"(d[82]), "+f"(d[83]), "+f"(d[84]), "+f"(d[85]), "+f"(d[86]), "+f"(d[87]), "+f"(d[88]), "+f"(d[89]), "+f"(d[90]), "+f"(d[91]), "+f"(d[92]), "+f"(d[93]), "+f"(d[94]), "+f"(d[95]), "+f"(d[96]), "+f"(d[97]), "+f"(d[98]), "+f"(d[99]), "+f"(d[100]), "+f"(d[101]), "+f"(d[102]), "+f"(d[103]), "+f"(d[104]), "+f"(d[105]), "+f"(d[106]), "+f"(d[107]), "+f"(d[108]), "+f"(d[109]), "+f"(d[110]), "+f"(d[111]), "+f"(d[112]), "+f"(d[113]), "+f"(d[114]), "+f"(d[115]), "+f"(d[116]), "+f"(d[117]), "+f"(d[118]), "+f"(d[119]), "+f"(d[120]), "+f"(d[121]), "+f"(d[122]), "+f"(d[123]), "+f"(d[124]), "+f"(d[125]), "+f"(d[126]), "+f"(d[127])
    : "l"(da), "l"(db), "n"(TB));
}
template <int TB>
__device__ __forceinline__ void wg_ss32(float (&d)[16], uint64_t da, uint64_t db) {
  asm volatile(
    "wgmma.mma_async.sync.aligned.m64n32k16.f32.bf16.bf16 {%0, %1, %2, %3, %4, %5, %6, %7, %8, %9, %10, %11, %12, %13, %14, %15}, %16, %17, 1, 1, 1, 0, %18;"
    : "+f"(d[0]), "+f"(d[1]), "+f"(d[2]), "+f"(d[3]), "+f"(d[4]), "+f"(d[5]), "+f"(d[6]), "+f"(d[7]), "+f"(d[8]), "+f"(d[9]), "+f"(d[10]), "+f"(d[11]), "+f"(d[12]), "+f"(d[13]), "+f"(d[14]), "+f"(d[15])
    : "l"(da), "l"(db), "n"(TB));
}
template <int TB>
__device__ __forceinline__ void wg_rs256(float (&d)[128], uint32_t a0, uint32_t a1, uint32_t a2, uint32_t a3, uint64_t db) {
  asm volatile(
    "wgmma.mma_async.sync.aligned.m64n256k16.f32.bf16.bf16 {%0, %1, %2, %3, %4, %5, %6, %7, %8, %9, %10, %11, %12, %13, %14, %15, %16, %17, %18, %19, %20, %21, %22, %23, %24, %25, %26, %27, %28, %29, %30, %31, %32, %33, %34, %35, %36, %37, %38, %39, %40, %41, %42, %43, %44, %45, %46, %47, %48, %49, %50, %51, %52, %53, %54, %55, %56, %57, %58, %59, %60, %61, %62, %63, %64, %65, %66, %67, %68, %69, %70, %71, %72, %73, %74, %75, %76, %77, %78, %79, %80, %81, %82, %83, %84, %85, %86, %87, %88, %89, %90, %91, %92, %93, %94, %95, %96, %97, %98, %99, %100, %101, %102, %103, %104, %105, %106, %107, %108, %109, %110, %111, %112, %113, %114, %115, %116, %117, %118, %119, %120, %121, %122, %123, %124, %125, %126, %127}, {%128, %129, %130, %131}, %132, 1, 1, 1, %133;"
    : "+f"(d[0]), "+f"(d[1]), "+f"(d[2]), "+f"(d[3]), "+f"(d[4]), "+f"(d[5]), "+f"(d[6]), "+f"(d[7]), "+f"(d[8]), "+f"(d[9]), "+f"(d[10]), "+f"(d[11]), "+f"(d[12]), "+f"(d[13]), "+f"(d[14]), "+f"(d[15]), "+f"(d[16]), "+f"(d[17]), "+f"(d[18]), "+f"(d[19]), "+f"(d[20]), "+f"(d[21]), "+f"(d[22]), "+f"(d[23]), "+f"(d[24]), "+f"(d[25]), "+f"(d[26]), "+f"(d[27]), "+f"(d[28]), "+f"(d[29]), "+f"(d[30]), "+f"(d[31]), "+f"(d[32]), "+f"(d[33]), "+f"(d[34]), "+f"(d[35]), "+f"(d[36]), "+f"(d[37]), "+f"(d[38]), "+f"(d[39]), "+f"(d[40]), "+f"(d[41]), "+f"(d[42]), "+f"(d[43]), "+f"(d[44]), "+f"(d[45]), "+f"(d[46]), "+f"(d[47]), "+f"(d[48]), "+f"(d[49]), "+f"(d[50]), "+f"(d[51]), "+f"(d[52]), "+f"(d[53]), "+f"(d[54]), "+f"(d[55]), "+f"(d[56]), "+f"(d[57]), "+f"(d[58]), "+f"(d[59]), "+f"(d[60]), "+f"(d[61]), "+f"(d[62]), "+f"(d[63]), "+f"(d[64]), "+f"(d[65]), "+f"(d[66]), "+f"(d[67]), "+f"(d[68]), "+f"(d[69]), "+f"(d[70]), "+f"(d[71]), "+f"(d[72]), "+f"(d[73]), "+f"(d[74]), "+f"(d[75]), "+f"(d[76]), "+f"(d[77]), "+f"(d[78]), "+f"(d[79]), "+f"(d[80]), "+f"(d[81]), "+f"(d[82]), "+f"(d[83]), "+f"(d[84]), "+f"(d[85]), "+f"(d[86]), "+f"(d[87]), "+f"(d[88]), "+f"(d[89]), "+f"(d[90]), "+f"(d[91]), "+f"(d[92]), "+f"(d[93]), "+f"(d[94]), "+f"(d[95]), "+f"(d[96]), "+f"(d[97]), "+f"(d[98]), "+f"(d[99]), "+f"(d[100]), "+f"(d[101]), "+f"(d[102]), "+f"(d[103]), "+f"(d[104]), "+f"(d[105]), "+f"(d[106]), "+f"(d[107]), "+f"(d[108]), "+f"(d[109]), "+f"(d[110]), "+f"(d[111]), "+f"(d[112]), "+f"(d[113]), "+f"(d[114]), "+f"(d[115]), "+f"(d[116]), "+f"(d[117]), "+f"(d[118]), "+f"(d[119]), "+f"(d[120]), "+f"(d[121]), "+f"(d[122]), "+f"(d[123]), "+f"(d[124]), "+f"(d[125]), "+f"(d[126]), "+f"(d[127])
    : "r"(a0), "r"(a1), "r"(a2), "r"(a3), "l"(db), "n"(TB));
}
template <int TB>
__device__ __forceinline__ void wg_rs32(float (&d)[16], uint32_t a0, uint32_t a1, uint32_t a2, uint32_t a3, uint64_t db) {
  asm volatile(
    "wgmma.mma_async.sync.aligned.m64n32k16.f32.bf16.bf16 {%0, %1, %2, %3, %4, %5, %6, %7, %8, %9, %10, %11, %12, %13, %14, %15}, {%16, %17, %18, %19}, %20, 1, 1, 1, %21;"
    : "+f"(d[0]), "+f"(d[1]), "+f"(d[2]), "+f"(d[3]), "+f"(d[4]), "+f"(d[5]), "+f"(d[6]), "+f"(d[7]), "+f"(d[8]), "+f"(d[9]), "+f"(d[10]), "+f"(d[11]), "+f"(d[12]), "+f"(d[13]), "+f"(d[14]), "+f"(d[15])
    : "r"(a0), "r"(a1), "r"(a2), "r"(a3), "l"(db), "n"(TB));
}
template <int TB>
__device__ __forceinline__ void wg_cv128(float (&d)[64], uint32_t a0, uint32_t a1, uint32_t a2, uint32_t a3, uint64_t db) {
  asm volatile(
    "wgmma.mma_async.sync.aligned.m64n128k16.f32.bf16.bf16 {%0, %1, %2, %3, %4, %5, %6, %7, %8, %9, %10, %11, %12, %13, %14, %15, %16, %17, %18, %19, %20, %21, %22, %23, %24, %25, %26, %27, %28, %29, %30, %31, %32, %33, %34, %35, %36, %37, %38, %39, %40, %41, %42, %43, %44, %45, %46, %47, %48, %49, %50, %51, %52, %53, %54, %55, %56, %57, %58, %59, %60, %61, %62, %63}, {%64, %65, %66, %67}, %68, 1, 1, 1, %69;"
    : "+f"(d[0]), "+f"(d[1]), "+f"(d[2]), "+f"(d[3]), "+f"(d[4]), "+f"(d[5]), "+f"(d[6]), "+f"(d[7]), "+f"(d[8]), "+f"(d[9]), "+f"(d[10]), "+f"(d[11]), "+f"(d[12]), "+f"(d[13]), "+f"(d[14]), "+f"(d[15]), "+f"(d[16]), "+f"(d[17]), "+f"(d[18]), "+f"(d[19]), "+f"(d[20]), "+f"(d[21]), "+f"(d[22]), "+f"(d[23]), "+f"(d[24]), "+f"(d[25]), "+f"(d[26]), "+f"(d[27]), "+f"(d[28]), "+f"(d[29]), "+f"(d[30]), "+f"(d[31]), "+f"(d[32]), "+f"(d[33]), "+f"(d[34]), "+f"(d[35]), "+f"(d[36]), "+f"(d[37]), "+f"(d[38]), "+f"(d[39]), "+f"(d[40]), "+f"(d[41]), "+f"(d[42]), "+f"(d[43]), "+f"(d[44]), "+f"(d[45]), "+f"(d[46]), "+f"(d[47]), "+f"(d[48]), "+f"(d[49]), "+f"(d[50]), "+f"(d[51]), "+f"(d[52]), "+f"(d[53]), "+f"(d[54]), "+f"(d[55]), "+f"(d[56]), "+f"(d[57]), "+f"(d[58]), "+f"(d[59]), "+f"(d[60]), "+f"(d[61]), "+f"(d[62]), "+f"(d[63])
    : "r"(a0), "r"(a1), "r"(a2), "r"(a3), "l"(db), "n"(TB));
}
template <int TB>
__device__ __forceinline__ void wg_cv96(float (&d)[48], uint32_t a0, uint32_t a1, uint32_t a2, uint32_t a3, uint64_t db) {
  asm volatile(
    "wgmma.mma_async.sync.aligned.m64n96k16.f32.bf16.bf16 {%0, %1, %2, %3, %4, %5, %6, %7, %8, %9, %10, %11, %12, %13, %14, %15, %16, %17, %18, %19, %20, %21, %22, %23, %24, %25, %26, %27, %28, %29, %30, %31, %32, %33, %34, %35, %36, %37, %38, %39, %40, %41, %42, %43, %44, %45, %46, %47}, {%48, %49, %50, %51}, %52, 1, 1, 1, %53;"
    : "+f"(d[0]), "+f"(d[1]), "+f"(d[2]), "+f"(d[3]), "+f"(d[4]), "+f"(d[5]), "+f"(d[6]), "+f"(d[7]), "+f"(d[8]), "+f"(d[9]), "+f"(d[10]), "+f"(d[11]), "+f"(d[12]), "+f"(d[13]), "+f"(d[14]), "+f"(d[15]), "+f"(d[16]), "+f"(d[17]), "+f"(d[18]), "+f"(d[19]), "+f"(d[20]), "+f"(d[21]), "+f"(d[22]), "+f"(d[23]), "+f"(d[24]), "+f"(d[25]), "+f"(d[26]), "+f"(d[27]), "+f"(d[28]), "+f"(d[29]), "+f"(d[30]), "+f"(d[31]), "+f"(d[32]), "+f"(d[33]), "+f"(d[34]), "+f"(d[35]), "+f"(d[36]), "+f"(d[37]), "+f"(d[38]), "+f"(d[39]), "+f"(d[40]), "+f"(d[41]), "+f"(d[42]), "+f"(d[43]), "+f"(d[44]), "+f"(d[45]), "+f"(d[46]), "+f"(d[47])
    : "r"(a0), "r"(a1), "r"(a2), "r"(a3), "l"(db), "n"(TB));
}
template <int TB>
__device__ __forceinline__ void wg_cv64(float (&d)[32], uint32_t a0, uint32_t a1, uint32_t a2, uint32_t a3, uint64_t db) {
  asm volatile(
    "wgmma.mma_async.sync.aligned.m64n64k16.f32.bf16.bf16 {%0, %1, %2, %3, %4, %5, %6, %7, %8, %9, %10, %11, %12, %13, %14, %15, %16, %17, %18, %19, %20, %21, %22, %23, %24, %25, %26, %27, %28, %29, %30, %31}, {%32, %33, %34, %35}, %36, 1, 1, 1, %37;"
    : "+f"(d[0]), "+f"(d[1]), "+f"(d[2]), "+f"(d[3]), "+f"(d[4]), "+f"(d[5]), "+f"(d[6]), "+f"(d[7]), "+f"(d[8]), "+f"(d[9]), "+f"(d[10]), "+f"(d[11]), "+f"(d[12]), "+f"(d[13]), "+f"(d[14]), "+f"(d[15]), "+f"(d[16]), "+f"(d[17]), "+f"(d[18]), "+f"(d[19]), "+f"(d[20]), "+f"(d[21]), "+f"(d[22]), "+f"(d[23]), "+f"(d[24]), "+f"(d[25]), "+f"(d[26]), "+f"(d[27]), "+f"(d[28]), "+f"(d[29]), "+f"(d[30]), "+f"(d[31])
    : "r"(a0), "r"(a1), "r"(a2), "r"(a3), "l"(db), "n"(TB));
}
template <int TB>
__device__ __forceinline__ void wg_cv128_init(float (&d)[64], uint32_t a0, uint32_t a1, uint32_t a2, uint32_t a3, uint64_t db) {
  asm volatile(
    "wgmma.mma_async.sync.aligned.m64n128k16.f32.bf16.bf16 {%0, %1, %2, %3, %4, %5, %6, %7, %8, %9, %10, %11, %12, %13, %14, %15, %16, %17, %18, %19, %20, %21, %22, %23, %24, %25, %26, %27, %28, %29, %30, %31, %32, %33, %34, %35, %36, %37, %38, %39, %40, %41, %42, %43, %44, %45, %46, %47, %48, %49, %50, %51, %52, %53, %54, %55, %56, %57, %58, %59, %60, %61, %62, %63}, {%64, %65, %66, %67}, %68, 0, 1, 1, %69;"
    : "=f"(d[0]), "=f"(d[1]), "=f"(d[2]), "=f"(d[3]), "=f"(d[4]), "=f"(d[5]), "=f"(d[6]), "=f"(d[7]), "=f"(d[8]), "=f"(d[9]), "=f"(d[10]), "=f"(d[11]), "=f"(d[12]), "=f"(d[13]), "=f"(d[14]), "=f"(d[15]), "=f"(d[16]), "=f"(d[17]), "=f"(d[18]), "=f"(d[19]), "=f"(d[20]), "=f"(d[21]), "=f"(d[22]), "=f"(d[23]), "=f"(d[24]), "=f"(d[25]), "=f"(d[26]), "=f"(d[27]), "=f"(d[28]), "=f"(d[29]), "=f"(d[30]), "=f"(d[31]), "=f"(d[32]), "=f"(d[33]), "=f"(d[34]), "=f"(d[35]), "=f"(d[36]), "=f"(d[37]), "=f"(d[38]), "=f"(d[39]), "=f"(d[40]), "=f"(d[41]), "=f"(d[42]), "=f"(d[43]), "=f"(d[44]), "=f"(d[45]), "=f"(d[46]), "=f"(d[47]), "=f"(d[48]), "=f"(d[49]), "=f"(d[50]), "=f"(d[51]), "=f"(d[52]), "=f"(d[53]), "=f"(d[54]), "=f"(d[55]), "=f"(d[56]), "=f"(d[57]), "=f"(d[58]), "=f"(d[59]), "=f"(d[60]), "=f"(d[61]), "=f"(d[62]), "=f"(d[63])
    : "r"(a0), "r"(a1), "r"(a2), "r"(a3), "l"(db), "n"(TB));
}
template <int TB>
__device__ __forceinline__ void wg_rs256_init(float (&d)[128], uint32_t a0, uint32_t a1, uint32_t a2, uint32_t a3, uint64_t db) {
  asm volatile(
    "wgmma.mma_async.sync.aligned.m64n256k16.f32.bf16.bf16 {%0, %1, %2, %3, %4, %5, %6, %7, %8, %9, %10, %11, %12, %13, %14, %15, %16, %17, %18, %19, %20, %21, %22, %23, %24, %25, %26, %27, %28, %29, %30, %31, %32, %33, %34, %35, %36, %37, %38, %39, %40, %41, %42, %43, %44, %45, %46, %47, %48, %49, %50, %51, %52, %53, %54, %55, %56, %57, %58, %59, %60, %61, %62, %63, %64, %65, %66, %67, %68, %69, %70, %71, %72, %73, %74, %75, %76, %77, %78, %79, %80, %81, %82, %83, %84, %85, %86, %87, %88, %89, %90, %91, %92, %93, %94, %95, %96, %97, %98, %99, %100, %101, %102, %103, %104, %105, %106, %107, %108, %109, %110, %111, %112, %113, %114, %115, %116, %117, %118, %119, %120, %121, %122, %123, %124, %125, %126, %127}, {%128, %129, %130, %131}, %132, 0, 1, 1, %133;"
    : "=f"(d[0]), "=f"(d[1]), "=f"(d[2]), "=f"(d[3]), "=f"(d[4]), "=f"(d[5]), "=f"(d[6]), "=f"(d[7]), "=f"(d[8]), "=f"(d[9]), "=f"(d[10]), "=f"(d[11]), "=f"(d[12]), "=f"(d[13]), "=f"(d[14]), "=f"(d[15]), "=f"(d[16]), "=f"(d[17]), "=f"(d[18]), "=f"(d[19]), "=f"(d[20]), "=f"(d[21]), "=f"(d[22]), "=f"(d[23]), "=f"(d[24]), "=f"(d[25]), "=f"(d[26]), "=f"(d[27]), "=f"(d[28]), "=f"(d[29]), "=f"(d[30]), "=f"(d[31]), "=f"(d[32]), "=f"(d[33]), "=f"(d[34]), "=f"(d[35]), "=f"(d[36]), "=f"(d[37]), "=f"(d[38]), "=f"(d[39]), "=f"(d[40]), "=f"(d[41]), "=f"(d[42]), "=f"(d[43]), "=f"(d[44]), "=f"(d[45]), "=f"(d[46]), "=f"(d[47]), "=f"(d[48]), "=f"(d[49]), "=f"(d[50]), "=f"(d[51]), "=f"(d[52]), "=f"(d[53]), "=f"(d[54]), "=f"(d[55]), "=f"(d[56]), "=f"(d[57]), "=f"(d[58]), "=f"(d[59]), "=f"(d[60]), "=f"(d[61]), "=f"(d[62]), "=f"(d[63]), "=f"(d[64]), "=f"(d[65]), "=f"(d[66]), "=f"(d[67]), "=f"(d[68]), "=f"(d[69]), "=f"(d[70]), "=f"(d[71]), "=f"(d[72]), "=f"(d[73]), "=f"(d[74]), "=f"(d[75]), "=f"(d[76]), "=f"(d[77]), "=f"(d[78]), "=f"(d[79]), "=f"(d[80]), "=f"(d[81]), "=f"(d[82]), "=f"(d[83]), "=f"(d[84]), "=f"(d[85]), "=f"(d[86]), "=f"(d[87]), "=f"(d[88]), "=f"(d[89]), "=f"(d[90]), "=f"(d[91]), "=f"(d[92]), "=f"(d[93]), "=f"(d[94]), "=f"(d[95]), "=f"(d[96]), "=f"(d[97]), "=f"(d[98]), "=f"(d[99]), "=f"(d[100]), "=f"(d[101]), "=f"(d[102]), "=f"(d[103]), "=f"(d[104]), "=f"(d[105]), "=f"(d[106]), "=f"(d[107]), "=f"(d[108]), "=f"(d[109]), "=f"(d[110]), "=f"(d[111]), "=f"(d[112]), "=f"(d[113]), "=f"(d[114]), "=f"(d[115]), "=f"(d[116]), "=f"(d[117]), "=f"(d[118]), "=f"(d[119]), "=f"(d[120]), "=f"(d[121]), "=f"(d[122]), "=f"(d[123]), "=f"(d[124]), "=f"(d[125]), "=f"(d[126]), "=f"(d[127])
    : "r"(a0), "r"(a1), "r"(a2), "r"(a3), "l"(db), "n"(TB));
}
template <int TB>
__device__ __forceinline__ void wg_rs32_init(float (&d)[16], uint32_t a0, uint32_t a1, uint32_t a2, uint32_t a3, uint64_t db) {
  asm volatile(
    "wgmma.mma_async.sync.aligned.m64n32k16.f32.bf16.bf16 {%0, %1, %2, %3, %4, %5, %6, %7, %8, %9, %10, %11, %12, %13, %14, %15}, {%16, %17, %18, %19}, %20, 0, 1, 1, %21;"
    : "=f"(d[0]), "=f"(d[1]), "=f"(d[2]), "=f"(d[3]), "=f"(d[4]), "=f"(d[5]), "=f"(d[6]), "=f"(d[7]), "=f"(d[8]), "=f"(d[9]), "=f"(d[10]), "=f"(d[11]), "=f"(d[12]), "=f"(d[13]), "=f"(d[14]), "=f"(d[15])
    : "r"(a0), "r"(a1), "r"(a2), "r"(a3), "l"(db), "n"(TB));
}

constexpr int NST = 7, SLOT = 9216;
constexpr uint32_t SM_XN = 0, SM_HIN = 147456, SM_RING = 163840, SM_BAR = SM_RING + 7 * SLOT;
constexpr uint32_t SM_KD = SM_BAR + 256, SMEM_BYTES = SM_KD + 3840;
constexpr uint32_t B_FULL = 0, B_EMPTY = 56, B_XN = 112, B_K2048 = 176, B_HF = 184, B_HE = 200, B_CV = 216, B_PT = 224, B_YT = 232, B_SG = 240, B_X = 248;
constexpr uint32_t PR_LN = 65536, PR_PAR = 98304, PR_K0 = SM_HIN + 12288;
constexpr uint32_t T_U = 0, T_KP = 17408, T_K0 = 51200, T_X0 = 53248, T_X1 = SM_HIN + 4 * 18432, T_YT = 0, T_STG = 65536, T_PART = SM_HIN;
constexpr uint32_t U_BYTES = U_LEN * 2, KP_BYTES = KP_LEN * 4, IMG = 18432;

struct Params {
  CUtensorMap xn, gate, up, dn, dn5, dp, dp5, x, x5, y, y5, out, out5;
  const __nv_bfloat16 *xp, *logA, *Aim, *Cre, *Cim, *logdt, *Dsk;
};

__device__ __forceinline__ float us2f(uint32_t v) { return __uint_as_float(v << 16); }
struct KgIn { uint32_t la, ai, cr, ci, ldt, dsk; };
__device__ __forceinline__ void kgen_load(const Params& p, int ch0, int tid, KgIn& in) {
  const int e = ch0 * (NM_ / 2) + tid;
  in.la = __ldg((const uint32_t*)p.logA + e); in.ai = __ldg((const uint32_t*)p.Aim + e);
  in.cr = __ldg((const uint32_t*)p.Cre + e); in.ci = __ldg((const uint32_t*)p.Cim + e);
  in.ldt = __ldg((const unsigned short*)p.logdt + ch0 + (tid >> 6)); in.dsk = __ldg((const unsigned short*)p.Dsk + ch0 + (tid >> 6));
}
struct KgState { float acc[5][4]; float v; };
struct cf { float r, i; };
__device__ __forceinline__ cf cmul(cf a, cf b) { return {fmaf(a.r, b.r, -(a.i * b.i)), fmaf(a.r, b.i, a.i * b.r)}; }
__device__ __forceinline__ cf csq(cf a) { return {fmaf(a.r, a.r, -(a.i * a.i)), (a.r + a.r) * a.i}; }
__device__ __forceinline__ cf cexp2(float lm, float th) {
  float m; asm("ex2.approx.ftz.f32 %0, %1;" : "=f"(m) : "f"(lm));
  return {m * __cosf(th), m * __sinf(th)};
}
__device__ __forceinline__ float turns(float w) { return (w - rintf(w)) * 6.283185307179586f; }
__device__ __forceinline__ void kgen_params(unsigned char* sm, int tid, KgIn in, KgState& st) {
  const int warp = tid >> 5, lane = tid & 31;
  float4* par = (float4*)(sm + PR_PAR + warp * 6144) + lane;
  const float dt = bf_round(expf(bf_lo(in.ldt)));
  float v = 0.f;
#pragma unroll 1
  for (int r = 0; r < 2; r++) {
    const float x = -bf_round(expf(bf_lo(in.la))) * dt * 1.4426950408889634f;
    const float w = bf_lo(in.ai) * dt * 0.15915494309189535f;
    const cf c = {2.f * bf_lo(in.cr) * dt, 2.f * bf_lo(in.ci) * dt};
    const cf e2 = cexp2(2.f * x, turns(2.f * w)), e64 = cexp2(64.f * x, turns(64.f * w));
    const cf e4 = csq(e2), e6 = cmul(e2, e4), e128 = csq(e64), e256 = csq(e128), e512 = csq(e256), e1024 = csq(e512);
    const cf c1 = cmul(c, e128), c256 = cmul(c, e256), c512 = cmul(c, e512), c4 = cmul(c, e1024);
    const cf c516 = cmul(c512, e4), c258 = cmul(c256, e2), c260 = cmul(c256, e4), c262 = cmul(c256, e6);
    v += fmaf(c4.r, e1024.r, -(c4.i * e1024.i));
    par[0] = make_float4(x, turns(w), turns(8.f * w), turns(128.f * w));
    par[64] = make_float4(c.r, c.i, c1.r, c1.i);
    par[128] = make_float4(c4.r, c4.i, e64.r, e64.i);
    par[192] = make_float4(c512.r, c512.i, c516.r, c516.i);
    par[256] = make_float4(c256.r, c256.i, c258.r, c258.i);
    par[320] = make_float4(c260.r, c260.i, c262.r, c262.i);
    par += 32;
    in.la >>= 16; in.ai >>= 16; in.cr >>= 16; in.ci >>= 16;
  }
#pragma unroll
  for (int o = 16; o; o >>= 1) v += __shfl_xor_sync(0xffffffffu, v, o);
  __syncwarp();
#pragma unroll
  for (int t = 0; t < 5; t++) { st.acc[t][0] = st.acc[t][1] = st.acc[t][2] = st.acc[t][3] = 0.f; }
  if (lane == 0 && !(warp & 1)) st.acc[0][0] = bf_lo(in.dsk);
  st.v = v;
}
__device__ __forceinline__ void kgen_steps(unsigned char* sm, int tid, KgState& st) {
  const int warp = tid >> 5, lane = tid & 31, g = lane >> 2, q = lane & 3;
  const float4* par = (const float4*)(sm + PR_PAR + warp * 6144) + q;
  const float2* p3 = (const float2*)(par + 192) + (g & 1);
  const float2* p2 = (const float2*)(par + 256 + 64 * ((g >> 1) & 1)) + (g & 1);
  const float g1 = (float)g, g8 = 8.f * g1, g128 = 128.f * g1;
  const int l1 = 4 * (g >> 1) + q, l2 = 4 * (g >> 2) + q;
#pragma unroll 4
  for (int ks = 0; ks < 16; ks++) {
    const float4 P = par[4 * ks], Q = par[64 + 4 * ks], R = par[128 + 4 * ks];
    const float2 c3 = p3[8 * ks], c2 = p2[8 * ks];
    const cf e = cexp2(P.x * g1, P.y * g1), a1 = cexp2(P.x * g8, P.z * g1), t = cexp2(P.x * g128, P.w * g1);
    const cf a2 = cmul(a1, cf{R.z, R.w});
    const cf t1 = {__shfl_sync(0xffffffffu, t.r, l1), __shfl_sync(0xffffffffu, t.i, l1)};
    const cf t2 = {__shfl_sync(0xffffffffu, t.r, l2), __shfl_sync(0xffffffffu, t.i, l2)};
    auto mma = [&](float (&d)[4], cf u, float cr, float ci) {
      const float b0 = fmaf(u.r, cr, -(u.i * ci)), b1 = fmaf(-u.r, ci, -(u.i * cr));
      asm("mma.sync.aligned.m16n8k8.row.col.f32.tf32.tf32.f32 {%0,%1,%2,%3}, {%4,%5,%6,%7}, {%8,%9}, {%0,%1,%2,%3};"
          : "+f"(d[0]), "+f"(d[1]), "+f"(d[2]), "+f"(d[3])
          : "r"(__float_as_uint(a1.r)), "r"(__float_as_uint(a2.r)), "r"(__float_as_uint(a1.i)), "r"(__float_as_uint(a2.i)),
            "r"(__float_as_uint(b0)), "r"(__float_as_uint(b1)));
    };
    mma(st.acc[0], e, Q.x, Q.y);
    mma(st.acc[1], e, Q.z, Q.w);
    mma(st.acc[4], t, R.x, R.y);
    mma(st.acc[2], t2, c2.x, c2.y);
    mma(st.acc[3], t1, c3.x, c3.y);
  }
}
__device__ __forceinline__ void kgen_finish(unsigned char* sm, unsigned short* kd, unsigned short* k2048, int tid, KgState& st) {
  const int warp = tid >> 5, lane = tid & 31, g = lane >> 2, q = lane & 3;
  float4* red = (float4*)(sm + SM_HIN + (warp >> 1) * 3072) + lane;
  if (warp & 1) {
#pragma unroll
    for (int t = 0; t < 5; t++) red[t * 32] = make_float4(st.acc[t][0], st.acc[t][1], st.acc[t][2], st.acc[t][3]);
    red[160].x = st.v;
  }
  named_bar(3, 256);
  if (!(warp & 1)) {
    uint32_t lo[5], hi[5];
#pragma unroll
    for (int t = 0; t < 5; t++) {
      const float4 r = red[t * 32];
      lo[t] = pack_bf16(st.acc[t][0] + r.x, st.acc[t][1] + r.y); hi[t] = pack_bf16(st.acc[t][2] + r.z, st.acc[t][3] + r.w);
    }
    *k2048 = (unsigned short)pack_bf16(st.v + red[160].x, 0.f);
    uint32_t* kw = (uint32_t*)kd;
    kw[lane] = lo[0]; kw[32 + lane] = hi[0]; kw[64 + lane] = lo[1]; kw[96 + lane] = hi[1];
    kw[128 + 2 * g + (q & 1) + 32 * (q >> 1)] = lo[2]; kw[144 + 2 * g + (q & 1) + 32 * (q >> 1)] = hi[2];
    kw[192 + g + 16 * q] = lo[3]; kw[200 + g + 16 * q] = hi[3];
    kd[512 + g + 32 * q] = (unsigned short)lo[4]; kd[528 + g + 32 * q] = (unsigned short)(lo[4] >> 16);
    kd[520 + g + 32 * q] = (unsigned short)hi[4]; kd[536 + g + 32 * q] = (unsigned short)(hi[4] >> 16);
  }
}
constexpr int kd_index(int l) {
  if (l < 256) return l;
  const int sh = l < 512 ? 1 : l < 1024 ? 2 : 3;
  return ((l + (1 << (sh - 1)) - 1 + ((l >> sh) & 1)) >> sh) + 128 * sh;
}
struct KTab { unsigned int e[512 * 4]; };
constexpr KTab make_ktab() {
  KTab t = {};
  for (int it = 0; it < 511; it++) {
    const int l0 = 4 * it, b1 = kd_index(l0) & ~1;
    const unsigned int np = 0x54 + 0x22 * (l0 ? kd_index(l0 - 1) - b1 : 0);
    unsigned int n[4] = {0, 0, 0, 0};
    for (int k = 0; k < 4; k++) n[k] = 0x10 + 0x22 * (kd_index(l0 + k) - b1);
    t.e[4 * it] = 2 * b1 | ((b1 < 638 ? 4u : 0u) << 16);
    t.e[4 * it + 1] = (n[0] + 0x44) | (np << 8) | (n[1] << 16) | (n[0] << 24);
    t.e[4 * it + 2] = n[2] | (n[1] << 8) | (n[3] << 16) | (n[2] << 24);
    t.e[4 * it + 3] = l0 ? 0xffffffffu : 0xffffu;
  }
  return t;
}
__device__ __align__(16) const KTab g_ktab = make_ktab();
template <int NT>
__device__ __forceinline__ void kexpand(uint32_t sb, uint32_t k0, uint32_t k1, uint32_t k2048, int tid, uint4 e) {
#pragma unroll 1
  for (int it = tid; it < 511; it += NT) {
    const uint4 en = __ldg((const uint4*)g_ktab.e + min(it + NT, 511));
    const uint32_t o = e.x & 0xffffu, o2 = o + (e.x >> 16), dst = sb + T_KP + 64 + 16 * it;
#pragma unroll
    for (int c = 0; c < 4; c++) {
      const uint32_t a = c ? k1 + 1280 * (c - 1) : k0;
      const uint32_t x0 = lds32(a + o - 4), x1 = lds32(a + o), x2 = lds32(a + o2);
      sts128(dst + c * KP_BYTES, make_uint4(__byte_perm(x0, x1, e.y) & e.w, __byte_perm(x1, x2, e.y >> 16), __byte_perm(x1, x2, e.z), __byte_perm(x1, x2, e.z >> 16)));
    }
    e = en;
  }
  if (tid < 36) {
    const int c = tid / 9, i = tid - 9 * c;
    uint4 v = make_uint4(0u, 0u, 0u, 0u);
    if (i == 4) {
      uint32_t z, y;
      asm volatile("ld.shared.u16 %0, [%1];" : "=r"(z) : "r"(k2048 + 2 * c) : "memory");
      asm volatile("ld.shared.u16 %0, [%1];" : "=r"(y) : "r"((c ? k1 + 1280 * (c - 1) : k0) + 1278) : "memory");
      v = make_uint4(z | (y << 16), z * 0x10001u, z * 0x10001u, z * 0x10001u);
    }
    sts128(sb + T_KP + c * KP_BYTES + 16 * (i < 4 ? i : 511 + i), v);
  }
  if (tid < 64) sts128(sb + T_U + (tid >> 4) * U_BYTES + (tid & 15) * 16, make_uint4(0u, 0u, 0u, 0u));
  fence_async_smem();
}

template <int NR>
__device__ __forceinline__ void conv_mma(float (&d)[NR], const uint32_t* a, uint64_t db) {
  if constexpr (NR == 64) wg_cv128<0>(d, a[0], a[1], a[2], a[3], db);
  else if constexpr (NR == 48) wg_cv96<0>(d, a[0], a[1], a[2], a[3], db);
  else if constexpr (NR == 32) wg_cv64<0>(d, a[0], a[1], a[2], a[3], db);
  else wg_rs32<0>(d, a[0], a[1], a[2], a[3], db);
}
__device__ __forceinline__ void conv_load(uint32_t (&a)[8], uint32_t o) {
#pragma unroll
  for (int c = 0; c < 2; c++) {
    a[4 * c + 0] = lds32(o + c * KP_BYTES); a[4 * c + 1] = lds32(o + c * KP_BYTES + 512);
    a[4 * c + 2] = lds32(o + c * KP_BYTES - 32); a[4 * c + 3] = lds32(o + c * KP_BYTES + 480);
  }
}
template <int NR>
__device__ __forceinline__ void conv_phase(float (&dA)[NR], float (&dB)[NR], uint32_t (&a)[4][8], uint32_t kp, uint64_t dU) {
#pragma unroll 1
  for (int i = 0; i < 2; i++) {
#pragma unroll
    for (int k = 0; k < 4; k++) {
      wg_fence();
      conv_mma<NR>(dA, a[k], dU - 2 * k); conv_mma<NR>(dB, a[k] + 4, dU - 2 * k + (U_BYTES >> 4));
      wg_commit();
      wg_wait<1>();
      if (k == 2 && i) kp += 64 * 24;
      conv_load(a[(k + 2) & 3], kp + 64 * (k + 2));
    }
    kp += 256;
    dU -= 8;
  }
  wg_wait<0>();
  reg_fence(dA); reg_fence(dB);
}
template <int NR>
__device__ __forceinline__ void upper_copy(float (&dst)[NR - 16], const float (&src)[NR]) {
#pragma unroll
  for (int i = 0; i < NR - 16; i++) asm volatile("mov.b32 %0, %1;" : "=f"(dst[i]) : "f"(src[i + 16]));
}
__device__ __forceinline__ void conv2(uint32_t sb, int wg, int w, int lane) {
  const int g = lane >> 2, q = lane & 3;
  float dA[64], dB[64];
  uint32_t a[4][8];
  const uint32_t kp = sb + T_KP + 2 * wg * KP_BYTES + 4 * (16 + 256 * (w >> 1) + 8 * (w & 1) + g - 2 * q);
  const uint64_t dU = mk_desc(sb + T_U + 2 * wg * U_BYTES + 256, 16, 256, 3);
#pragma unroll
  for (int i = 0; i < 64; i++) { dA[i] = 0.f; dB[i] = 0.f; }
  conv_load(a[0], kp); conv_load(a[1], kp + 64);
  conv_phase<64>(dA, dB, a, kp, dU);
  float eA[48], eB[48];
  upper_copy<64>(eA, dA); upper_copy<64>(eB, dB);
  conv_phase<48>(eA, eB, a, kp + 2048, dU);
  float fA[32], fB[32];
  upper_copy<48>(fA, eA); upper_copy<48>(fB, eB);
  conv_phase<32>(fA, fB, a, kp + 4096, dU);
  float gA[16], gB[16];
  upper_copy<32>(gA, fA); upper_copy<32>(gB, fB);
  conv_phase<16>(gA, gB, a, kp + 6144, dU);
#pragma unroll
  for (int i = 0; i < 16; i++) {
    dA[16 + i] = eA[i]; dA[32 + i] = fA[i]; dA[48 + i] = gA[i];
    dB[16 + i] = eB[i]; dB[32 + i] = fB[i]; dB[48 + i] = gB[i];
  }
  PROF_T(53);
  float z[2][16][2];
#pragma unroll
  for (int m = 0; m < 16; m++)
#pragma unroll
    for (int e = 0; e < 2; e++) {
      z[0][m][e] = m ? dA[4 * m + e] + dA[4 * m - 2 + e] : dA[e];
      z[1][m][e] = m ? dB[4 * m + e] + dB[4 * m - 2 + e] : dB[e];
    }
  const uint32_t xb = sb + T_X0 + wg * 8192, xc = wg ? T_X1 - T_X0 - 8192 : 4096;
  const uint32_t xw = xb + (w * 32 + lane) * 16, xr = xb + ((w ^ 2) * 32 + lane) * 16;
  float k[2][8][2];
  if (w < 2) {
#pragma unroll
    for (int c = 0; c < 2; c++)
#pragma unroll
      for (int m = 0; m < 8; m += 4) {
        sts128(xw + c * xc + (m >> 2) * 2048, make_uint4(pack_bf16(z[c][8 + m][0], z[c][8 + m][1]), pack_bf16(z[c][9 + m][0], z[c][9 + m][1]),
                                                          pack_bf16(z[c][10 + m][0], z[c][10 + m][1]), pack_bf16(z[c][11 + m][0], z[c][11 + m][1])));
#pragma unroll
        for (int i = 0; i < 4; i++) { k[c][m + i][0] = z[c][m + i][0]; k[c][m + i][1] = z[c][m + i][1]; }
      }
  } else {
#pragma unroll
    for (int c = 0; c < 2; c++)
#pragma unroll
      for (int m = 0; m < 8; m += 4) {
        sts128(xw + c * xc + (m >> 2) * 2048, make_uint4(m ? pack_bf16(z[c][m - 2][0], z[c][m - 2][1]) : 0u, m ? pack_bf16(z[c][m - 1][0], z[c][m - 1][1]) : 0u,
                                                          pack_bf16(z[c][m][0], z[c][m][1]), pack_bf16(z[c][m + 1][0], z[c][m + 1][1])));
#pragma unroll
        for (int i = 0; i < 4; i++) { k[c][m + i][0] = z[c][6 + m + i][0]; k[c][m + i][1] = z[c][6 + m + i][1]; }
      }
  }
  named_bar(1 + wg, 128);
  const uint32_t yb = sb + T_U + 2 * wg * U_BYTES;
#pragma unroll
  for (int c = 0; c < 2; c++)
#pragma unroll
    for (int m = 0; m < 8; m += 4) {
      const uint4 u = lds128(xr + c * xc + (m >> 2) * 2048);
      stmatrix_x4_t(yb + c * 4096 + (64 * (w >> 1) + 8 * m + lane) * 32 + 16 * (w & 1),
                    pack_bf16(k[c][m][0] + bf_lo(u.x), k[c][m][1] + bf_hi(u.x)), pack_bf16(k[c][m + 1][0] + bf_lo(u.y), k[c][m + 1][1] + bf_hi(u.y)),
                    pack_bf16(k[c][m + 2][0] + bf_lo(u.z), k[c][m + 2][1] + bf_hi(u.z)), pack_bf16(k[c][m + 3][0] + bf_lo(u.w), k[c][m + 3][1] + bf_hi(u.w)));
    }
  fence_async_smem();
  named_arrive(10 + wg, 160);
}
__device__ __forceinline__ void conv_ship(uint32_t sb, uint32_t bar, int wg, int ch, int cnt, bool el) {
  named_bar(10 + wg, 160);
  if (el) {
    bulk_s2g(g_y + (size_t)ch * L_, sb + T_U + 2 * wg * U_BYTES, 8192);
    bulk_commit_wait();
    cnt_add_done(cnt);
    mbar_arrive(bar + B_SG);
  }
  __syncwarp();
}

__global__ void __cluster_dims__(2, 1, 1) __launch_bounds__(384, 1) fused_kernel(const __grid_constant__ Params p) {
  extern __shared__ __align__(1024) unsigned char smem_raw[];
  const uint32_t sb = smem_u32(smem_raw);
  const uint32_t bar = sb + SM_BAR;
  const uint32_t vb = blockIdx.x;
  const int j = vb & 1, pair = vb >> 1, mt = pair & 15, sp = pair >> 4;
  const bool spare = pair >= 64;
  const int warp = __shfl_sync(0xffffffffu, threadIdx.x >> 5, 0), wg = warp >> 2, w = warp & 3;
  const int row0 = mt * 128 + (2 * sp + j) * 16;
  const int f0 = sp * 1152;
  const long long t_start = clock64();
  KgIn kin;
  if (wg < 2) kgen_load(p, spare ? 512 + ((int)vb - 128) * 16 : vb * 4, threadIdx.x, kin);
  if (threadIdx.x >= 288 && threadIdx.x < 301) prefetch_map(&p.xn + (threadIdx.x - 288));
  if (threadIdx.x == 256) {
    mbar_init(bar + B_X, 1);
    if (!spare) {
      mbar_expect_tx(bar + B_X, 16 * D_ * 2);
      bulk_g2s(sb + PR_LN, p.xp + (size_t)row0 * D_, 16 * D_ * 2, bar + B_X);
    }
#pragma unroll
    for (int i = 0; i < 30; i++) if (i != 22) mbar_init(bar + 8 * i, (i >= 7 && i < 14) ? 8 : (i == 27 && !spare) ? 4 : 1);
    mbar_init(bar + B_SG, 2);
    mbar_expect_tx(bar + B_HF, 8192); mbar_expect_tx(bar + B_HF + 8, 8192);
    asm volatile("fence.mbarrier_init.release.cluster;" ::: "memory");
  }
  __syncthreads();
  asm volatile("barrier.cluster.arrive.relaxed.aligned;" ::: "memory");

  if (wg == 2) {
    const int t = threadIdx.x & 127, lane = t & 31;
    const bool el = elect_one();
    if (!spare) {
      const uint32_t ra = sb + PR_LN + (t >> 3) * (D_ * 2) + (t & 7) * 16;
      if (w == 1 && el) {
#pragma unroll 1
        for (int u = 0; u < NST; u++) {
          const uint32_t dst = sb + SM_RING + u * SLOT, fb = bar + B_FULL + 8 * u;
          mbar_expect_tx(fb, 8192);
          tma_2d(dst, &p.gate, f0 + 64 * j, 32 * u, fb);
          tma_2d(dst + 4096, &p.up, f0 + 64 * j, 32 * u, fb);
        }
      }
      mbar_wait(bar + B_X, 0);
      PROF_T(61);
      uint4 v[9];
#pragma unroll
      for (int i = 0; i < 9; i++) v[i] = lds128(ra + i * 128);
      uint32_t* u = (uint32_t*)v;
      const float x0 = bf_lo(__shfl_sync(0xffffffffu, u[0], lane & 24));
      float s = 0.f, s2 = 0.f, q = 0.f, q2 = 0.f;
#pragma unroll
      for (int i = 0; i < 36; i++) {
        const float a = bf_lo(u[i]) - x0, b = bf_hi(u[i]) - x0;
        s += a; s2 += b; q = fmaf(a, a, q); q2 = fmaf(b, b, q2);
      }
      s += s2; q += q2;
#pragma unroll
      for (int o = 4; o; o >>= 1) { s += __shfl_xor_sync(0xffffffffu, s, o); q += __shfl_xor_sync(0xffffffffu, q, o); }
      s *= (1.0f / D_);
      const __nv_bfloat162 mb = __float2bfloat162_rn(s + x0);
      const float rinv = 1.0f / bf_round(sqrtf(bf_round(bf_round(fmaxf(fmaf(-s, s, q * (1.0f / D_)), 0.f)) + 1e-5f)));
#pragma unroll
      for (int i = 0; i < 36; i++) {
        const __nv_bfloat162 d2 = __hsub2(*(const __nv_bfloat162*)&u[i], mb);
        const uint32_t d = *(const uint32_t*)&d2;
        u[i] = pack_bf16(bf_lo(d) * rinv, bf_hi(d) * rinv);
      }
#pragma unroll
      for (int i = 0; i < 9; i++) sts128(ra + i * 128, v[i]);
      fence_async_smem();
      named_bar(5, 128);
      PROF_T(62);
      if (w == 0 && el) bulk_s2g(g_xn + (size_t)row0 * D_, sb + PR_LN, 16 * D_ * 2);
    }
    asm volatile("barrier.cluster.wait.aligned;" ::: "memory");
    asm volatile("setmaxnreg.dec.sync.aligned.u32 24;");
    if (w == 0) {
      if (!spare) {
        if (el) {
          bulk_commit_wait();
          cnt_add_done(C_LN + mt);
        }
        __syncwarp();
        PROF_T(63);
        cnt_wait(C_LN + mt, 8);
        PROF_T(67);
        fence_async_all();
#pragma unroll 1
        for (int kb = 0; kb < 6; kb++) {
          if (el) {
            mbar_expect_tx(bar + B_XN + 8 * kb, 16384);
            tma_2d(sb + SM_XN + kb * 16384, &p.xn, kb * 64, mt * 128, bar + B_XN + 8 * kb);
          }
        }
        named_bar(4, 384);
        PROF_T(69);
        uint32_t slot = 0, ph = 0;
#pragma unroll 1
        for (int c = 0; c <= 9; c++) {
          const int fc = f0 + c * 128;
          if (c < 9) {
            for (int u = c ? 0 : NST; u < 18; u++) {
              mbar_wait(bar + B_EMPTY + 8 * slot, ph);
              if (el) {
                const uint32_t dst = sb + SM_RING + slot * SLOT, fb = bar + B_FULL + 8 * slot;
                mbar_expect_tx(fb, 8192);
                tma_2d(dst, &p.gate, fc + 64 * j, 32 * u, fb);
                tma_2d(dst + 4096, &p.up, fc + 64 * j, 32 * u, fb);
                if (c == 0 && u < 10) {
                  const int kb = u - 1;
                  if (kb < 8) mbar_expect_tx(bar + B_XN + 8 * kb, kb < 7 ? 16384 : 32768);
                  tma_2d(sb + SM_XN + kb * 16384, &p.xn, kb * 64, mt * 128, bar + B_XN + 8 * min(kb, 7));
                }
              }
              if (++slot == NST) { slot = 0; ph ^= 1; }
            }
          }
          const int fp = (fc - 128 + 64 * (1 - j)) >> 3, fo = fc + 64 * j;
#pragma unroll
          for (int i = 0; i < 8; i++) {
            const bool isP = i < 4;
            const int u = i & 3;
            if (isP ? (c == 0) : (c == 9)) continue;
            mbar_wait(bar + B_EMPTY + 8 * slot, ph);
            if (el) {
              const uint32_t dst = sb + SM_RING + slot * SLOT, fb = bar + B_FULL + 8 * slot;
              mbar_expect_tx(fb, 9216);
              if (isP) {
                tma_5d(dst, &p.dp, 0, 0, fp + 4 * (u >> 1), 2 * (u & 1), 4 * j, fb);
                tma_4d(dst + 8192, &p.dp5, 512 + 32 * j, 0, fp + 4 * (u >> 1), 2 * (u & 1), fb);
              } else {
                tma_3d(dst, &p.dn, 0, fo + 16 * u, 4 * j, fb);
                tma_2d(dst + 8192, &p.dn5, 512 + 32 * j, fo + 16 * u, fb);
              }
            }
            if (++slot == NST) { slot = 0; ph ^= 1; }
          }
        }
        const int ch0 = vb * 4;
        cnt_wait(C_U, 384);
        fence_async_all();
        if (el) {
          mbar_expect_tx(bar + B_CV, 4 * L_ * 2);
#pragma unroll 1
          for (int c = 0; c < 4; c++) bulk_g2s(sb + T_U + c * U_BYTES + 256, g_u + (size_t)(ch0 + c) * L_, L_ * 2, bar + B_CV);
        }
        unsigned char* img = g_part + (size_t)(2 * mt + j) * 16 * IMG;
        mbar_wait(bar + B_SG, 0);
        PROF_T(71);
        if (lane < 6) {
          const int r = (sp + 1 + (lane >> 1)) & 3;
          if (lane & 1) bulk_s2g(img + (r * 4 + sp) * IMG + 16384, sb + T_STG + 65536 + (r >> 1) * 8192 + (r & 1) * 2048, 2048);
          else bulk_s2g(img + (r * 4 + sp) * IMG, sb + T_STG + r * 16384, 16384);
          bulk_commit_wait();
        } else if (lane == 6) {
          mbar_expect_tx(bar + B_PT, 3 * IMG);
          mbar_expect_tx(bar + B_X, IMG);
          tma_2d(sb + T_PART + 3 * IMG, &p.x, 256 * j + 64 * sp, mt * 128, bar + B_X);
          tma_2d(sb + T_PART + 3 * IMG + 16384, &p.x5, 512 + 32 * j, mt * 128 + 32 * sp, bar + B_X);
        }
        __syncwarp();
        PROF_T(72);
        if (el) cnt_add_done(C_PART + 2 * mt + j);
        cnt_wait(C_PART + 2 * mt + j, 4);
        fence_async_all();
        PROF_T(74);
        if (lane < 3) bulk_g2s(sb + T_PART + lane * IMG, img + (sp * 4 + ((sp + 1 + lane) & 3)) * IMG, IMG, bar + B_PT);
        cnt_wait(C_Y5, 32);
        mbar_wait(bar + B_SG, 1);
        if (el) {
          mbar_expect_tx(bar + B_YT, IMG);
          tma_2d(sb + T_YT + 16384, &p.y5, mt * 128 + 32 * sp, 512 + 32 * j, bar + B_YT);
        }
        cnt_wait(C_Y + 4 * j + sp, 32);
        PROF_T(75);
        fence_async_all();
        if (el) {
          tma_2d(sb + T_YT, &p.y, mt * 128, 256 * j + 64 * sp, bar + B_YT);
          tma_2d(sb + T_YT + 8192, &p.y, mt * 128 + 64, 256 * j + 64 * sp, bar + B_YT);
        }
      } else {
        named_bar(7, 288);
        cnt_wait(C_U, 384);
        fence_async_all();
#pragma unroll 1
        for (int grp = 0; grp < 4; grp++) {
          const int ch0 = 512 + ((int)vb - 128) * 16 + grp * 4;
          if (grp) mbar_wait(bar + B_SG, (grp - 1) & 1);
          if (el) {
            mbar_expect_tx(bar + B_CV, 4 * L_ * 2);
#pragma unroll 1
            for (int c = 0; c < 4; c++) bulk_g2s(sb + T_U + c * U_BYTES + 256, g_u + (size_t)(ch0 + c) * L_, L_ * 2, bar + B_CV);
          }
        }
      }
      PROF_T(79);
      unsigned int old = 0;
      if (el) old = atomicAdd(g_cnt + C_DONE * 32, 1u) + 1;
      if (__any_sync(0xffffffffu, old == gridDim.x)) { g_cnt[lane * 32] = 0u; g_cnt[(lane + 32) * 32] = 0u; }
    } else {
      if (!spare) {
        named_bar(4, 384);
        uint4 k0v = make_uint4(0u, 0u, 0u, 0u);
        if (t < 112) k0v = lds128(sb + PR_K0 + (t - 32) * 16);
        named_bar(8, 96);
        if (t == 32) { mbar_arrive_remote(mapa(bar + B_HE, j ^ 1)); mbar_arrive_remote(mapa(bar + B_HE + 8, j ^ 1)); }
#pragma unroll 1
        for (int i = 0; i < 8; i++) mbar_wait(bar + B_XN + 8 * i, 0);
        const int tok = 8 * ((lane & 7) >> 1) + 2 * (lane >> 3) + (lane & 1);
#pragma unroll 1
        for (int it = w - 1; it < 36; it += 3) {
          const int oc = 9 * (2 * sp + j) + (it >> 2), tg = it & 3;
          uint4 v;
          ldmatrix_x4_t(sb + SM_XN + (oc >> 3) * 16384 + (32 * tg + tok) * 128 + (((oc ^ tok) & 7) << 4), v.x, v.y, v.z, v.w);
          ((uint4*)(g_u + (size_t)(8 * oc + (lane >> 2)) * L_ + mt * 128))[(4 * tg + (lane & 3)) ^ (tg >> 1)] = v;
        }
        __syncwarp();
        if (lane == 0) { fence_async_all(); cnt_add(C_U); }
        const uint4 e0 = __ldg((const uint4*)g_ktab.e + (t - 32));
        named_bar(9, 352);
        if (t < 112) sts128(sb + T_K0 + (t - 32) * 16, k0v);
        named_bar(8, 96);
        kexpand<96>(sb, sb + T_K0, sb + SM_KD, bar + B_K2048, t - 32, e0);
        __syncwarp();
        if (lane == 0) mbar_arrive(bar + B_CV);
        if (w < 3) conv_ship(sb, bar, w - 1, vb * 4 + 2 * (w - 1), C_Y + (vb >> 4), el);
      } else if (w < 3) {
#pragma unroll 1
        for (int grp = 0; grp < 4; grp++) conv_ship(sb, bar, w - 1, 512 + ((int)vb - 128) * 16 + grp * 4 + 2 * (w - 1), C_Y5, el);
      }
    }
  } else {
    const int t = threadIdx.x & 127, lane = t & 31;
    KgState kst;
    kgen_params(smem_raw, threadIdx.x, kin, kst);
    if (!spare) {
      PROF_T(60);
      kgen_steps(smem_raw, threadIdx.x, kst);
      PROF_T(51);
      kgen_finish(smem_raw, (unsigned short*)(smem_raw + (warp < 2 ? PR_K0 : SM_KD + ((warp >> 1) - 1) * 1280)),
                  (unsigned short*)(smem_raw + SM_BAR + B_K2048) + (warp >> 1), threadIdx.x, kst);
      named_arrive(4, 384);
    } else {
      const int c0 = 512 + ((int)vb - 128) * 16;
#pragma unroll 1
      for (int grp = 0; grp < 4; grp++) {
        if (grp) { kgen_load(p, c0 + grp * 4, threadIdx.x, kin); kgen_params(smem_raw, threadIdx.x, kin, kst); }
        kgen_steps(smem_raw, threadIdx.x, kst);
        kgen_finish(smem_raw, (unsigned short*)(smem_raw + SM_RING + (grp * 4 + (warp >> 1)) * 1280),
                    (unsigned short*)(smem_raw + SM_KD) + grp * 4 + (warp >> 1), threadIdx.x, kst);
        named_bar(3, 256);
      }
      named_arrive(7, 288);
    }
    PROF_T(41);
    asm volatile("barrier.cluster.wait.aligned;" ::: "memory");
    asm volatile("setmaxnreg.inc.sync.aligned.u32 240;");
    if (!spare) {
      const bool leader = (t == 0);
      float O1[128], O2[16];
      uint32_t slot = 0, ph = 0, prev = 0;
      const uint32_t hin = sb + SM_HIN + wg * 8192;
      const uint32_t r_hin = mapa(hin + (16 * w + (lane >> 2)) * 128 + (((lane & 3) ^ (lane >> 2)) << 4), j ^ 1);
      const uint32_t r_hf = mapa(bar + B_HF + 8 * wg, j ^ 1), r_he = mapa(bar + B_HE + 8 * wg, j ^ 1);
      const uint64_t dA0 = mk_desc(sb + SM_XN + wg * 8192, 16, 1024, 1);
      const uint64_t dH0 = mk_desc(hin, 16, 1024, 1);
      const uint64_t dG0 = mk_desc(sb + SM_RING, 4096, 1024, 1);
      const uint64_t dW0 = mk_desc(sb + SM_RING, 2048, 1024, 1);
      const uint64_t dX0 = mk_desc(sb + SM_RING + 8192, 512, 512, 2);
      auto adv = [&]() { prev = slot; if (++slot == NST) { slot = 0; ph ^= 1; } };
      auto release = [&](uint32_t s) { if (lane == 0) mbar_arrive(bar + B_EMPTY + 8 * s); };
      auto peer_begin = [&](int cp) {
        mbar_wait(bar + B_HF + 8 * wg, cp & 1);
        if (leader && cp < 8) mbar_expect_tx(bar + B_HF + 8 * wg, 8192);
        fence_async_smem();
      };
      auto peer_unit = [&](int u) {
        wg_fence();
        wg_ss256<1>(O1, dH0 + 2 * u, dW0 + (uint64_t)(slot * (SLOT >> 4)));
        wg_ss32<1>(O2, dH0 + 2 * u, dX0 + (uint64_t)(slot * (SLOT >> 4)));
        wg_commit();
      };
      auto chunk = [&](auto first_c, const int c) {
        constexpr bool FIRST = decltype(first_c)::value;
        float S[64];
        {
          if (FIRST) mbar_wait(bar + B_XN, 0);
          mbar_wait(bar + B_FULL + 8 * slot, ph);
          if (FIRST) { PROF_T(42); PROF_G(2); }
          const uint64_t db = dG0 + (uint64_t)(slot * (SLOT >> 4));
          wg_fence();
          wg_ss128_init<1>(S, dA0, db);
          wg_ss128<1>(S, dA0 + 2, db + 128);
          wg_commit();
          adv();
        }
#pragma unroll 1
        for (int u = 1; u < 18; u++) {
          if (FIRST && !(u & 1) && u < 16) mbar_wait(bar + B_XN + 8 * (u >> 1), 0);
          mbar_wait(bar + B_FULL + 8 * slot, ph);
          const uint64_t da = dA0 + (uint64_t)((u >> 1) * 1024 + (u & 1) * 4);
          const uint64_t db = dG0 + (uint64_t)(slot * (SLOT >> 4));
          wg_fence();
          wg_ss128<1>(S, da, db);
          wg_ss128<1>(S, da + 2, db + 128);
          wg_commit();
          if constexpr (!FIRST) { if (u == 12) peer_begin(c - 1); }
          wg_wait<1>();
          release(prev);
          if (c == 8 && u == 8) named_arrive(9, 352);
          adv();
        }
        uint32_t H[16];
        if constexpr (FIRST) { wg_wait<0>(); release(prev); }
        uint32_t rs = prev;
        auto rel_next = [&]() { release(rs); if (++rs == NST) rs = 0; };
        auto P = [&](int u) {
          mbar_wait(bar + B_FULL + 8 * slot, ph);
          peer_unit(u);
          if (u) { wg_wait<2>(); rel_next(); }
          adv();
        };
        auto E = [&](int u) {
#pragma unroll
          for (int i = 8 * u; i < 8 * u + 8; i++) asm volatile("" : "+f"(S[i]), "+f"(S[32 + i])::"memory");
#pragma unroll
          for (int g = 2 * u; g < 2 * u + 2; g++) {
            H[2 * g] = pack_bf16(geglu(S[4 * g], S[32 + 4 * g]), geglu(S[4 * g + 1], S[33 + 4 * g]));
            H[2 * g + 1] = pack_bf16(geglu(S[4 * g + 2], S[34 + 4 * g]), geglu(S[4 * g + 3], S[35 + 4 * g]));
          }
#pragma unroll
          for (int i = 4 * u; i < 4 * u + 4; i++) asm volatile("" : "+r"(H[i])::"memory");
        };
        auto O = [&](int u) {
          mbar_wait(bar + B_FULL + 8 * slot, ph);
          wg_fence();
          if (FIRST && u == 0) {
            wg_rs256_init<1>(O1, H[0], H[1], H[2], H[3], dW0 + (uint64_t)(slot * (SLOT >> 4)));
            wg_rs32_init<1>(O2, H[0], H[1], H[2], H[3], dX0 + (uint64_t)(slot * (SLOT >> 4)));
            rs = slot;
          } else {
            wg_rs256<1>(O1, H[4 * u], H[4 * u + 1], H[4 * u + 2], H[4 * u + 3], dW0 + (uint64_t)(slot * (SLOT >> 4)));
            wg_rs32<1>(O2, H[4 * u], H[4 * u + 1], H[4 * u + 2], H[4 * u + 3], dX0 + (uint64_t)(slot * (SLOT >> 4)));
          }
          wg_commit();
          if (u == 3) {
            mbar_wait(bar + B_HE + 8 * wg, c & 1);
            st_async_v4(r_hin, H[0], H[2], H[4], H[6], r_hf);
            st_async_v4(r_hin ^ 64, H[8], H[10], H[12], H[14], r_hf);
            st_async_v4(r_hin + 1024, H[1], H[3], H[5], H[7], r_hf);
            st_async_v4((r_hin ^ 64) + 1024, H[9], H[11], H[13], H[15], r_hf);
          }
          if (!FIRST || u >= 2) { wg_wait<2>(); rel_next(); }
          if (u == 1) { if constexpr (!FIRST) { if (leader) mbar_arrive_remote(r_he); } }
          if (u == 3) { wg_wait<1>(); rel_next(); wg_wait<0>(); rel_next(); }
          adv();
        };
        if constexpr (FIRST) { E(0); O(0); E(1); O(1); E(2); O(2); E(3); O(3); }
        else { P(0); P(1); E(0); P(2); E(1); P(3); O(0); E(2); O(1); O(2); E(3); O(3); }
        PROF_T(4 + 4 * c); PROF_G(100 + c);
      };
      chunk(std::true_type{}, 0);
#pragma unroll 1
      for (int c = 1; c < 9; c++) chunk(std::false_type{}, c);
      peer_begin(8);
#pragma unroll 1
      for (int u = 0; u < 4; u++) { mbar_wait(bar + B_FULL + 8 * slot, ph); peer_unit(u); adv(); }
      wg_wait<0>();
      reg_fence(O1); reg_fence(O2);
      PROF_T(40); PROF_G(3);
      const int mi = lane >> 3, li = lane & 7;
      {
        const int row = 16 * w + 8 * (mi & 1) + li;
        const uint32_t stg = sb + T_STG + wg * 8192 + row * 128;
#pragma unroll
        for (int g = 0; g < 32; g += 2)
          stmatrix_x4(stg + (g >> 3) * 16384 + ((((g & 7) + (mi >> 1)) ^ li) << 4), pack_bf16(O1[4 * g], O1[4 * g + 1]), pack_bf16(O1[4 * g + 2], O1[4 * g + 3]),
                      pack_bf16(O1[4 * g + 4], O1[4 * g + 5]), pack_bf16(O1[4 * g + 6], O1[4 * g + 7]));
#pragma unroll
        for (int g = 0; g < 4; g += 2)
          stmatrix_x4(stg + 65536 - row * 64 + (((g + (mi >> 1)) ^ (li >> 1)) << 4), pack_bf16(O2[4 * g], O2[4 * g + 1]), pack_bf16(O2[4 * g + 2], O2[4 * g + 3]),
                      pack_bf16(O2[4 * g + 4], O2[4 * g + 5]), pack_bf16(O2[4 * g + 6], O2[4 * g + 7]));
        fence_async_smem();
        named_bar(1 + wg, 128);
        if (leader) mbar_arrive(bar + B_SG);
      }
      mbar_wait(bar + B_CV, 0);
      PROF_T(43);
      conv2(sb, wg, w, lane);
      PROF_T(44); PROF_G(5);
      const uint32_t rowi = 8 * (mi & 1) + li;
      const uint32_t own_m = sb + T_STG + sp * 16384, own_t = sb + T_STG + 65536 - 16384 + (sp >> 1) * 8192 + (sp & 1) * 2048;
      auto off = [&](int k) -> uint32_t {
        return k < 4 ? (16 * warp + rowi) * 128 + (((2 * k + (mi >> 1)) ^ li) << 4) : 16384 + (16 * warp + rowi) * 64 + (((2 * (k - 4) + (mi >> 1)) ^ (li >> 1)) << 4);
      };
      float f[6][8];
#pragma unroll
      for (int k = 0; k < 6; k++)
#pragma unroll
        for (int i = 0; i < 8; i++) f[k][i] = 0.f;
      named_bar(3, 256);
#pragma unroll 1
      for (int rep = 0; rep < 2; rep++) {
      mbar_wait(bar + (rep ? B_PT : B_X), rep ^ 1);
#pragma unroll 1
      for (int s = 2 * rep; s < 2 + 3 * rep; s++) {
        const uint32_t am = s ? sb + T_PART + (4 - s) * IMG : own_m, at = s ? am : own_t;
#pragma unroll
        for (int k = 0; k < 6; k++) {
          if (k >= 4 && warp >= 2) break;
          uint32_t r[4];
          ldmatrix_x4((k < 4 ? am : at) + off(k), r);
#pragma unroll
          for (int i = 0; i < 4; i++) { f[k][2 * i] += bf_lo(r[i]); f[k][2 * i + 1] += bf_hi(r[i]); }
        }
      }
      if (rep) { PROF_T(56); mbar_wait(bar + B_YT, 0); PROF_T(45); PROF_G(6); }
#pragma unroll
      for (int k = 0; k < 6; k++) {
        if (k >= 4 && warp >= 2) break;
        const uint32_t ya = k < 4 ? (warp >> 2) * 8192 + (16 * k + 8 * (mi >> 1) + li) * 128 + (((2 * (warp & 3) + (mi & 1)) ^ li) << 4)
                                  : 16384 + (16 * (k - 4) + 8 * (mi >> 1) + li) * 64 + (((2 * warp + (mi & 1)) ^ (li >> 1)) << 4);
        uint32_t y0, y1, y2, y3;
        ldmatrix_x4_t(sb + T_YT + ya, y0, y1, y2, y3);
        stmatrix_x4((k < 4 ? own_m : own_t) + off(k), pack_bf16(f[k][0] + bf_lo(y0), f[k][1] + bf_hi(y0)), pack_bf16(f[k][2] + bf_lo(y1), f[k][3] + bf_hi(y1)),
                    pack_bf16(f[k][4] + bf_lo(y2), f[k][5] + bf_hi(y2)), pack_bf16(f[k][6] + bf_lo(y3), f[k][7] + bf_hi(y3)));
      }
      fence_async_smem();
      __syncwarp();
      }
      PROF_T(57);
      if (lane == 0) {
        tma_store_2d(&p.out, own_m + warp * 2048, 256 * j + 64 * sp, mt * 128 + 16 * warp);
        if (warp < 2) tma_store_2d(&p.out5, own_t + 16384 + warp * 1024, 512 + 32 * j, mt * 128 + 32 * sp + 16 * warp);
        asm volatile("cp.async.bulk.commit_group;" ::: "memory");
        asm volatile("cp.async.bulk.wait_group.read 0;" ::: "memory");
      }
      PROF_T(46); PROF_G(7);
    } else {
#pragma unroll 1
      for (int grp = 0; grp < 4; grp++) {
        if (grp) mbar_wait(bar + B_SG, (grp - 1) & 1);
        kexpand<256>(sb, sb + SM_RING + grp * 5120, sb + SM_RING + grp * 5120 + 1280, sb + SM_KD + 8 * grp, threadIdx.x, __ldg((const uint4*)g_ktab.e + threadIdx.x));
        named_bar(3, 256);
        mbar_wait(bar + B_CV, grp & 1);
        conv2(sb, wg, w, lane);
        named_bar(3, 256);
      }
      PROF_T(46);
    }
  }
}

typedef CUresult (*PFN_enc)(CUtensorMap*, CUtensorMapDataType, cuuint32_t, void*, const cuuint64_t*, const cuuint64_t*, const cuuint32_t*,
                            const cuuint32_t*, CUtensorMapInterleave, CUtensorMapSwizzle, CUtensorMapL2promotion, CUtensorMapFloatOOBfill);

void enc(PFN_enc fn, CUtensorMap* m, void* ptr, int rank, const cuuint64_t* dims, const cuuint64_t* strides, const cuuint32_t* box, CUtensorMapSwizzle sw) {
  cuuint32_t es[5] = {1, 1, 1, 1, 1};
  fn(m, CU_TENSOR_MAP_DATA_TYPE_BFLOAT16, rank, ptr, dims, strides, box, es, CU_TENSOR_MAP_INTERLEAVE_NONE, sw,
     CU_TENSOR_MAP_L2_PROMOTION_L2_128B, CU_TENSOR_MAP_FLOAT_OOB_FILL_NONE);
}

}

extern "C" void kernel_launch(void* const* d_in, const int* in_sizes, int n_in, void* d_out, int out_size) {
  static Params pr;
  static void* key[5] = {nullptr, nullptr, nullptr, nullptr, nullptr};
  if (key[0] != d_in[8] || key[1] != d_in[9] || key[2] != d_in[10] || key[3] != d_in[0] || key[4] != d_out) {
    key[0] = d_in[8]; key[1] = d_in[9]; key[2] = d_in[10]; key[3] = d_in[0]; key[4] = d_out;
    void* fnp = nullptr; cudaDriverEntryPointQueryResult st;
    cudaGetDriverEntryPoint("cuTensorMapEncodeTiled", &fnp, cudaEnableDefault, &st);
    PFN_enc fn = (PFN_enc)fnp;
    void *p_xn, *p_y;
    cudaGetSymbolAddress(&p_xn, g_xn); cudaGetSymbolAddress(&p_y, g_y);
    { cuuint64_t d[2] = {D_, L_}, s[1] = {D_ * 2};
      { cuuint32_t b[2] = {64, 128}; enc(fn, &pr.xn, p_xn, 2, d, s, b, CU_TENSOR_MAP_SWIZZLE_128B); }
      { cuuint32_t b[2] = {64, 128}; enc(fn, &pr.x, d_in[0], 2, d, s, b, CU_TENSOR_MAP_SWIZZLE_128B); }
      { cuuint32_t b[2] = {64, 16}; enc(fn, &pr.out, d_out, 2, d, s, b, CU_TENSOR_MAP_SWIZZLE_128B); }
      { cuuint32_t b[2] = {32, 32}; enc(fn, &pr.x5, d_in[0], 2, d, s, b, CU_TENSOR_MAP_SWIZZLE_64B); }
      { cuuint32_t b[2] = {32, 16}; enc(fn, &pr.out5, d_out, 2, d, s, b, CU_TENSOR_MAP_SWIZZLE_64B); } }
    { cuuint64_t d[2] = {F_, D_}, s[1] = {F_ * 2}; cuuint32_t b[2] = {64, 32};
      enc(fn, &pr.gate, d_in[8], 2, d, s, b, CU_TENSOR_MAP_SWIZZLE_128B); enc(fn, &pr.up, d_in[9], 2, d, s, b, CU_TENSOR_MAP_SWIZZLE_128B); }
    { void* wd = d_in[10];
      { cuuint64_t d[3] = {64, F_, 9}, s[2] = {D_ * 2, 128}; cuuint32_t b[3] = {64, 16, 4}; enc(fn, &pr.dn, wd, 3, d, s, b, CU_TENSOR_MAP_SWIZZLE_128B); }
      { cuuint64_t d[2] = {D_, F_}, s[1] = {D_ * 2}; cuuint32_t b[2] = {32, 16}; enc(fn, &pr.dn5, wd, 2, d, s, b, CU_TENSOR_MAP_SWIZZLE_64B); }
      { cuuint64_t d[5] = {64, 2, F_ / 8, 4, 9}, s[4] = {D_ * 2, D_ * 16, D_ * 4, 128}; cuuint32_t b[5] = {64, 2, 4, 2, 4};
        enc(fn, &pr.dp, wd, 5, d, s, b, CU_TENSOR_MAP_SWIZZLE_128B); }
      { cuuint64_t d[4] = {D_, 2, F_ / 8, 4}, s[3] = {D_ * 2, D_ * 16, D_ * 4}; cuuint32_t b[4] = {32, 2, 4, 2};
        enc(fn, &pr.dp5, wd, 4, d, s, b, CU_TENSOR_MAP_SWIZZLE_64B); }
    }
    { cuuint64_t d[2] = {L_, D_}, s[1] = {L_ * 2};
      { cuuint32_t b[2] = {64, 64}; enc(fn, &pr.y, p_y, 2, d, s, b, CU_TENSOR_MAP_SWIZZLE_128B); }
      { cuuint32_t b[2] = {32, 32}; enc(fn, &pr.y5, p_y, 2, d, s, b, CU_TENSOR_MAP_SWIZZLE_64B); } }
    cudaFuncSetAttribute(fused_kernel, cudaFuncAttributeMaxDynamicSharedMemorySize, SMEM_BYTES);
  }
  const __nv_bfloat16* const* in = (const __nv_bfloat16* const*)d_in;
  pr.xp = in[0]; pr.logA = in[1]; pr.Aim = in[2]; pr.Cre = in[3]; pr.Cim = in[4]; pr.logdt = in[5]; pr.Dsk = in[6];
  fused_kernel<<<132, 384, SMEM_BYTES>>>(pr);
}
```

```cpp
#include <cuda_runtime.h>
#include <cuda_bf16.h>
#include <cuda.h>
#include <stdint.h>
#include <type_traits>

namespace {

constexpr int L_ = 2048, D_ = 576, F_ = 4608, NM_ = 128;
constexpr int KP_LEN = 2080;
constexpr int U_LEN = 2176;

__device__ __align__(1024) __nv_bfloat16 g_xn[L_ * D_];
__device__ __align__(1024) __nv_bfloat16 g_u[D_ * L_];
__device__ __align__(1024) unsigned char g_part[32 * 16 * 18432];
__device__ __align__(1024) __nv_bfloat16 g_y[D_ * L_];
__device__ __align__(1024) unsigned int g_cnt[64 * 32];
constexpr int C_LN = 0, C_PART = 16, C_U = 48, C_Y = 49, C_Y5 = 57, C_DONE = 58;

__device__ __forceinline__ uint32_t smem_u32(const void* p) { return (uint32_t)__cvta_generic_to_shared(p); }
__device__ __forceinline__ void mbar_init(uint32_t bar, uint32_t cnt) { asm volatile("mbarrier.init.shared::cta.b64 [%0], %1;" ::"r"(bar), "r"(cnt)); }
__device__ __forceinline__ void mbar_expect_tx(uint32_t bar, uint32_t bytes) { asm volatile("mbarrier.arrive.expect_tx.shared::cta.b64 _, [%0], %1;" ::"r"(bar), "r"(bytes) : "memory"); }
__device__ __forceinline__ void mbar_arrive(uint32_t bar) { asm volatile("mbarrier.arrive.shared::cta.b64 _, [%0];" ::"r"(bar) : "memory"); }
__device__ __forceinline__ void mbar_arrive_remote(uint32_t bar) { asm volatile("mbarrier.arrive.shared::cluster.b64 _, [%0];" ::"r"(bar) : "memory"); }
__device__ __forceinline__ void mbar_wait(uint32_t bar, uint32_t parity) {
  asm volatile("{\n.reg .pred p, q;\n.reg .u32 n;\nmov.u32 n, 0;\nLW:\nmbarrier.try_wait.parity.shared::cta.b64 p, [%0], %1;\n"
               "add.u32 n, n, 1;\nsetp.lt.and.u32 q, n, 65536, !p;\n@q bra LW;\n}" ::"r"(bar), "r"(parity) : "memory");
}
__device__ __forceinline__ bool elect_one() {
  uint32_t ok;
  asm volatile("{\n.reg .pred p;\nelect.sync _|p, 0xffffffff;\nselp.u32 %0, 1, 0, p;\n}" : "=r"(ok));
  return ok;
}
__device__ __forceinline__ void tma_2d(uint32_t dst, const CUtensorMap* map, int c0, int c1, uint32_t bar) {
  asm volatile("cp.async.bulk.tensor.2d.shared::cluster.global.mbarrier::complete_tx::bytes [%0], [%1, {%3, %4}], [%2];"
               ::"r"(dst), "l"(map), "r"(bar), "r"(c0), "r"(c1) : "memory");
}
__device__ __forceinline__ void tma_3d(uint32_t dst, const CUtensorMap* map, int c0, int c1, int c2, uint32_t bar) {
  asm volatile("cp.async.bulk.tensor.3d.shared::cluster.global.mbarrier::complete_tx::bytes [%0], [%1, {%3, %4, %5}], [%2];"
               ::"r"(dst), "l"(map), "r"(bar), "r"(c0), "r"(c1), "r"(c2) : "memory");
}
__device__ __forceinline__ void tma_4d(uint32_t dst, const CUtensorMap* map, int c0, int c1, int c2, int c3, uint32_t bar) {
  asm volatile("cp.async.bulk.tensor.4d.shared::cluster.global.mbarrier::complete_tx::bytes [%0], [%1, {%3, %4, %5, %6}], [%2];"
               ::"r"(dst), "l"(map), "r"(bar), "r"(c0), "r"(c1), "r"(c2), "r"(c3) : "memory");
}
__device__ __forceinline__ void tma_5d(uint32_t dst, const CUtensorMap* map, int c0, int c1, int c2, int c3, int c4, uint32_t bar) {
  asm volatile("cp.async.bulk.tensor.5d.shared::cluster.global.mbarrier::complete_tx::bytes [%0], [%1, {%3, %4, %5, %6, %7}], [%2];"
               ::"r"(dst), "l"(map), "r"(bar), "r"(c0), "r"(c1), "r"(c2), "r"(c3), "r"(c4) : "memory");
}
__device__ __forceinline__ void bulk_g2s(uint32_t dst, const void* src, uint32_t bytes, uint32_t bar) {
  asm volatile("cp.async.bulk.shared::cluster.global.mbarrier::complete_tx::bytes [%0], [%1], %2, [%3];"
               ::"r"(dst), "l"(src), "r"(bytes), "r"(bar) : "memory");
}
__device__ __forceinline__ void prefetch_map(const CUtensorMap* m) { asm volatile("prefetch.tensormap [%0];" ::"l"(m) : "memory"); }
__device__ __forceinline__ uint32_t mapa(uint32_t addr, uint32_t rank) { uint32_t r; asm volatile("mapa.shared::cluster.u32 %0, %1, %2;" : "=r"(r) : "r"(addr), "r"(rank)); return r; }
__device__ __forceinline__ void fence_async_smem() { asm volatile("fence.proxy.async.shared::cta;" ::: "memory"); }
__device__ __forceinline__ void wg_fence() { asm volatile("wgmma.fence.sync.aligned;" ::: "memory"); }
__device__ __forceinline__ void wg_commit() { asm volatile("wgmma.commit_group.sync.aligned;" ::: "memory"); }
template <int N> __device__ __forceinline__ void wg_wait() { asm volatile("wgmma.wait_group.sync.aligned %0;" ::"n"(N) : "memory"); }
template <int N> __device__ __forceinline__ void reg_fence(float (&d)[N]) {
#pragma unroll
  for (int i = 0; i < N; i++) asm volatile("" : "+f"(d[i])::"memory");
}
__device__ __forceinline__ void named_bar(int id, int n) { asm volatile("bar.sync %0, %1;" ::"r"(id), "r"(n) : "memory"); }
__device__ __forceinline__ uint64_t mk_desc(uint32_t addr, uint32_t lbo, uint32_t sbo, uint32_t sw) {
  return (uint64_t)((addr & 0x3FFFF) >> 4) | ((uint64_t)(lbo >> 4) << 16) | ((uint64_t)(sbo >> 4) << 32) | ((uint64_t)sw << 62);
}
__device__ __forceinline__ uint32_t pack_bf16(float lo, float hi) {
  uint32_t r; asm("cvt.rn.bf16x2.f32 %0, %1, %2;" : "=r"(r) : "f"(hi), "f"(lo)); return r;
}
__device__ __forceinline__ float bf_lo(uint32_t v) { return __uint_as_float(v << 16); }
__device__ __forceinline__ float bf_hi(uint32_t v) { return __uint_as_float(v & 0xffff0000u); }
__device__ __forceinline__ float bf_round(float x) { return __bfloat162float(__float2bfloat16_rn(x)); }
__device__ __forceinline__ void st_async_v4(uint32_t addr, uint32_t a, uint32_t b, uint32_t c, uint32_t d, uint32_t bar) {
  asm volatile("st.async.weak.shared::cluster.mbarrier::complete_tx::bytes.v4.b32 [%0], {%1, %2, %3, %4}, [%5];"
               ::"r"(addr), "r"(a), "r"(b), "r"(c), "r"(d), "r"(bar) : "memory");
}
__device__ __forceinline__ void stmatrix_x4_t(uint32_t addr, uint32_t a, uint32_t b, uint32_t c, uint32_t d) {
  asm volatile("stmatrix.sync.aligned.m8n8.x4.trans.shared.b16 [%0], {%1, %2, %3, %4};" ::"r"(addr), "r"(a), "r"(b), "r"(c), "r"(d) : "memory");
}
__device__ __forceinline__ void ldmatrix_x4_t(uint32_t addr, uint32_t& a, uint32_t& b, uint32_t& c, uint32_t& d) {
  asm volatile("ldmatrix.sync.aligned.m8n8.x4.trans.shared.b16 {%0, %1, %2, %3}, [%4];" : "=r"(a), "=r"(b), "=r"(c), "=r"(d) : "r"(addr) : "memory");
}
__device__ __forceinline__ uint32_t lds32(uint32_t addr) { uint32_t v; asm volatile("ld.shared.b32 %0, [%1];" : "=r"(v) : "r"(addr) : "memory"); return v; }
__device__ __forceinline__ float geglu(float g, float u) {
  float z = g * fmaf(g * g, 0.0356774081f, 0.7978845608f);
  float t; asm("tanh.approx.f32 %0, %1;" : "=f"(t) : "f"(z));
  return (g * u) * fmaf(t, 0.5f, 0.5f);
}

__device__ __forceinline__ uint4 lds128(uint32_t addr) { uint4 v; asm volatile("ld.shared.v4.b32 {%0,%1,%2,%3}, [%4];" : "=r"(v.x), "=r"(v.y), "=r"(v.z), "=r"(v.w) : "r"(addr) : "memory"); return v; }
__device__ __forceinline__ void stmatrix_x4(uint32_t addr, uint32_t a, uint32_t b, uint32_t c, uint32_t d) {
  asm volatile("stmatrix.sync.aligned.m8n8.x4.shared.b16 [%0], {%1, %2, %3, %4};" ::"r"(addr), "r"(a), "r"(b), "r"(c), "r"(d) : "memory");
}
__device__ __forceinline__ void ldmatrix_x4(uint32_t addr, uint32_t (&r)[4]) {
  asm volatile("ldmatrix.sync.aligned.m8n8.x4.shared.b16 {%0, %1, %2, %3}, [%4];" : "=r"(r[0]), "=r"(r[1]), "=r"(r[2]), "=r"(r[3]) : "r"(addr) : "memory");
}
__device__ __forceinline__ void sts128(uint32_t addr, uint4 v) { asm volatile("st.shared.v4.b32 [%0], {%1,%2,%3,%4};" ::"r"(addr), "r"(v.x), "r"(v.y), "r"(v.z), "r"(v.w) : "memory"); }
__device__ __forceinline__ void bulk_s2g(void* dst, uint32_t src, uint32_t bytes) {
  asm volatile("cp.async.bulk.global.shared::cta.bulk_group [%0], [%1], %2;" ::"l"(dst), "r"(src), "r"(bytes) : "memory");
}
__device__ __forceinline__ void tma_store_2d(const CUtensorMap* map, uint32_t src, int c0, int c1) {
  asm volatile("cp.async.bulk.tensor.2d.global.shared::cta.bulk_group [%0, {%2, %3}], [%1];" ::"l"(map), "r"(src), "r"(c0), "r"(c1) : "memory");
}
__device__ __forceinline__ void bulk_commit_wait() {
  asm volatile("cp.async.bulk.commit_group;" ::: "memory");
  asm volatile("cp.async.bulk.wait_group 0;" ::: "memory");
}
__device__ __forceinline__ void named_arrive(int id, int n) { asm volatile("bar.arrive %0, %1;" ::"r"(id), "r"(n) : "memory"); }
__device__ __forceinline__ void fence_async_all() { asm volatile("fence.proxy.async.global;" ::: "memory"); }
__device__ __forceinline__ void cnt_add(int idx) {
  asm volatile("red.release.gpu.global.add.u32 [%0], 1;" ::"l"(g_cnt + idx * 32) : "memory");
}
__device__ __forceinline__ void cnt_add_done(int idx) {
  asm volatile("red.relaxed.gpu.global.add.u32 [%0], 1;" ::"l"(g_cnt + idx * 32) : "memory");
}
__device__ __forceinline__ void cnt_wait(int idx, uint32_t target) {
  const unsigned int* p = g_cnt + idx * 32;
#pragma unroll 1
  for (int it = 0; it < (1 << 18); it++) {
    uint32_t v; asm volatile("ld.acquire.gpu.global.u32 %0, [%1];" : "=r"(v) : "l"(p) : "memory");
    if (v >= target) break;
  }
}

template <int TB>
__device__ __forceinline__ void wg_ss128_init(float (&d)[64], uint64_t da, uint64_t db) {
  asm volatile(
    "wgmma.mma_async.sync.aligned.m64n128k16.f32.bf16.bf16 {%0, %1, %2, %3, %4, %5, %6, %7, %8, %9, %10, %11, %12, %13, %14, %15, %16, %17, %18, %19, %20, %21, %22, %23, %24, %25, %26, %27, %28, %29, %30, %31, %32, %33, %34, %35, %36, %37, %38, %39, %40, %41, %42, %43, %44, %45, %46, %47, %48, %49, %50, %51, %52, %53, %54, %55, %56, %57, %58, %59, %60, %61, %62, %63}, %64, %65, 0, 1, 1, 0, %66;"
    : "=f"(d[0]), "=f"(d[1]), "=f"(d[2]), "=f"(d[3]), "=f"(d[4]), "=f"(d[5]), "=f"(d[6]), "=f"(d[7]), "=f"(d[8]), "=f"(d[9]), "=f"(d[10]), "=f"(d[11]), "=f"(d[12]), "=f"(d[13]), "=f"(d[14]), "=f"(d[15]), "=f"(d[16]), "=f"(d[17]), "=f"(d[18]), "=f"(d[19]), "=f"(d[20]), "=f"(d[21]), "=f"(d[22]), "=f"(d[23]), "=f"(d[24]), "=f"(d[25]), "=f"(d[26]), "=f"(d[27]), "=f"(d[28]), "=f"(d[29]), "=f"(d[30]), "=f"(d[31]), "=f"(d[32]), "=f"(d[33]), "=f"(d[34]), "=f"(d[35]), "=f"(d[36]), "=f"(d[37]), "=f"(d[38]), "=f"(d[39]), "=f"(d[40]), "=f"(d[41]), "=f"(d[42]), "=f"(d[43]), "=f"(d[44]), "=f"(d[45]), "=f"(d[46]), "=f"(d[47]), "=f"(d[48]), "=f"(d[49]), "=f"(d[50]), "=f"(d[51]), "=f"(d[52]), "=f"(d[53]), "=f"(d[54]), "=f"(d[55]), "=f"(d[56]), "=f"(d[57]), "=f"(d[58]), "=f"(d[59]), "=f"(d[60]), "=f"(d[61]), "=f"(d[62]), "=f"(d[63])
    : "l"(da), "l"(db), "n"(TB));
}
template <int TB>
__device__ __forceinline__ void wg_ss128(float (&d)[64], uint64_t da, uint64_t db) {
  asm volatile(
    "wgmma.mma_async.sync.aligned.m64n128k16.f32.bf16.bf16 {%0, %1, %2, %3, %4, %5, %6, %7, %8, %9, %10, %11, %12, %13, %14, %15, %16, %17, %18, %19, %20, %21, %22, %23, %24, %25, %26, %27, %28, %29, %30, %31, %32, %33, %34, %35, %36, %37, %38, %39, %40, %41, %42, %43, %44, %45, %46, %47, %48, %49, %50, %51, %52, %53, %54, %55, %56, %57, %58, %59, %60, %61, %62, %63}, %64, %65, 1, 1, 1, 0, %66;"
    : "+f"(d[0]), "+f"(d[1]), "+f"(d[2]), "+f"(d[3]), "+f"(d[4]), "+f"(d[5]), "+f"(d[6]), "+f"(d[7]), "+f"(d[8]), "+f"(d[9]), "+f"(d[10]), "+f"(d[11]), "+f"(d[12]), "+f"(d[13]), "+f"(d[14]), "+f"(d[15]), "+f"(d[16]), "+f"(d[17]), "+f"(d[18]), "+f"(d[19]), "+f"(d[20]), "+f"(d[21]), "+f"(d[22]), "+f"(d[23]), "+f"(d[24]), "+f"(d[25]), "+f"(d[26]), "+f"(d[27]), "+f"(d[28]), "+f"(d[29]), "+f"(d[30]), "+f"(d[31]), "+f"(d[32]), "+f"(d[33]), "+f"(d[34]), "+f"(d[35]), "+f"(d[36]), "+f"(d[37]), "+f"(d[38]), "+f"(d[39]), "+f"(d[40]), "+f"(d[41]), "+f"(d[42]), "+f"(d[43]), "+f"(d[44]), "+f"(d[45]), "+f"(d[46]), "+f"(d[47]), "+f"(d[48]), "+f"(d[49]), "+f"(d[50]), "+f"(d[51]), "+f"(d[52]), "+f"(d[53]), "+f"(d[54]), "+f"(d[55]), "+f"(d[56]), "+f"(d[57]), "+f"(d[58]), "+f"(d[59]), "+f"(d[60]), "+f"(d[61]), "+f"(d[62]), "+f"(d[63])
    : "l"(da), "l"(db), "n"(TB));
}
template <int TB>
__device__ __forceinline__ void wg_ss256(float (&d)[128], uint64_t da, uint64_t db) {
  asm volatile(
    "wgmma.mma_async.sync.aligned.m64n256k16.f32.bf16.bf16 {%0, %1, %2, %3, %4, %5, %6, %7, %8, %9, %10, %11, %12, %13, %14, %15, %16, %17, %18, %19, %20, %21, %22, %23, %24, %25, %26, %27, %28, %29, %30, %31, %32, %33, %34, %35, %36, %37, %38, %39, %40, %41, %42, %43, %44, %45, %46, %47, %48, %49, %50, %51, %52, %53, %54, %55, %56, %57, %58, %59, %60, %61, %62, %63, %64, %65, %66, %67, %68, %69, %70, %71, %72, %73, %74, %75, %76, %77, %78, %79, %80, %81, %82, %83, %84, %85, %86, %87, %88, %89, %90, %91, %92, %93, %94, %95, %96, %97, %98, %99, %100, %101, %102, %103, %104, %105, %106, %107, %108, %109, %110, %111, %112, %113, %114, %115, %116, %117, %118, %119, %120, %121, %122, %123, %124, %125, %126, %127}, %128, %129, 1, 1, 1, 0, %130;"
    : "+f"(d[0]), "+f"(d[1]), "+f"(d[2]), "+f"(d[3]), "+f"(d[4]), "+f"(d[5]), "+f"(d[6]), "+f"(d[7]), "+f"(d[8]), "+f"(d[9]), "+f"(d[10]), "+f"(d[11]), "+f"(d[12]), "+f"(d[13]), "+f"(d[14]), "+f"(d[15]), "+f"(d[16]), "+f"(d[17]), "+f"(d[18]), "+f"(d[19]), "+f"(d[20]), "+f"(d[21]), "+f"(d[22]), "+f"(d[23]), "+f"(d[24]), "+f"(d[25]), "+f"(d[26]), "+f"(d[27]), "+f"(d[28]), "+f"(d[29]), "+f"(d[30]), "+f"(d[31]), "+f"(d[32]), "+f"(d[33]), "+f"(d[34]), "+f"(d[35]), "+f"(d[36]), "+f"(d[37]), "+f"(d[38]), "+f"(d[39]), "+f"(d[40]), "+f"(d[41]), "+f"(d[42]), "+f"(d[43]), "+f"(d[44]), "+f"(d[45]), "+f"(d[46]), "+f"(d[47]), "+f"(d[48]), "+f"(d[49]), "+f"(d[50]), "+f"(d[51]), "+f"(d[52]), "+f"(d[53]), "+f"(d[54]), "+f"(d[55]), "+f"(d[56]), "+f"(d[57]), "+f"(d[58]), "+f"(d[59]), "+f"(d[60]), "+f"(d[61]), "+f"(d[62]), "+f"(d[63]), "+f"(d[64]), "+f"(d[65]), "+f"(d[66]), "+f"(d[67]), "+f"(d[68]), "+f"(d[69]), "+f"(d[70]), "+f"(d[71]), "+f"(d[72]), "+f"(d[73]), "+f"(d[74]), "+f"(d[75]), "+f"(d[76]), "+f"(d[77]), "+f"(d[78]), "+f"(d[79]), "+f"(d[80]), "+f"(d[81]), "+f"(d[82]), "+f"(d[83]), "+f"(d[84]), "+f"(d[85]), "+f"(d[86]), "+f"(d[87]), "+f"(d[88]), "+f"(d[89]), "+f"(d[90]), "+f"(d[91]), "+f"(d[92]), "+f"(d[93]), "+f"(d[94]), "+f"(d[95]), "+f"(d[96]), "+f"(d[97]), "+f"(d[98]), "+f"(d[99]), "+f"(d[100]), "+f"(d[101]), "+f"(d[102]), "+f"(d[103]), "+f"(d[104]), "+f"(d[105]), "+f"(d[106]), "+f"(d[107]), "+f"(d[108]), "+f"(d[109]), "+f"(d[110]), "+f"(d[111]), "+f"(d[112]), "+f"(d[113]), "+f"(d[114]), "+f"(d[115]), "+f"(d[116]), "+f"(d[117]), "+f"(d[118]), "+f"(d[119]), "+f"(d[120]), "+f"(d[121]), "+f"(d[122]), "+f"(d[123]), "+f"(d[124]), "+f"(d[125]), "+f"(d[126]), "+f"(d[127])
    : "l"(da), "l"(db), "n"(TB));
}
template <int TB>
__device__ __forceinline__ void wg_ss32(float (&d)[16], uint64_t da, uint64_t db) {
  asm volatile(
    "wgmma.mma_async.sync.aligned.m64n32k16.f32.bf16.bf16 {%0, %1, %2, %3, %4, %5, %6, %7, %8, %9, %10, %11, %12, %13, %14, %15}, %16, %17, 1, 1, 1, 0, %18;"
    : "+f"(d[0]), "+f"(d[1]), "+f"(d[2]), "+f"(d[3]), "+f"(d[4]), "+f"(d[5]), "+f"(d[6]), "+f"(d[7]), "+f"(d[8]), "+f"(d[9]), "+f"(d[10]), "+f"(d[11]), "+f"(d[12]), "+f"(d[13]), "+f"(d[14]), "+f"(d[15])
    : "l"(da), "l"(db), "n"(TB));
}
template <int TB>
__device__ __forceinline__ void wg_rs256(float (&d)[128], uint32_t a0, uint32_t a1, uint32_t a2, uint32_t a3, uint64_t db) {
  asm volatile(
    "wgmma.mma_async.sync.aligned.m64n256k16.f32.bf16.bf16 {%0, %1, %2, %3, %4, %5, %6, %7, %8, %9, %10, %11, %12, %13, %14, %15, %16, %17, %18, %19, %20, %21, %22, %23, %24, %25, %26, %27, %28, %29, %30, %31, %32, %33, %34, %35, %36, %37, %38, %39, %40, %41, %42, %43, %44, %45, %46, %47, %48, %49, %50, %51, %52, %53, %54, %55, %56, %57, %58, %59, %60, %61, %62, %63, %64, %65, %66, %67, %68, %69, %70, %71, %72, %73, %74, %75, %76, %77, %78, %79, %80, %81, %82, %83, %84, %85, %86, %87, %88, %89, %90, %91, %92, %93, %94, %95, %96, %97, %98, %99, %100, %101, %102, %103, %104, %105, %106, %107, %108, %109, %110, %111, %112, %113, %114, %115, %116, %117, %118, %119, %120, %121, %122, %123, %124, %125, %126, %127}, {%128, %129, %130, %131}, %132, 1, 1, 1, %133;"
    : "+f"(d[0]), "+f"(d[1]), "+f"(d[2]), "+f"(d[3]), "+f"(d[4]), "+f"(d[5]), "+f"(d[6]), "+f"(d[7]), "+f"(d[8]), "+f"(d[9]), "+f"(d[10]), "+f"(d[11]), "+f"(d[12]), "+f"(d[13]), "+f"(d[14]), "+f"(d[15]), "+f"(d[16]), "+f"(d[17]), "+f"(d[18]), "+f"(d[19]), "+f"(d[20]), "+f"(d[21]), "+f"(d[22]), "+f"(d[23]), "+f"(d[24]), "+f"(d[25]), "+f"(d[26]), "+f"(d[27]), "+f"(d[28]), "+f"(d[29]), "+f"(d[30]), "+f"(d[31]), "+f"(d[32]), "+f"(d[33]), "+f"(d[34]), "+f"(d[35]), "+f"(d[36]), "+f"(d[37]), "+f"(d[38]), "+f"(d[39]), "+f"(d[40]), "+f"(d[41]), "+f"(d[42]), "+f"(d[43]), "+f"(d[44]), "+f"(d[45]), "+f"(d[46]), "+f"(d[47]), "+f"(d[48]), "+f"(d[49]), "+f"(d[50]), "+f"(d[51]), "+f"(d[52]), "+f"(d[53]), "+f"(d[54]), "+f"(d[55]), "+f"(d[56]), "+f"(d[57]), "+f"(d[58]), "+f"(d[59]), "+f"(d[60]), "+f"(d[61]), "+f"(d[62]), "+f"(d[63]), "+f"(d[64]), "+f"(d[65]), "+f"(d[66]), "+f"(d[67]), "+f"(d[68]), "+f"(d[69]), "+f"(d[70]), "+f"(d[71]), "+f"(d[72]), "+f"(d[73]), "+f"(d[74]), "+f"(d[75]), "+f"(d[76]), "+f"(d[77]), "+f"(d[78]), "+f"(d[79]), "+f"(d[80]), "+f"(d[81]), "+f"(d[82]), "+f"(d[83]), "+f"(d[84]), "+f"(d[85]), "+f"(d[86]), "+f"(d[87]), "+f"(d[88]), "+f"(d[89]), "+f"(d[90]), "+f"(d[91]), "+f"(d[92]), "+f"(d[93]), "+f"(d[94]), "+f"(d[95]), "+f"(d[96]), "+f"(d[97]), "+f"(d[98]), "+f"(d[99]), "+f"(d[100]), "+f"(d[101]), "+f"(d[102]), "+f"(d[103]), "+f"(d[104]), "+f"(d[105]), "+f"(d[106]), "+f"(d[107]), "+f"(d[108]), "+f"(d[109]), "+f"(d[110]), "+f"(d[111]), "+f"(d[112]), "+f"(d[113]), "+f"(d[114]), "+f"(d[115]), "+f"(d[116]), "+f"(d[117]), "+f"(d[118]), "+f"(d[119]), "+f"(d[120]), "+f"(d[121]), "+f"(d[122]), "+f"(d[123]), "+f"(d[124]), "+f"(d[125]), "+f"(d[126]), "+f"(d[127])
    : "r"(a0), "r"(a1), "r"(a2), "r"(a3), "l"(db), "n"(TB));
}
template <int TB>
__device__ __forceinline__ void wg_rs32(float (&d)[16], uint32_t a0, uint32_t a1, uint32_t a2, uint32_t a3, uint64_t db) {
  asm volatile(
    "wgmma.mma_async.sync.aligned.m64n32k16.f32.bf16.bf16 {%0, %1, %2, %3, %4, %5, %6, %7, %8, %9, %10, %11, %12, %13, %14, %15}, {%16, %17, %18, %19}, %20, 1, 1, 1, %21;"
    : "+f"(d[0]), "+f"(d[1]), "+f"(d[2]), "+f"(d[3]), "+f"(d[4]), "+f"(d[5]), "+f"(d[6]), "+f"(d[7]), "+f"(d[8]), "+f"(d[9]), "+f"(d[10]), "+f"(d[11]), "+f"(d[12]), "+f"(d[13]), "+f"(d[14]), "+f"(d[15])
    : "r"(a0), "r"(a1), "r"(a2), "r"(a3), "l"(db), "n"(TB));
}
template <int TB>
__device__ __forceinline__ void wg_cv128(float (&d)[64], uint32_t a0, uint32_t a1, uint32_t a2, uint32_t a3, uint64_t db) {
  asm volatile(
    "wgmma.mma_async.sync.aligned.m64n128k16.f32.bf16.bf16 {%0, %1, %2, %3, %4, %5, %6, %7, %8, %9, %10, %11, %12, %13, %14, %15, %16, %17, %18, %19, %20, %21, %22, %23, %24, %25, %26, %27, %28, %29, %30, %31, %32, %33, %34, %35, %36, %37, %38, %39, %40, %41, %42, %43, %44, %45, %46, %47, %48, %49, %50, %51, %52, %53, %54, %55, %56, %57, %58, %59, %60, %61, %62, %63}, {%64, %65, %66, %67}, %68, 1, 1, 1, %69;"
    : "+f"(d[0]), "+f"(d[1]), "+f"(d[2]), "+f"(d[3]), "+f"(d[4]), "+f"(d[5]), "+f"(d[6]), "+f"(d[7]), "+f"(d[8]), "+f"(d[9]), "+f"(d[10]), "+f"(d[11]), "+f"(d[12]), "+f"(d[13]), "+f"(d[14]), "+f"(d[15]), "+f"(d[16]), "+f"(d[17]), "+f"(d[18]), "+f"(d[19]), "+f"(d[20]), "+f"(d[21]), "+f"(d[22]), "+f"(d[23]), "+f"(d[24]), "+f"(d[25]), "+f"(d[26]), "+f"(d[27]), "+f"(d[28]), "+f"(d[29]), "+f"(d[30]), "+f"(d[31]), "+f"(d[32]), "+f"(d[33]), "+f"(d[34]), "+f"(d[35]), "+f"(d[36]), "+f"(d[37]), "+f"(d[38]), "+f"(d[39]), "+f"(d[40]), "+f"(d[41]), "+f"(d[42]), "+f"(d[43]), "+f"(d[44]), "+f"(d[45]), "+f"(d[46]), "+f"(d[47]), "+f"(d[48]), "+f"(d[49]), "+f"(d[50]), "+f"(d[51]), "+f"(d[52]), "+f"(d[53]), "+f"(d[54]), "+f"(d[55]), "+f"(d[56]), "+f"(d[57]), "+f"(d[58]), "+f"(d[59]), "+f"(d[60]), "+f"(d[61]), "+f"(d[62]), "+f"(d[63])
    : "r"(a0), "r"(a1), "r"(a2), "r"(a3), "l"(db), "n"(TB));
}
template <int TB>
__device__ __forceinline__ void wg_cv96(float (&d)[48], uint32_t a0, uint32_t a1, uint32_t a2, uint32_t a3, uint64_t db) {
  asm volatile(
    "wgmma.mma_async.sync.aligned.m64n96k16.f32.bf16.bf16 {%0, %1, %2, %3, %4, %5, %6, %7, %8, %9, %10, %11, %12, %13, %14, %15, %16, %17, %18, %19, %20, %21, %22, %23, %24, %25, %26, %27, %28, %29, %30, %31, %32, %33, %34, %35, %36, %37, %38, %39, %40, %41, %42, %43, %44, %45, %46, %47}, {%48, %49, %50, %51}, %52, 1, 1, 1, %53;"
    : "+f"(d[0]), "+f"(d[1]), "+f"(d[2]), "+f"(d[3]), "+f"(d[4]), "+f"(d[5]), "+f"(d[6]), "+f"(d[7]), "+f"(d[8]), "+f"(d[9]), "+f"(d[10]), "+f"(d[11]), "+f"(d[12]), "+f"(d[13]), "+f"(d[14]), "+f"(d[15]), "+f"(d[16]), "+f"(d[17]), "+f"(d[18]), "+f"(d[19]), "+f"(d[20]), "+f"(d[21]), "+f"(d[22]), "+f"(d[23]), "+f"(d[24]), "+f"(d[25]), "+f"(d[26]), "+f"(d[27]), "+f"(d[28]), "+f"(d[29]), "+f"(d[30]), "+f"(d[31]), "+f"(d[32]), "+f"(d[33]), "+f"(d[34]), "+f"(d[35]), "+f"(d[36]), "+f"(d[37]), "+f"(d[38]), "+f"(d[39]), "+f"(d[40]), "+f"(d[41]), "+f"(d[42]), "+f"(d[43]), "+f"(d[44]), "+f"(d[45]), "+f"(d[46]), "+f"(d[47])
    : "r"(a0), "r"(a1), "r"(a2), "r"(a3), "l"(db), "n"(TB));
}
template <int TB>
__device__ __forceinline__ void wg_cv64(float (&d)[32], uint32_t a0, uint32_t a1, uint32_t a2, uint32_t a3, uint64_t db) {
  asm volatile(
    "wgmma.mma_async.sync.aligned.m64n64k16.f32.bf16.bf16 {%0, %1, %2, %3, %4, %5, %6, %7, %8, %9, %10, %11, %12, %13, %14, %15, %16, %17, %18, %19, %20, %21, %22, %23, %24, %25, %26, %27, %28, %29, %30, %31}, {%32, %33, %34, %35}, %36, 1, 1, 1, %37;"
    : "+f"(d[0]), "+f"(d[1]), "+f"(d[2]), "+f"(d[3]), "+f"(d[4]), "+f"(d[5]), "+f"(d[6]), "+f"(d[7]), "+f"(d[8]), "+f"(d[9]), "+f"(d[10]), "+f"(d[11]), "+f"(d[12]), "+f"(d[13]), "+f"(d[14]), "+f"(d[15]), "+f"(d[16]), "+f"(d[17]), "+f"(d[18]), "+f"(d[19]), "+f"(d[20]), "+f"(d[21]), "+f"(d[22]), "+f"(d[23]), "+f"(d[24]), "+f"(d[25]), "+f"(d[26]), "+f"(d[27]), "+f"(d[28]), "+f"(d[29]), "+f"(d[30]), "+f"(d[31])
    : "r"(a0), "r"(a1), "r"(a2), "r"(a3), "l"(db), "n"(TB));
}
template <int TB>
__device__ __forceinline__ void wg_cv128_init(float (&d)[64], uint32_t a0, uint32_t a1, uint32_t a2, uint32_t a3, uint64_t db) {
  asm volatile(
    "wgmma.mma_async.sync.aligned.m64n128k16.f32.bf16.bf16 {%0, %1, %2, %3, %4, %5, %6, %7, %8, %9, %10, %11, %12, %13, %14, %15, %16, %17, %18, %19, %20, %21, %22, %23, %24, %25, %26, %27, %28, %29, %30, %31, %32, %33, %34, %35, %36, %37, %38, %39, %40, %41, %42, %43, %44, %45, %46, %47, %48, %49, %50, %51, %52, %53, %54, %55, %56, %57, %58, %59, %60, %61, %62, %63}, {%64, %65, %66, %67}, %68, 0, 1, 1, %69;"
    : "=f"(d[0]), "=f"(d[1]), "=f"(d[2]), "=f"(d[3]), "=f"(d[4]), "=f"(d[5]), "=f"(d[6]), "=f"(d[7]), "=f"(d[8]), "=f"(d[9]), "=f"(d[10]), "=f"(d[11]), "=f"(d[12]), "=f"(d[13]), "=f"(d[14]), "=f"(d[15]), "=f"(d[16]), "=f"(d[17]), "=f"(d[18]), "=f"(d[19]), "=f"(d[20]), "=f"(d[21]), "=f"(d[22]), "=f"(d[23]), "=f"(d[24]), "=f"(d[25]), "=f"(d[26]), "=f"(d[27]), "=f"(d[28]), "=f"(d[29]), "=f"(d[30]), "=f"(d[31]), "=f"(d[32]), "=f"(d[33]), "=f"(d[34]), "=f"(d[35]), "=f"(d[36]), "=f"(d[37]), "=f"(d[38]), "=f"(d[39]), "=f"(d[40]), "=f"(d[41]), "=f"(d[42]), "=f"(d[43]), "=f"(d[44]), "=f"(d[45]), "=f"(d[46]), "=f"(d[47]), "=f"(d[48]), "=f"(d[49]), "=f"(d[50]), "=f"(d[51]), "=f"(d[52]), "=f"(d[53]), "=f"(d[54]), "=f"(d[55]), "=f"(d[56]), "=f"(d[57]), "=f"(d[58]), "=f"(d[59]), "=f"(d[60]), "=f"(d[61]), "=f"(d[62]), "=f"(d[63])
    : "r"(a0), "r"(a1), "r"(a2), "r"(a3), "l"(db), "n"(TB));
}
template <int TB>
__device__ __forceinline__ void wg_rs256_init(float (&d)[128], uint32_t a0, uint32_t a1, uint32_t a2, uint32_t a3, uint64_t db) {
  asm volatile(
    "wgmma.mma_async.sync.aligned.m64n256k16.f32.bf16.bf16 {%0, %1, %2, %3, %4, %5, %6, %7, %8, %9, %10, %11, %12, %13, %14, %15, %16, %17, %18, %19, %20, %21, %22, %23, %24, %25, %26, %27, %28, %29, %30, %31, %32, %33, %34, %35, %36, %37, %38, %39, %40, %41, %42, %43, %44, %45, %46, %47, %48, %49, %50, %51, %52, %53, %54, %55, %56, %57, %58, %59, %60, %61, %62, %63, %64, %65, %66, %67, %68, %69, %70, %71, %72, %73, %74, %75, %76, %77, %78, %79, %80, %81, %82, %83, %84, %85, %86, %87, %88, %89, %90, %91, %92, %93, %94, %95, %96, %97, %98, %99, %100, %101, %102, %103, %104, %105, %106, %107, %108, %109, %110, %111, %112, %113, %114, %115, %116, %117, %118, %119, %120, %121, %122, %123, %124, %125, %126, %127}, {%128, %129, %130, %131}, %132, 0, 1, 1, %133;"
    : "=f"(d[0]), "=f"(d[1]), "=f"(d[2]), "=f"(d[3]), "=f"(d[4]), "=f"(d[5]), "=f"(d[6]), "=f"(d[7]), "=f"(d[8]), "=f"(d[9]), "=f"(d[10]), "=f"(d[11]), "=f"(d[12]), "=f"(d[13]), "=f"(d[14]), "=f"(d[15]), "=f"(d[16]), "=f"(d[17]), "=f"(d[18]), "=f"(d[19]), "=f"(d[20]), "=f"(d[21]), "=f"(d[22]), "=f"(d[23]), "=f"(d[24]), "=f"(d[25]), "=f"(d[26]), "=f"(d[27]), "=f"(d[28]), "=f"(d[29]), "=f"(d[30]), "=f"(d[31]), "=f"(d[32]), "=f"(d[33]), "=f"(d[34]), "=f"(d[35]), "=f"(d[36]), "=f"(d[37]), "=f"(d[38]), "=f"(d[39]), "=f"(d[40]), "=f"(d[41]), "=f"(d[42]), "=f"(d[43]), "=f"(d[44]), "=f"(d[45]), "=f"(d[46]), "=f"(d[47]), "=f"(d[48]), "=f"(d[49]), "=f"(d[50]), "=f"(d[51]), "=f"(d[52]), "=f"(d[53]), "=f"(d[54]), "=f"(d[55]), "=f"(d[56]), "=f"(d[57]), "=f"(d[58]), "=f"(d[59]), "=f"(d[60]), "=f"(d[61]), "=f"(d[62]), "=f"(d[63]), "=f"(d[64]), "=f"(d[65]), "=f"(d[66]), "=f"(d[67]), "=f"(d[68]), "=f"(d[69]), "=f"(d[70]), "=f"(d[71]), "=f"(d[72]), "=f"(d[73]), "=f"(d[74]), "=f"(d[75]), "=f"(d[76]), "=f"(d[77]), "=f"(d[78]), "=f"(d[79]), "=f"(d[80]), "=f"(d[81]), "=f"(d[82]), "=f"(d[83]), "=f"(d[84]), "=f"(d[85]), "=f"(d[86]), "=f"(d[87]), "=f"(d[88]), "=f"(d[89]), "=f"(d[90]), "=f"(d[91]), "=f"(d[92]), "=f"(d[93]), "=f"(d[94]), "=f"(d[95]), "=f"(d[96]), "=f"(d[97]), "=f"(d[98]), "=f"(d[99]), "=f"(d[100]), "=f"(d[101]), "=f"(d[102]), "=f"(d[103]), "=f"(d[104]), "=f"(d[105]), "=f"(d[106]), "=f"(d[107]), "=f"(d[108]), "=f"(d[109]), "=f"(d[110]), "=f"(d[111]), "=f"(d[112]), "=f"(d[113]), "=f"(d[114]), "=f"(d[115]), "=f"(d[116]), "=f"(d[117]), "=f"(d[118]), "=f"(d[119]), "=f"(d[120]), "=f"(d[121]), "=f"(d[122]), "=f"(d[123]), "=f"(d[124]), "=f"(d[125]), "=f"(d[126]), "=f"(d[127])
    : "r"(a0), "r"(a1), "r"(a2), "r"(a3), "l"(db), "n"(TB));
}
template <int TB>
__device__ __forceinline__ void wg_rs32_init(float (&d)[16], uint32_t a0, uint32_t a1, uint32_t a2, uint32_t a3, uint64_t db) {
  asm volatile(
    "wgmma.mma_async.sync.aligned.m64n32k16.f32.bf16.bf16 {%0, %1, %2, %3, %4, %5, %6, %7, %8, %9, %10, %11, %12, %13, %14, %15}, {%16, %17, %18, %19}, %20, 0, 1, 1, %21;"
    : "=f"(d[0]), "=f"(d[1]), "=f"(d[2]), "=f"(d[3]), "=f"(d[4]), "=f"(d[5]), "=f"(d[6]), "=f"(d[7]), "=f"(d[8]), "=f"(d[9]), "=f"(d[10]), "=f"(d[11]), "=f"(d[12]), "=f"(d[13]), "=f"(d[14]), "=f"(d[15])
    : "r"(a0), "r"(a1), "r"(a2), "r"(a3), "l"(db), "n"(TB));
}


constexpr int NST = 7, SLOT = 9216;
constexpr uint32_t SM_XN = 0, SM_HIN = 147456, SM_RING = 163840, SM_BAR = SM_RING + 7 * SLOT;
constexpr uint32_t SM_KD = SM_BAR + 256, SMEM_BYTES = SM_KD + 3840;
constexpr uint32_t B_FULL = 0, B_EMPTY = 56, B_XN = 112, B_K2048 = 176, B_HF = 184, B_HE = 200, B_CV = 216, B_PT = 224, B_YT = 232, B_SG = 240, B_X = 248;
constexpr uint32_t PR_LN = 65536, PR_PAR = 98304, PR_K0 = SM_HIN + 12288;
constexpr uint32_t T_U = 0, T_KP = 17408, T_K0 = 51200, T_X0 = 53248, T_X1 = SM_HIN + 4 * 18432, T_YT = 0, T_STG = 65536, T_PART = SM_HIN;
constexpr uint32_t U_BYTES = U_LEN * 2, KP_BYTES = KP_LEN * 4, IMG = 18432;

struct Params {
  CUtensorMap xn, gate, up, dn, dn5, dp, dp5, x, x5, y, y5, out, out5;
  const __nv_bfloat16 *xp, *logA, *Aim, *Cre, *Cim, *logdt, *Dsk;
};

struct KgIn { uint32_t la, ai, cr, ci, ldt, dsk; };
__device__ __forceinline__ void kgen_load(const Params& p, int ch0, int tid, KgIn& in) {
  const int e = ch0 * (NM_ / 2) + tid;
  in.la = __ldg((const uint32_t*)p.logA + e); in.ai = __ldg((const uint32_t*)p.Aim + e);
  in.cr = __ldg((const uint32_t*)p.Cre + e); in.ci = __ldg((const uint32_t*)p.Cim + e);
  in.ldt = __ldg((const unsigned short*)p.logdt + ch0 + (tid >> 6)); in.dsk = __ldg((const unsigned short*)p.Dsk + ch0 + (tid >> 6));
}
struct KgState { float acc[5][4]; float v; };
struct cf { float r, i; };
__device__ __forceinline__ cf cmul(cf a, cf b) { return {fmaf(a.r, b.r, -(a.i * b.i)), fmaf(a.r, b.i, a.i * b.r)}; }
__device__ __forceinline__ cf csq(cf a) { return {fmaf(a.r, a.r, -(a.i * a.i)), (a.r + a.r) * a.i}; }
__device__ __forceinline__ cf cexp2(float lm, float th) {
  float m; asm("ex2.approx.ftz.f32 %0, %1;" : "=f"(m) : "f"(lm));
  return {m * __cosf(th), m * __sinf(th)};
}
__device__ __forceinline__ float turns(float w) { return (w - rintf(w)) * 6.283185307179586f; }
__device__ __forceinline__ void kgen_params(unsigned char* sm, int tid, KgIn in, KgState& st) {
  const int warp = tid >> 5, lane = tid & 31;
  float4* par = (float4*)(sm + PR_PAR + warp * 6144) + lane;
  const float dt = bf_round(expf(bf_lo(in.ldt)));
  float v = 0.f;
#pragma unroll 1
  for (int r = 0; r < 2; r++) {
    const float x = -bf_round(expf(bf_lo(in.la))) * dt * 1.4426950408889634f;
    const float w = bf_lo(in.ai) * dt * 0.15915494309189535f;
    const cf c = {2.f * bf_lo(in.cr) * dt, 2.f * bf_lo(in.ci) * dt};
    const cf e2 = cexp2(2.f * x, turns(2.f * w)), e64 = cexp2(64.f * x, turns(64.f * w));
    const cf e4 = csq(e2), e6 = cmul(e2, e4), e128 = csq(e64), e256 = csq(e128), e512 = csq(e256), e1024 = csq(e512);
    const cf c1 = cmul(c, e128), c256 = cmul(c, e256), c512 = cmul(c, e512), c4 = cmul(c, e1024);
    const cf c516 = cmul(c512, e4), c258 = cmul(c256, e2), c260 = cmul(c256, e4), c262 = cmul(c256, e6);
    v += fmaf(c4.r, e1024.r, -(c4.i * e1024.i));
    par[0] = make_float4(x, turns(w), turns(8.f * w), turns(128.f * w));
    par[64] = make_float4(c.r, c.i, c1.r, c1.i);
    par[128] = make_float4(c4.r, c4.i, e64.r, e64.i);
    par[192] = make_float4(c512.r, c512.i, c516.r, c516.i);
    par[256] = make_float4(c256.r, c256.i, c258.r, c258.i);
    par[320] = make_float4(c260.r, c260.i, c262.r, c262.i);
    par += 32;
    in.la >>= 16; in.ai >>= 16; in.cr >>= 16; in.ci >>= 16;
  }
#pragma unroll
  for (int o = 16; o; o >>= 1) v += __shfl_xor_sync(0xffffffffu, v, o);
  __syncwarp();
#pragma unroll
  for (int t = 0; t < 5; t++) { st.acc[t][0] = st.acc[t][1] = st.acc[t][2] = st.acc[t][3] = 0.f; }
  if (lane == 0 && !(warp & 1)) st.acc[0][0] = bf_lo(in.dsk);
  st.v = v;
}
__device__ __forceinline__ void kgen_steps(unsigned char* sm, int tid, KgState& st) {
  const int warp = tid >> 5, lane = tid & 31, g = lane >> 2, q = lane & 3;
  const float4* par = (const float4*)(sm + PR_PAR + warp * 6144) + q;
  const float2* p3 = (const float2*)(par + 192) + (g & 1);
  const float2* p2 = (const float2*)(par + 256 + 64 * ((g >> 1) & 1)) + (g & 1);
  const float g1 = (float)g, g8 = 8.f * g1, g128 = 128.f * g1;
  const int l1 = 4 * (g >> 1) + q, l2 = 4 * (g >> 2) + q;
#pragma unroll 4
  for (int ks = 0; ks < 16; ks++) {
    const float4 P = par[4 * ks], Q = par[64 + 4 * ks], R = par[128 + 4 * ks];
    const float2 c3 = p3[8 * ks], c2 = p2[8 * ks];
    const cf e = cexp2(P.x * g1, P.y * g1), a1 = cexp2(P.x * g8, P.z * g1), t = cexp2(P.x * g128, P.w * g1);
    const cf a2 = cmul(a1, cf{R.z, R.w});
    const cf t1 = {__shfl_sync(0xffffffffu, t.r, l1), __shfl_sync(0xffffffffu, t.i, l1)};
    const cf t2 = {__shfl_sync(0xffffffffu, t.r, l2), __shfl_sync(0xffffffffu, t.i, l2)};
    auto mma = [&](float (&d)[4], cf u, float cr, float ci) {
      const float b0 = fmaf(u.r, cr, -(u.i * ci)), b1 = fmaf(-u.r, ci, -(u.i * cr));
      asm("mma.sync.aligned.m16n8k8.row.col.f32.tf32.tf32.f32 {%0,%1,%2,%3}, {%4,%5,%6,%7}, {%8,%9}, {%0,%1,%2,%3};"
          : "+f"(d[0]), "+f"(d[1]), "+f"(d[2]), "+f"(d[3])
          : "r"(__float_as_uint(a1.r)), "r"(__float_as_uint(a2.r)), "r"(__float_as_uint(a1.i)), "r"(__float_as_uint(a2.i)),
            "r"(__float_as_uint(b0)), "r"(__float_as_uint(b1)));
    };
    mma(st.acc[0], e, Q.x, Q.y);
    mma(st.acc[1], e, Q.z, Q.w);
    mma(st.acc[4], t, R.x, R.y);
    mma(st.acc[2], t2, c2.x, c2.y);
    mma(st.acc[3], t1, c3.x, c3.y);
  }
}
__device__ __forceinline__ void kgen_finish(unsigned char* sm, unsigned short* kd, unsigned short* k2048, int tid, KgState& st) {
  const int warp = tid >> 5, lane = tid & 31, g = lane >> 2, q = lane & 3;
  float4* red = (float4*)(sm + SM_HIN + (warp >> 1) * 3072) + lane;
  if (warp & 1) {
#pragma unroll
    for (int t = 0; t < 5; t++) red[t * 32] = make_float4(st.acc[t][0], st.acc[t][1], st.acc[t][2], st.acc[t][3]);
    red[160].x = st.v;
  }
  named_bar(3, 256);
  if (!(warp & 1)) {
    uint32_t lo[5], hi[5];
#pragma unroll
    for (int t = 0; t < 5; t++) {
      const float4 r = red[t * 32];
      lo[t] = pack_bf16(st.acc[t][0] + r.x, st.acc[t][1] + r.y); hi[t] = pack_bf16(st.acc[t][2] + r.z, st.acc[t][3] + r.w);
    }
    *k2048 = (unsigned short)pack_bf16(st.v + red[160].x, 0.f);
    uint32_t* kw = (uint32_t*)kd;
    kw[lane] = lo[0]; kw[32 + lane] = hi[0]; kw[64 + lane] = lo[1]; kw[96 + lane] = hi[1];
    kw[128 + 2 * g + (q & 1) + 32 * (q >> 1)] = lo[2]; kw[144 + 2 * g + (q & 1) + 32 * (q >> 1)] = hi[2];
    kw[192 + g + 16 * q] = lo[3]; kw[200 + g + 16 * q] = hi[3];
    kd[512 + g + 32 * q] = (unsigned short)lo[4]; kd[528 + g + 32 * q] = (unsigned short)(lo[4] >> 16);
    kd[520 + g + 32 * q] = (unsigned short)hi[4]; kd[536 + g + 32 * q] = (unsigned short)(hi[4] >> 16);
  }
}
constexpr int kd_index(int l) {
  if (l < 256) return l;
  const int sh = l < 512 ? 1 : l < 1024 ? 2 : 3;
  return ((l + (1 << (sh - 1)) - 1 + ((l >> sh) & 1)) >> sh) + 128 * sh;
}
struct KTab { unsigned int e[512 * 4]; };
constexpr KTab make_ktab() {
  KTab t = {};
  for (int it = 0; it < 511; it++) {
    const int l0 = 4 * it, b1 = kd_index(l0) & ~1;
    const unsigned int np = 0x54 + 0x22 * (l0 ? kd_index(l0 - 1) - b1 : 0);
    unsigned int n[4] = {0, 0, 0, 0};
    for (int k = 0; k < 4; k++) n[k] = 0x10 + 0x22 * (kd_index(l0 + k) - b1);
    t.e[4 * it] = 2 * b1 | ((b1 < 638 ? 4u : 0u) << 16);
    t.e[4 * it + 1] = (n[0] + 0x44) | (np << 8) | (n[1] << 16) | (n[0] << 24);
    t.e[4 * it + 2] = n[2] | (n[1] << 8) | (n[3] << 16) | (n[2] << 24);
    t.e[4 * it + 3] = l0 ? 0xffffffffu : 0xffffu;
  }
  return t;
}
__device__ __align__(16) const KTab g_ktab = make_ktab();
template <int NT>
__device__ __forceinline__ void kexpand(uint32_t sb, uint32_t k0, uint32_t k1, uint32_t k2048, int tid, uint4 e) {
#pragma unroll 1
  for (int it = tid; it < 511; it += NT) {
    const uint4 en = __ldg((const uint4*)g_ktab.e + min(it + NT, 511));
    const uint32_t o = e.x & 0xffffu, o2 = o + (e.x >> 16), dst = sb + T_KP + 64 + 16 * it;
#pragma unroll
    for (int c = 0; c < 4; c++) {
      const uint32_t a = c ? k1 + 1280 * (c - 1) : k0;
      const uint32_t x0 = lds32(a + o - 4), x1 = lds32(a + o), x2 = lds32(a + o2);
      sts128(dst + c * KP_BYTES, make_uint4(__byte_perm(x0, x1, e.y) & e.w, __byte_perm(x1, x2, e.y >> 16), __byte_perm(x1, x2, e.z), __byte_perm(x1, x2, e.z >> 16)));
    }
    e = en;
  }
  if (tid < 36) {
    const int c = tid / 9, i = tid - 9 * c;
    uint4 v = make_uint4(0u, 0u, 0u, 0u);
    if (i == 4) {
      uint32_t z, y;
      asm volatile("ld.shared.u16 %0, [%1];" : "=r"(z) : "r"(k2048 + 2 * c) : "memory");
      asm volatile("ld.shared.u16 %0, [%1];" : "=r"(y) : "r"((c ? k1 + 1280 * (c - 1) : k0) + 1278) : "memory");
      v = make_uint4(z | (y << 16), z * 0x10001u, z * 0x10001u, z * 0x10001u);
    }
    sts128(sb + T_KP + c * KP_BYTES + 16 * (i < 4 ? i : 511 + i), v);
  }
  if (tid < 64) sts128(sb + T_U + (tid >> 4) * U_BYTES + (tid & 15) * 16, make_uint4(0u, 0u, 0u, 0u));
  fence_async_smem();
}

template <int NR>
__device__ __forceinline__ void conv_mma(float (&d)[NR], const uint32_t* a, uint64_t db) {
  if constexpr (NR == 64) wg_cv128<0>(d, a[0], a[1], a[2], a[3], db);
  else if constexpr (NR == 48) wg_cv96<0>(d, a[0], a[1], a[2], a[3], db);
  else if constexpr (NR == 32) wg_cv64<0>(d, a[0], a[1], a[2], a[3], db);
  else wg_rs32<0>(d, a[0], a[1], a[2], a[3], db);
}
__device__ __forceinline__ void conv_load(uint32_t (&a)[8], uint32_t o) {
#pragma unroll
  for (int c = 0; c < 2; c++) {
    a[4 * c + 0] = lds32(o + c * KP_BYTES); a[4 * c + 1] = lds32(o + c * KP_BYTES + 512);
    a[4 * c + 2] = lds32(o + c * KP_BYTES - 32); a[4 * c + 3] = lds32(o + c * KP_BYTES + 480);
  }
}
template <int NR>
__device__ __forceinline__ void conv_phase(float (&dA)[NR], float (&dB)[NR], uint32_t (&a)[4][8], uint32_t kp, uint64_t dU) {
#pragma unroll
  for (int i = 0; i < 2; i++) {
#pragma unroll
    for (int k = 0; k < 4; k++) {
      wg_fence();
      if constexpr (NR == 64) {
        if (i == 0 && k == 0) { wg_cv128_init<0>(dA, a[0][0], a[0][1], a[0][2], a[0][3], dU); wg_cv128_init<0>(dB, a[0][4], a[0][5], a[0][6], a[0][7], dU + (U_BYTES >> 4)); }
        else { conv_mma<NR>(dA, a[k], dU - 2 * k); conv_mma<NR>(dB, a[k] + 4, dU - 2 * k + (U_BYTES >> 4)); }
      } else { conv_mma<NR>(dA, a[k], dU - 2 * k); conv_mma<NR>(dB, a[k] + 4, dU - 2 * k + (U_BYTES >> 4)); }
      wg_commit();
      wg_wait<1>();
      if (k == 2 && i) kp += 64 * 24;
      conv_load(a[(k + 2) & 3], kp + 64 * (k + 2));
    }
    kp += 256;
    dU -= 8;
  }
  wg_wait<0>();
  reg_fence(dA); reg_fence(dB);
}
template <int NR>
__device__ __forceinline__ void upper_copy(float (&dst)[NR - 16], const float (&src)[NR]) {
#pragma unroll
  for (int i = 0; i < NR - 16; i++) asm volatile("mov.b32 %0, %1;" : "=f"(dst[i]) : "f"(src[i + 16]));
}
__device__ __forceinline__ void conv2(uint32_t sb, int wg, int w, int lane) {
  const int g = lane >> 2, q = lane & 3;
  float dA[64], dB[64];
  uint32_t a[4][8];
  const uint32_t kp = sb + T_KP + 2 * wg * KP_BYTES + 4 * (16 + 256 * (w >> 1) + 8 * (w & 1) + g - 2 * q);
  const uint64_t dU = mk_desc(sb + T_U + 2 * wg * U_BYTES + 256, 16, 256, 3);
  conv_load(a[0], kp); conv_load(a[1], kp + 64);
  conv_phase<64>(dA, dB, a, kp, dU);
  float eA[48], eB[48];
  upper_copy<64>(eA, dA); upper_copy<64>(eB, dB);
  conv_phase<48>(eA, eB, a, kp + 2048, dU);
  float fA[32], fB[32];
  upper_copy<48>(fA, eA); upper_copy<48>(fB, eB);
  conv_phase<32>(fA, fB, a, kp + 4096, dU);
  float gA[16], gB[16];
  upper_copy<32>(gA, fA); upper_copy<32>(gB, fB);
  conv_phase<16>(gA, gB, a, kp + 6144, dU);
#pragma unroll
  for (int i = 0; i < 16; i++) {
    dA[16 + i] = eA[i]; dA[32 + i] = fA[i]; dA[48 + i] = gA[i];
    dB[16 + i] = eB[i]; dB[32 + i] = fB[i]; dB[48 + i] = gB[i];
  }
  float z[2][16][2];
#pragma unroll
  for (int m = 0; m < 16; m++)
#pragma unroll
    for (int e = 0; e < 2; e++) {
      z[0][m][e] = m ? dA[4 * m + e] + dA[4 * m - 2 + e] : dA[e];
      z[1][m][e] = m ? dB[4 * m + e] + dB[4 * m - 2 + e] : dB[e];
    }
  const uint32_t xb = sb + T_X0 + wg * 8192, xc = wg ? T_X1 - T_X0 - 8192 : 4096;
  const uint32_t xw = xb + (w * 32 + lane) * 16, xr = xb + ((w ^ 2) * 32 + lane) * 16;
  float k[2][8][2];
  if (w < 2) {
#pragma unroll
    for (int c = 0; c < 2; c++)
#pragma unroll
      for (int m = 0; m < 8; m += 4) {
        sts128(xw + c * xc + (m >> 2) * 2048, make_uint4(pack_bf16(z[c][8 + m][0], z[c][8 + m][1]), pack_bf16(z[c][9 + m][0], z[c][9 + m][1]),
                                                          pack_bf16(z[c][10 + m][0], z[c][10 + m][1]), pack_bf16(z[c][11 + m][0], z[c][11 + m][1])));
#pragma unroll
        for (int i = 0; i < 4; i++) { k[c][m + i][0] = z[c][m + i][0]; k[c][m + i][1] = z[c][m + i][1]; }
      }
  } else {
#pragma unroll
    for (int c = 0; c < 2; c++)
#pragma unroll
      for (int m = 0; m < 8; m += 4) {
        sts128(xw + c * xc + (m >> 2) * 2048, make_uint4(m ? pack_bf16(z[c][m - 2][0], z[c][m - 2][1]) : 0u, m ? pack_bf16(z[c][m - 1][0], z[c][m - 1][1]) : 0u,
                                                          pack_bf16(z[c][m][0], z[c][m][1]), pack_bf16(z[c][m + 1][0], z[c][m + 1][1])));
#pragma unroll
        for (int i = 0; i < 4; i++) { k[c][m + i][0] = z[c][6 + m + i][0]; k[c][m + i][1] = z[c][6 + m + i][1]; }
      }
  }
  named_bar(1 + wg, 128);
  const uint32_t yb = sb + T_U + 2 * wg * U_BYTES;
#pragma unroll
  for (int c = 0; c < 2; c++)
#pragma unroll
    for (int m = 0; m < 8; m += 4) {
      const uint4 u = lds128(xr + c * xc + (m >> 2) * 2048);
      stmatrix_x4_t(yb + c * 4096 + (64 * (w >> 1) + 8 * m + lane) * 32 + 16 * (w & 1),
                    pack_bf16(k[c][m][0] + bf_lo(u.x), k[c][m][1] + bf_hi(u.x)), pack_bf16(k[c][m + 1][0] + bf_lo(u.y), k[c][m + 1][1] + bf_hi(u.y)),
                    pack_bf16(k[c][m + 2][0] + bf_lo(u.z), k[c][m + 2][1] + bf_hi(u.z)), pack_bf16(k[c][m + 3][0] + bf_lo(u.w), k[c][m + 3][1] + bf_hi(u.w)));
    }
  fence_async_smem();
  named_arrive(10 + wg, 160);
}
__device__ __forceinline__ void conv_ship(uint32_t sb, uint32_t bar, int wg, int ch, int cnt, bool el) {
  named_bar(10 + wg, 160);
  if (el) {
    bulk_s2g(g_y + (size_t)ch * L_, sb + T_U + 2 * wg * U_BYTES, 8192);
    bulk_commit_wait();
    cnt_add_done(cnt);
    mbar_arrive(bar + B_SG);
  }
  __syncwarp();
}

__global__ void __cluster_dims__(2, 1, 1) __launch_bounds__(384, 1) fused_kernel(const __grid_constant__ Params p) {
  extern __shared__ __align__(1024) unsigned char smem_raw[];
  const uint32_t sb = smem_u32(smem_raw);
  const uint32_t bar = sb + SM_BAR;
  const uint32_t vb = blockIdx.x;
  const int j = vb & 1, pair = vb >> 1, mt = pair & 15, sp = pair >> 4;
  const bool spare = pair >= 64;
  const int warp = __shfl_sync(0xffffffffu, threadIdx.x >> 5, 0), wg = warp >> 2, w = warp & 3;
  const int row0 = mt * 128 + (2 * sp + j) * 16;
  const int f0 = sp * 1152;
  KgIn kin;
  if (wg < 2) kgen_load(p, spare ? 512 + ((int)vb - 128) * 16 : vb * 4, threadIdx.x, kin);
  if (threadIdx.x >= 288 && threadIdx.x < 301) prefetch_map(&p.xn + (threadIdx.x - 288));
  if (threadIdx.x == 256) {
    mbar_init(bar + B_X, 1);
    if (!spare) {
      mbar_expect_tx(bar + B_X, 16 * D_ * 2);
      bulk_g2s(sb + PR_LN, p.xp + (size_t)row0 * D_, 16 * D_ * 2, bar + B_X);
    }
#pragma unroll
    for (int i = 0; i < 30; i++) if (i != 22) mbar_init(bar + 8 * i, (i >= 7 && i < 14) ? 8 : (i == 27 && !spare) ? 4 : 1);
    mbar_init(bar + B_SG, 2);
    mbar_expect_tx(bar + B_HF, 8192); mbar_expect_tx(bar + B_HF + 8, 8192);
    asm volatile("fence.mbarrier_init.release.cluster;" ::: "memory");
  }
  __syncthreads();
  asm volatile("barrier.cluster.arrive.relaxed.aligned;" ::: "memory");

  if (wg == 2) {
    const int t = threadIdx.x & 127, lane = t & 31;
    const bool el = elect_one();
    if (!spare) {
      const uint32_t ra = sb + PR_LN + (t >> 3) * (D_ * 2) + (t & 7) * 16;
      if (w == 1 && el) {
#pragma unroll 1
        for (int u = 0; u < NST; u++) {
          const uint32_t dst = sb + SM_RING + u * SLOT, fb = bar + B_FULL + 8 * u;
          mbar_expect_tx(fb, 8192);
          tma_2d(dst, &p.gate, f0 + 64 * j, 32 * u, fb);
          tma_2d(dst + 4096, &p.up, f0 + 64 * j, 32 * u, fb);
        }
      }
      mbar_wait(bar + B_X, 0);
      uint4 v[9];
#pragma unroll
      for (int i = 0; i < 9; i++) v[i] = lds128(ra + i * 128);
      uint32_t* u = (uint32_t*)v;
      const float x0 = bf_lo(__shfl_sync(0xffffffffu, u[0], lane & 24));
      float s = 0.f, s2 = 0.f, q = 0.f, q2 = 0.f;
#pragma unroll
      for (int i = 0; i < 36; i++) {
        const float a = bf_lo(u[i]) - x0, b = bf_hi(u[i]) - x0;
        s += a; s2 += b; q = fmaf(a, a, q); q2 = fmaf(b, b, q2);
      }
      s += s2; q += q2;
#pragma unroll
      for (int o = 4; o; o >>= 1) { s += __shfl_xor_sync(0xffffffffu, s, o); q += __shfl_xor_sync(0xffffffffu, q, o); }
      s *= (1.0f / D_);
      const __nv_bfloat162 mb = __float2bfloat162_rn(s + x0);
      const float rinv = 1.0f / bf_round(sqrtf(bf_round(bf_round(fmaxf(fmaf(-s, s, q * (1.0f / D_)), 0.f)) + 1e-5f)));
#pragma unroll
      for (int i = 0; i < 36; i++) {
        const __nv_bfloat162 d2 = __hsub2(*(const __nv_bfloat162*)&u[i], mb);
        const uint32_t d = *(const uint32_t*)&d2;
        u[i] = pack_bf16(bf_lo(d) * rinv, bf_hi(d) * rinv);
      }
#pragma unroll
      for (int i = 0; i < 9; i++) sts128(ra + i * 128, v[i]);
      fence_async_smem();
      named_bar(5, 128);
      if (w == 0 && el) bulk_s2g(g_xn + (size_t)row0 * D_, sb + PR_LN, 16 * D_ * 2);
    }
    asm volatile("barrier.cluster.wait.aligned;" ::: "memory");
    asm volatile("setmaxnreg.dec.sync.aligned.u32 24;");
    if (w == 0) {
      if (!spare) {
        if (el) {
          bulk_commit_wait();
          cnt_add_done(C_LN + mt);
        }
        __syncwarp();
        cnt_wait(C_LN + mt, 8);
        fence_async_all();
#pragma unroll 1
        for (int kb = 0; kb < 6; kb++) {
          if (el) {
            mbar_expect_tx(bar + B_XN + 8 * kb, 16384);
            tma_2d(sb + SM_XN + kb * 16384, &p.xn, kb * 64, mt * 128, bar + B_XN + 8 * kb);
          }
        }
        named_bar(4, 384);
        uint32_t slot = 0, ph = 0;
#pragma unroll 1
        for (int c = 0; c <= 9; c++) {
          const int fc = f0 + c * 128;
          if (c < 9) {
            for (int u = c ? 0 : NST; u < 18; u++) {
              mbar_wait(bar + B_EMPTY + 8 * slot, ph);
              if (el) {
                const uint32_t dst = sb + SM_RING + slot * SLOT, fb = bar + B_FULL + 8 * slot;
                mbar_expect_tx(fb, 8192);
                tma_2d(dst, &p.gate, fc + 64 * j, 32 * u, fb);
                tma_2d(dst + 4096, &p.up, fc + 64 * j, 32 * u, fb);
                if (c == 0 && u < 10) {
                  const int kb = u - 1;
                  if (kb < 8) mbar_expect_tx(bar + B_XN + 8 * kb, kb < 7 ? 16384 : 32768);
                  tma_2d(sb + SM_XN + kb * 16384, &p.xn, kb * 64, mt * 128, bar + B_XN + 8 * min(kb, 7));
                }
              }
              if (++slot == NST) { slot = 0; ph ^= 1; }
            }
          }
          const int fp = (fc - 128 + 64 * (1 - j)) >> 3, fo = fc + 64 * j;
#pragma unroll
          for (int i = 0; i < 8; i++) {
            const bool isP = i < 4;
            const int u = i & 3;
            if (isP ? (c == 0) : (c == 9)) continue;
            mbar_wait(bar + B_EMPTY + 8 * slot, ph);
            if (el) {
              const uint32_t dst = sb + SM_RING + slot * SLOT, fb = bar + B_FULL + 8 * slot;
              mbar_expect_tx(fb, 9216);
              if (isP) {
                tma_5d(dst, &p.dp, 0, 0, fp + 4 * (u >> 1), 2 * (u & 1), 4 * j, fb);
                tma_4d(dst + 8192, &p.dp5, 512 + 32 * j, 0, fp + 4 * (u >> 1), 2 * (u & 1), fb);
              } else {
                tma_3d(dst, &p.dn, 0, fo + 16 * u, 4 * j, fb);
                tma_2d(dst + 8192, &p.dn5, 512 + 32 * j, fo + 16 * u, fb);
              }
            }
            if (++slot == NST) { slot = 0; ph ^= 1; }
          }
        }
        const int ch0 = vb * 4;
        cnt_wait(C_U, 384);
        fence_async_all();
        if (el) {
          mbar_expect_tx(bar + B_CV, 4 * L_ * 2);
#pragma unroll 1
          for (int c = 0; c < 4; c++) bulk_g2s(sb + T_U + c * U_BYTES + 256, g_u + (size_t)(ch0 + c) * L_, L_ * 2, bar + B_CV);
        }
        unsigned char* img = g_part + (size_t)(2 * mt + j) * 16 * IMG;
        mbar_wait(bar + B_SG, 0);
        if (lane < 6) {
          const int r = (sp + 1 + (lane >> 1)) & 3;
          if (lane & 1) bulk_s2g(img + (r * 4 + sp) * IMG + 16384, sb + T_STG + 65536 + (r >> 1) * 8192 + (r & 1) * 2048, 2048);
          else bulk_s2g(img + (r * 4 + sp) * IMG, sb + T_STG + r * 16384, 16384);
          bulk_commit_wait();
        } else if (lane == 6) {
          mbar_expect_tx(bar + B_PT, 3 * IMG);
          mbar_expect_tx(bar + B_X, IMG);
          tma_2d(sb + T_PART + 3 * IMG, &p.x, 256 * j + 64 * sp, mt * 128, bar + B_X);
          tma_2d(sb + T_PART + 3 * IMG + 16384, &p.x5, 512 + 32 * j, mt * 128 + 32 * sp, bar + B_X);
        }
        __syncwarp();
        if (el) cnt_add_done(C_PART + 2 * mt + j);
        cnt_wait(C_PART + 2 * mt + j, 4);
        fence_async_all();
        if (lane < 3) bulk_g2s(sb + T_PART + lane * IMG, img + (sp * 4 + ((sp + 1 + lane) & 3)) * IMG, IMG, bar + B_PT);
        cnt_wait(C_Y5, 32);
        mbar_wait(bar + B_SG, 1);
        if (el) {
          mbar_expect_tx(bar + B_YT, IMG);
          tma_2d(sb + T_YT + 16384, &p.y5, mt * 128 + 32 * sp, 512 + 32 * j, bar + B_YT);
        }
        cnt_wait(C_Y + 4 * j + sp, 32);
        fence_async_all();
        if (el) {
          tma_2d(sb + T_YT, &p.y, mt * 128, 256 * j + 64 * sp, bar + B_YT);
          tma_2d(sb + T_YT + 8192, &p.y, mt * 128 + 64, 256 * j + 64 * sp, bar + B_YT);
        }
      } else {
        named_bar(7, 288);
        cnt_wait(C_U, 384);
        fence_async_all();
#pragma unroll 1
        for (int grp = 0; grp < 4; grp++) {
          const int ch0 = 512 + ((int)vb - 128) * 16 + grp * 4;
          if (grp) mbar_wait(bar + B_SG, (grp - 1) & 1);
          if (el) {
            mbar_expect_tx(bar + B_CV, 4 * L_ * 2);
#pragma unroll 1
            for (int c = 0; c < 4; c++) bulk_g2s(sb + T_U + c * U_BYTES + 256, g_u + (size_t)(ch0 + c) * L_, L_ * 2, bar + B_CV);
          }
        }
      }
      unsigned int old = 0;
      if (el) old = atomicAdd(g_cnt + C_DONE * 32, 1u) + 1;
      if (__any_sync(0xffffffffu, old == gridDim.x)) { g_cnt[lane * 32] = 0u; g_cnt[(lane + 32) * 32] = 0u; }
    } else {
      if (!spare) {
        named_bar(4, 384);
        uint4 k0v = make_uint4(0u, 0u, 0u, 0u);
        if (t < 112) k0v = lds128(sb + PR_K0 + (t - 32) * 16);
        named_bar(8, 96);
        if (t == 32) { mbar_arrive_remote(mapa(bar + B_HE, j ^ 1)); mbar_arrive_remote(mapa(bar + B_HE + 8, j ^ 1)); }
#pragma unroll 1
        for (int i = 0; i < 8; i++) mbar_wait(bar + B_XN + 8 * i, 0);
        const int tok = 8 * ((lane & 7) >> 1) + 2 * (lane >> 3) + (lane & 1);
#pragma unroll 1
        for (int it = w - 1; it < 36; it += 3) {
          const int oc = 9 * (2 * sp + j) + (it >> 2), tg = it & 3;
          uint4 v;
          ldmatrix_x4_t(sb + SM_XN + (oc >> 3) * 16384 + (32 * tg + tok) * 128 + (((oc ^ tok) & 7) << 4), v.x, v.y, v.z, v.w);
          ((uint4*)(g_u + (size_t)(8 * oc + (lane >> 2)) * L_ + mt * 128))[(4 * tg + (lane & 3)) ^ (tg >> 1)] = v;
        }
        __syncwarp();
        if (lane == 0) { fence_async_all(); cnt_add(C_U); }
        const uint4 e0 = __ldg((const uint4*)g_ktab.e + (t - 32));
        named_bar(9, 352);
        if (t < 112) sts128(sb + T_K0 + (t - 32) * 16, k0v);
        named_bar(8, 96);
        kexpand<96>(sb, sb + T_K0, sb + SM_KD, bar + B_K2048, t - 32, e0);
        __syncwarp();
        if (lane == 0) mbar_arrive(bar + B_CV);
        if (w < 3) conv_ship(sb, bar, w - 1, vb * 4 + 2 * (w - 1), C_Y + (vb >> 4), el);
      } else if (w < 3) {
#pragma unroll 1
        for (int grp = 0; grp < 4; grp++) conv_ship(sb, bar, w - 1, 512 + ((int)vb - 128) * 16 + grp * 4 + 2 * (w - 1), C_Y5, el);
      }
    }
  } else {
    const int t = threadIdx.x & 127, lane = t & 31;
    KgState kst;
    kgen_params(smem_raw, threadIdx.x, kin, kst);
    if (!spare) {
      kgen_steps(smem_raw, threadIdx.x, kst);
      kgen_finish(smem_raw, (unsigned short*)(smem_raw + (warp < 2 ? PR_K0 : SM_KD + ((warp >> 1) - 1) * 1280)),
                  (unsigned short*)(smem_raw + SM_BAR + B_K2048) + (warp >> 1), threadIdx.x, kst);
      named_arrive(4, 384);
    } else {
      const int c0 = 512 + ((int)vb - 128) * 16;
#pragma unroll 1
      for (int grp = 0; grp < 4; grp++) {
        if (grp) { kgen_load(p, c0 + grp * 4, threadIdx.x, kin); kgen_params(smem_raw, threadIdx.x, kin, kst); }
        kgen_steps(smem_raw, threadIdx.x, kst);
        kgen_finish(smem_raw, (unsigned short*)(smem_raw + SM_RING + (grp * 4 + (warp >> 1)) * 1280),
                    (unsigned short*)(smem_raw + SM_KD) + grp * 4 + (warp >> 1), threadIdx.x, kst);
        named_bar(3, 256);
      }
      named_arrive(7, 288);
    }
    asm volatile("barrier.cluster.wait.aligned;" ::: "memory");
    asm volatile("setmaxnreg.inc.sync.aligned.u32 240;");
    if (!spare) {
      const bool leader = (t == 0);
      float O1[128], O2[16];
      uint32_t slot = 0, ph = 0, prev = 0;
      const uint32_t hin = sb + SM_HIN + wg * 8192;
      const uint32_t r_hin = mapa(hin + (16 * w + (lane >> 2)) * 128 + (((lane & 3) ^ (lane >> 2)) << 4), j ^ 1);
      const uint32_t r_hf = mapa(bar + B_HF + 8 * wg, j ^ 1), r_he = mapa(bar + B_HE + 8 * wg, j ^ 1);
      const uint64_t dA0 = mk_desc(sb + SM_XN + wg * 8192, 16, 1024, 1);
      const uint64_t dH0 = mk_desc(hin, 16, 1024, 1);
      const uint64_t dG0 = mk_desc(sb + SM_RING, 4096, 1024, 1);
      const uint64_t dW0 = mk_desc(sb + SM_RING, 2048, 1024, 1);
      const uint64_t dX0 = mk_desc(sb + SM_RING + 8192, 512, 512, 2);
      auto adv = [&]() { prev = slot; if (++slot == NST) { slot = 0; ph ^= 1; } };
      auto release = [&](uint32_t s) { if (lane == 0) mbar_arrive(bar + B_EMPTY + 8 * s); };
      auto peer_begin = [&](int cp) {
        mbar_wait(bar + B_HF + 8 * wg, cp & 1);
        if (leader && cp < 8) mbar_expect_tx(bar + B_HF + 8 * wg, 8192);
        fence_async_smem();
      };
      auto peer_unit = [&](int u) {
        wg_fence();
        wg_ss256<1>(O1, dH0 + 2 * u, dW0 + (uint64_t)(slot * (SLOT >> 4)));
        wg_ss32<1>(O2, dH0 + 2 * u, dX0 + (uint64_t)(slot * (SLOT >> 4)));
        wg_commit();
      };
      auto chunk = [&](auto first_c, const int c) {
        constexpr bool FIRST = decltype(first_c)::value;
        float S[64];
        {
          if (FIRST) mbar_wait(bar + B_XN, 0);
          mbar_wait(bar + B_FULL + 8 * slot, ph);
          const uint64_t db = dG0 + (uint64_t)(slot * (SLOT >> 4));
          wg_fence();
          wg_ss128_init<1>(S, dA0, db);
          wg_ss128<1>(S, dA0 + 2, db + 128);
          wg_commit();
          adv();
        }
#pragma unroll 1
        for (int u = 1; u < 18; u++) {
          if (FIRST && !(u & 1) && u < 16) mbar_wait(bar + B_XN + 8 * (u >> 1), 0);
          mbar_wait(bar + B_FULL + 8 * slot, ph);
          const uint64_t da = dA0 + (uint64_t)((u >> 1) * 1024 + (u & 1) * 4);
          const uint64_t db = dG0 + (uint64_t)(slot * (SLOT >> 4));
          wg_fence();
          wg_ss128<1>(S, da, db);
          wg_ss128<1>(S, da + 2, db + 128);
          wg_commit();
          if constexpr (!FIRST) { if (u == 12) peer_begin(c - 1); }
          wg_wait<1>();
          release(prev);
          if (c == 8 && u == 8) named_arrive(9, 352);
          adv();
        }
        uint32_t H[16];
        if constexpr (FIRST) { wg_wait<0>(); release(prev); }
        uint32_t rs = prev;
        auto rel_next = [&]() { release(rs); if (++rs == NST) rs = 0; };
        auto P = [&](int u) {
          mbar_wait(bar + B_FULL + 8 * slot, ph);
          peer_unit(u);
          if (u) { wg_wait<2>(); rel_next(); }
          adv();
        };
        auto E = [&](int u) {
#pragma unroll
          for (int i = 8 * u; i < 8 * u + 8; i++) asm volatile("" : "+f"(S[i]), "+f"(S[32 + i])::"memory");
#pragma unroll
          for (int g = 2 * u; g < 2 * u + 2; g++) {
            H[2 * g] = pack_bf16(geglu(S[4 * g], S[32 + 4 * g]), geglu(S[4 * g + 1], S[33 + 4 * g]));
            H[2 * g + 1] = pack_bf16(geglu(S[4 * g + 2], S[34 + 4 * g]), geglu(S[4 * g + 3], S[35 + 4 * g]));
          }
#pragma unroll
          for (int i = 4 * u; i < 4 * u + 4; i++) asm volatile("" : "+r"(H[i])::"memory");
        };
        auto O = [&](int u) {
          mbar_wait(bar + B_FULL + 8 * slot, ph);
          wg_fence();
          if (FIRST && u == 0) {
            wg_rs256_init<1>(O1, H[0], H[1], H[2], H[3], dW0 + (uint64_t)(slot * (SLOT >> 4)));
            wg_rs32_init<1>(O2, H[0], H[1], H[2], H[3], dX0 + (uint64_t)(slot * (SLOT >> 4)));
            rs = slot;
          } else {
            wg_rs256<1>(O1, H[4 * u], H[4 * u + 1], H[4 * u + 2], H[4 * u + 3], dW0 + (uint64_t)(slot * (SLOT >> 4)));
            wg_rs32<1>(O2, H[4 * u], H[4 * u + 1], H[4 * u + 2], H[4 * u + 3], dX0 + (uint64_t)(slot * (SLOT >> 4)));
          }
          wg_commit();
          if (u == 3) {
            mbar_wait(bar + B_HE + 8 * wg, c & 1);
            st_async_v4(r_hin, H[0], H[2], H[4], H[6], r_hf);
            st_async_v4(r_hin ^ 64, H[8], H[10], H[12], H[14], r_hf);
            st_async_v4(r_hin + 1024, H[1], H[3], H[5], H[7], r_hf);
            st_async_v4((r_hin ^ 64) + 1024, H[9], H[11], H[13], H[15], r_hf);
          }
          if (!FIRST || u >= 2) { wg_wait<2>(); rel_next(); }
          if (u == 1) { if constexpr (!FIRST) { if (leader) mbar_arrive_remote(r_he); } }
          if (u == 3) { wg_wait<1>(); rel_next(); wg_wait<0>(); rel_next(); }
          adv();
        };
        if constexpr (FIRST) { E(0); O(0); E(1); O(1); E(2); O(2); E(3); O(3); }
        else { P(0); P(1); E(0); P(2); E(1); P(3); O(0); E(2); O(1); O(2); E(3); O(3); }
      };
      chunk(std::true_type{}, 0);
#pragma unroll 1
      for (int c = 1; c < 9; c++) chunk(std::false_type{}, c);
      peer_begin(8);
#pragma unroll 1
      for (int u = 0; u < 4; u++) { mbar_wait(bar + B_FULL + 8 * slot, ph); peer_unit(u); adv(); }
      wg_wait<0>();
      reg_fence(O1); reg_fence(O2);
      const int mi = lane >> 3, li = lane & 7;
      {
        const int row = 16 * w + 8 * (mi & 1) + li;
        const uint32_t stg = sb + T_STG + wg * 8192 + row * 128;
#pragma unroll
        for (int g = 0; g < 32; g += 2)
          stmatrix_x4(stg + (g >> 3) * 16384 + ((((g & 7) + (mi >> 1)) ^ li) << 4), pack_bf16(O1[4 * g], O1[4 * g + 1]), pack_bf16(O1[4 * g + 2], O1[4 * g + 3]),
                      pack_bf16(O1[4 * g + 4], O1[4 * g + 5]), pack_bf16(O1[4 * g + 6], O1[4 * g + 7]));
#pragma unroll
        for (int g = 0; g < 4; g += 2)
          stmatrix_x4(stg + 65536 - row * 64 + (((g + (mi >> 1)) ^ (li >> 1)) << 4), pack_bf16(O2[4 * g], O2[4 * g + 1]), pack_bf16(O2[4 * g + 2], O2[4 * g + 3]),
                      pack_bf16(O2[4 * g + 4], O2[4 * g + 5]), pack_bf16(O2[4 * g + 6], O2[4 * g + 7]));
        fence_async_smem();
        named_bar(1 + wg, 128);
        if (leader) mbar_arrive(bar + B_SG);
      }
      mbar_wait(bar + B_CV, 0);
      conv2(sb, wg, w, lane);
      const uint32_t rowi = 8 * (mi & 1) + li;
      const uint32_t own_m = sb + T_STG + sp * 16384, own_t = sb + T_STG + 65536 - 16384 + (sp >> 1) * 8192 + (sp & 1) * 2048;
      auto off = [&](int k) -> uint32_t {
        return k < 4 ? (16 * warp + rowi) * 128 + (((2 * k + (mi >> 1)) ^ li) << 4) : 16384 + (16 * warp + rowi) * 64 + (((2 * (k - 4) + (mi >> 1)) ^ (li >> 1)) << 4);
      };
      float f[6][8];
#pragma unroll
      for (int k = 0; k < 6; k++)
#pragma unroll
        for (int i = 0; i < 8; i++) f[k][i] = 0.f;
      named_bar(3, 256);
#pragma unroll 1
      for (int rep = 0; rep < 2; rep++) {
      mbar_wait(bar + (rep ? B_PT : B_X), rep ^ 1);
#pragma unroll 1
      for (int s = 2 * rep; s < 2 + 3 * rep; s++) {
        const uint32_t am = s ? sb + T_PART + (4 - s) * IMG : own_m, at = s ? am : own_t;
#pragma unroll
        for (int k = 0; k < 6; k++) {
          if (k >= 4 && warp >= 2) break;
          uint32_t r[4];
          ldmatrix_x4((k < 4 ? am : at) + off(k), r);
#pragma unroll
          for (int i = 0; i < 4; i++) { f[k][2 * i] += bf_lo(r[i]); f[k][2 * i + 1] += bf_hi(r[i]); }
        }
      }
      if (rep) mbar_wait(bar + B_YT, 0);
#pragma unroll
      for (int k = 0; k < 6; k++) {
        if (k >= 4 && warp >= 2) break;
        const uint32_t ya = k < 4 ? (warp >> 2) * 8192 + (16 * k + 8 * (mi >> 1) + li) * 128 + (((2 * (warp & 3) + (mi & 1)) ^ li) << 4)
                                  : 16384 + (16 * (k - 4) + 8 * (mi >> 1) + li) * 64 + (((2 * warp + (mi & 1)) ^ (li >> 1)) << 4);
        uint32_t y0, y1, y2, y3;
        ldmatrix_x4_t(sb + T_YT + ya, y0, y1, y2, y3);
        stmatrix_x4((k < 4 ? own_m : own_t) + off(k), pack_bf16(f[k][0] + bf_lo(y0), f[k][1] + bf_hi(y0)), pack_bf16(f[k][2] + bf_lo(y1), f[k][3] + bf_hi(y1)),
                    pack_bf16(f[k][4] + bf_lo(y2), f[k][5] + bf_hi(y2)), pack_bf16(f[k][6] + bf_lo(y3), f[k][7] + bf_hi(y3)));
      }
      fence_async_smem();
      __syncwarp();
      }
      if (lane == 0) {
        tma_store_2d(&p.out, own_m + warp * 2048, 256 * j + 64 * sp, mt * 128 + 16 * warp);
        if (warp < 2) tma_store_2d(&p.out5, own_t + 16384 + warp * 1024, 512 + 32 * j, mt * 128 + 32 * sp + 16 * warp);
        asm volatile("cp.async.bulk.commit_group;" ::: "memory");
        asm volatile("cp.async.bulk.wait_group.read 0;" ::: "memory");
      }
    } else {
#pragma unroll 1
      for (int grp = 0; grp < 4; grp++) {
        if (grp) mbar_wait(bar + B_SG, (grp - 1) & 1);
        kexpand<256>(sb, sb + SM_RING + grp * 5120, sb + SM_RING + grp * 5120 + 1280, sb + SM_KD + 8 * grp, threadIdx.x, __ldg((const uint4*)g_ktab.e + threadIdx.x));
        named_bar(3, 256);
        mbar_wait(bar + B_CV, grp & 1);
        conv2(sb, wg, w, lane);
        named_bar(3, 256);
      }
    }
  }
}

typedef CUresult (*PFN_enc)(CUtensorMap*, CUtensorMapDataType, cuuint32_t, void*, const cuuint64_t*, const cuuint64_t*, const cuuint32_t*,
                            const cuuint32_t*, CUtensorMapInterleave, CUtensorMapSwizzle, CUtensorMapL2promotion, CUtensorMapFloatOOBfill);

void enc(PFN_enc fn, CUtensorMap* m, void* ptr, int rank, const cuuint64_t* dims, const cuuint64_t* strides, const cuuint32_t* box, CUtensorMapSwizzle sw) {
  cuuint32_t es[5] = {1, 1, 1, 1, 1};
  fn(m, CU_TENSOR_MAP_DATA_TYPE_BFLOAT16, rank, ptr, dims, strides, box, es, CU_TENSOR_MAP_INTERLEAVE_NONE, sw,
     CU_TENSOR_MAP_L2_PROMOTION_L2_128B, CU_TENSOR_MAP_FLOAT_OOB_FILL_NONE);
}

}

extern "C" void kernel_launch(void* const* d_in, const int* in_sizes, int n_in, void* d_out, int out_size) {
  static Params pr;
  static void* key[5] = {nullptr, nullptr, nullptr, nullptr, nullptr};
  if (key[0] != d_in[8] || key[1] != d_in[9] || key[2] != d_in[10] || key[3] != d_in[0] || key[4] != d_out) {
    key[0] = d_in[8]; key[1] = d_in[9]; key[2] = d_in[10]; key[3] = d_in[0]; key[4] = d_out;
    void* fnp = nullptr; cudaDriverEntryPointQueryResult st;
    cudaGetDriverEntryPoint("cuTensorMapEncodeTiled", &fnp, cudaEnableDefault, &st);
    PFN_enc fn = (PFN_enc)fnp;
    void *p_xn, *p_y;
    cudaGetSymbolAddress(&p_xn, g_xn); cudaGetSymbolAddress(&p_y, g_y);
    { cuuint64_t d[2] = {D_, L_}, s[1] = {D_ * 2};
      { cuuint32_t b[2] = {64, 128}; enc(fn, &pr.xn, p_xn, 2, d, s, b, CU_TENSOR_MAP_SWIZZLE_128B); }
      { cuuint32_t b[2] = {64, 128}; enc(fn, &pr.x, d_in[0], 2, d, s, b, CU_TENSOR_MAP_SWIZZLE_128B); }
      { cuuint32_t b[2] = {64, 16}; enc(fn, &pr.out, d_out, 2, d, s, b, CU_TENSOR_MAP_SWIZZLE_128B); }
      { cuuint32_t b[2] = {32, 32}; enc(fn, &pr.x5, d_in[0], 2, d, s, b, CU_TENSOR_MAP_SWIZZLE_64B); }
      { cuuint32_t b[2] = {32, 16}; enc(fn, &pr.out5, d_out, 2, d, s, b, CU_TENSOR_MAP_SWIZZLE_64B); } }
    { cuuint64_t d[2] = {F_, D_}, s[1] = {F_ * 2}; cuuint32_t b[2] = {64, 32};
      enc(fn, &pr.gate, d_in[8], 2, d, s, b, CU_TENSOR_MAP_SWIZZLE_128B); enc(fn, &pr.up, d_in[9], 2, d, s, b, CU_TENSOR_MAP_SWIZZLE_128B); }
    { void* wd = d_in[10];
      { cuuint64_t d[3] = {64, F_, 9}, s[2] = {D_ * 2, 128}; cuuint32_t b[3] = {64, 16, 4}; enc(fn, &pr.dn, wd, 3, d, s, b, CU_TENSOR_MAP_SWIZZLE_128B); }
      { cuuint64_t d[2] = {D_, F_}, s[1] = {D_ * 2}; cuuint32_t b[2] = {32, 16}; enc(fn, &pr.dn5, wd, 2, d, s, b, CU_TENSOR_MAP_SWIZZLE_64B); }
      { cuuint64_t d[5] = {64, 2, F_ / 8, 4, 9}, s[4] = {D_ * 2, D_ * 16, D_ * 4, 128}; cuuint32_t b[5] = {64, 2, 4, 2, 4};
        enc(fn, &pr.dp, wd, 5, d, s, b, CU_TENSOR_MAP_SWIZZLE_128B); }
      { cuuint64_t d[4] = {D_, 2, F_ / 8, 4}, s[3] = {D_ * 2, D_ * 16, D_ * 4}; cuuint32_t b[4] = {32, 2, 4, 2};
        enc(fn, &pr.dp5, wd, 4, d, s, b, CU_TENSOR_MAP_SWIZZLE_64B); }
    }
    { cuuint64_t d[2] = {L_, D_}, s[1] = {L_ * 2};
      { cuuint32_t b[2] = {64, 64}; enc(fn, &pr.y, p_y, 2, d, s, b, CU_TENSOR_MAP_SWIZZLE_128B); }
      { cuuint32_t b[2] = {32, 32}; enc(fn, &pr.y5, p_y, 2, d, s, b, CU_TENSOR_MAP_SWIZZLE_64B); } }
    cudaFuncSetAttribute(fused_kernel, cudaFuncAttributeMaxDynamicSharedMemorySize, SMEM_BYTES);
  }
  const __nv_bfloat16* const* in = (const __nv_bfloat16* const*)d_in;
  pr.xp = in[0]; pr.logA = in[1]; pr.Aim = in[2]; pr.Cre = in[3]; pr.Cim = in[4]; pr.logdt = in[5]; pr.Dsk = in[6];
  fused_kernel<<<132, 384, SMEM_BYTES>>>(pr);
}
```

```cpp
#include <cuda_runtime.h>
#include <cuda_bf16.h>
#include <cuda.h>
#include <stdint.h>
#include <type_traits>

namespace {

constexpr int L_ = 2048, D_ = 576, F_ = 4608, NM_ = 128;
constexpr int KP_LEN = 2080;
constexpr int U_LEN = 2176;

__device__ __align__(1024) __nv_bfloat16 g_xn[L_ * D_];
__device__ __align__(1024) __nv_bfloat16 g_u[D_ * L_];
__device__ __align__(1024) unsigned char g_part[32 * 16 * 18432];
__device__ __align__(1024) __nv_bfloat16 g_y[D_ * L_];
__device__ __align__(1024) unsigned int g_cnt[64 * 32];
constexpr int C_LN = 0, C_PART = 16, C_U = 48, C_Y = 49, C_Y5 = 57, C_DONE = 58;

__device__ __forceinline__ uint32_t smem_u32(const void* p) { return (uint32_t)__cvta_generic_to_shared(p); }
__device__ __forceinline__ void mbar_init(uint32_t bar, uint32_t cnt) { asm volatile("mbarrier.init.shared::cta.b64 [%0], %1;" ::"r"(bar), "r"(cnt)); }
__device__ __forceinline__ void mbar_expect_tx(uint32_t bar, uint32_t bytes) { asm volatile("mbarrier.arrive.expect_tx.shared::cta.b64 _, [%0], %1;" ::"r"(bar), "r"(bytes) : "memory"); }
__device__ __forceinline__ void mbar_arrive(uint32_t bar) { asm volatile("mbarrier.arrive.shared::cta.b64 _, [%0];" ::"r"(bar) : "memory"); }
__device__ __forceinline__ void mbar_arrive_remote(uint32_t bar) { asm volatile("mbarrier.arrive.shared::cluster.b64 _, [%0];" ::"r"(bar) : "memory"); }
__device__ __forceinline__ void mbar_wait(uint32_t bar, uint32_t parity) {
  asm volatile("{\n.reg .pred p, q;\n.reg .u32 n;\nmov.u32 n, 0;\nLW:\nmbarrier.try_wait.parity.shared::cta.b64 p, [%0], %1;\n"
               "add.u32 n, n, 1;\nsetp.lt.and.u32 q, n, 65536, !p;\n@q bra LW;\n}" ::"r"(bar), "r"(parity) : "memory");
}
__device__ __forceinline__ bool elect_one() {
  uint32_t ok;
  asm volatile("{\n.reg .pred p;\nelect.sync _|p, 0xffffffff;\nselp.u32 %0, 1, 0, p;\n}" : "=r"(ok));
  return ok;
}
__device__ __forceinline__ void tma_2d(uint32_t dst, const CUtensorMap* map, int c0, int c1, uint32_t bar) {
  asm volatile("cp.async.bulk.tensor.2d.shared::cluster.global.mbarrier::complete_tx::bytes [%0], [%1, {%3, %4}], [%2];"
               ::"r"(dst), "l"(map), "r"(bar), "r"(c0), "r"(c1) : "memory");
}
__device__ __forceinline__ void tma_3d(uint32_t dst, const CUtensorMap* map, int c0, int c1, int c2, uint32_t bar) {
  asm volatile("cp.async.bulk.tensor.3d.shared::cluster.global.mbarrier::complete_tx::bytes [%0], [%1, {%3, %4, %5}], [%2];"
               ::"r"(dst), "l"(map), "r"(bar), "r"(c0), "r"(c1), "r"(c2) : "memory");
}
__device__ __forceinline__ void tma_4d(uint32_t dst, const CUtensorMap* map, int c0, int c1, int c2, int c3, uint32_t bar) {
  asm volatile("cp.async.bulk.tensor.4d.shared::cluster.global.mbarrier::complete_tx::bytes [%0], [%1, {%3, %4, %5, %6}], [%2];"
               ::"r"(dst), "l"(map), "r"(bar), "r"(c0), "r"(c1), "r"(c2), "r"(c3) : "memory");
}
__device__ __forceinline__ void tma_5d(uint32_t dst, const CUtensorMap* map, int c0, int c1, int c2, int c3, int c4, uint32_t bar) {
  asm volatile("cp.async.bulk.tensor.5d.shared::cluster.global.mbarrier::complete_tx::bytes [%0], [%1, {%3, %4, %5, %6, %7}], [%2];"
               ::"r"(dst), "l"(map), "r"(bar), "r"(c0), "r"(c1), "r"(c2), "r"(c3), "r"(c4) : "memory");
}
__device__ __forceinline__ void bulk_g2s(uint32_t dst, const void* src, uint32_t bytes, uint32_t bar) {
  asm volatile("cp.async.bulk.shared::cluster.global.mbarrier::complete_tx::bytes [%0], [%1], %2, [%3];"
               ::"r"(dst), "l"(src), "r"(bytes), "r"(bar) : "memory");
}
__device__ __forceinline__ void prefetch_map(const CUtensorMap* m) { asm volatile("prefetch.tensormap [%0];" ::"l"(m) : "memory"); }
__device__ __forceinline__ uint32_t mapa(uint32_t addr, uint32_t rank) { uint32_t r; asm volatile("mapa.shared::cluster.u32 %0, %1, %2;" : "=r"(r) : "r"(addr), "r"(rank)); return r; }
__device__ __forceinline__ void fence_async_smem() { asm volatile("fence.proxy.async.shared::cta;" ::: "memory"); }
__device__ __forceinline__ void wg_fence() { asm volatile("wgmma.fence.sync.aligned;" ::: "memory"); }
__device__ __forceinline__ void wg_commit() { asm volatile("wgmma.commit_group.sync.aligned;" ::: "memory"); }
template <int N> __device__ __forceinline__ void wg_wait() { asm volatile("wgmma.wait_group.sync.aligned %0;" ::"n"(N) : "memory"); }
template <int N> __device__ __forceinline__ void reg_fence(float (&d)[N]) {
#pragma unroll
  for (int i = 0; i < N; i++) asm volatile("" : "+f"(d[i])::"memory");
}
__device__ __forceinline__ void named_bar(int id, int n) { asm volatile("bar.sync %0, %1;" ::"r"(id), "r"(n) : "memory"); }
__device__ __forceinline__ uint64_t mk_desc(uint32_t addr, uint32_t lbo, uint32_t sbo, uint32_t sw) {
  return (uint64_t)((addr & 0x3FFFF) >> 4) | ((uint64_t)(lbo >> 4) << 16) | ((uint64_t)(sbo >> 4) << 32) | ((uint64_t)sw << 62);
}
__device__ __forceinline__ uint32_t pack_bf16(float lo, float hi) {
  uint32_t r; asm("cvt.rn.bf16x2.f32 %0, %1, %2;" : "=r"(r) : "f"(hi), "f"(lo)); return r;
}
__device__ __forceinline__ float bf_lo(uint32_t v) { return __uint_as_float(v << 16); }
__device__ __forceinline__ float bf_hi(uint32_t v) { return __uint_as_float(v & 0xffff0000u); }
__device__ __forceinline__ float bf_round(float x) { return __bfloat162float(__float2bfloat16_rn(x)); }
__device__ __forceinline__ void st_async_v4(uint32_t addr, uint32_t a, uint32_t b, uint32_t c, uint32_t d, uint32_t bar) {
  asm volatile("st.async.weak.shared::cluster.mbarrier::complete_tx::bytes.v4.b32 [%0], {%1, %2, %3, %4}, [%5];"
               ::"r"(addr), "r"(a), "r"(b), "r"(c), "r"(d), "r"(bar) : "memory");
}
__device__ __forceinline__ void stmatrix_x4_t(uint32_t addr, uint32_t a, uint32_t b, uint32_t c, uint32_t d) {
  asm volatile("stmatrix.sync.aligned.m8n8.x4.trans.shared.b16 [%0], {%1, %2, %3, %4};" ::"r"(addr), "r"(a), "r"(b), "r"(c), "r"(d) : "memory");
}
__device__ __forceinline__ void ldmatrix_x4_t(uint32_t addr, uint32_t& a, uint32_t& b, uint32_t& c, uint32_t& d) {
  asm volatile("ldmatrix.sync.aligned.m8n8.x4.trans.shared.b16 {%0, %1, %2, %3}, [%4];" : "=r"(a), "=r"(b), "=r"(c), "=r"(d) : "r"(addr) : "memory");
}
__device__ __forceinline__ uint32_t lds32(uint32_t addr) { uint32_t v; asm volatile("ld.shared.b32 %0, [%1];" : "=r"(v) : "r"(addr) : "memory"); return v; }

__device__ __forceinline__ uint32_t geglu2(float g0, float g1, float u0, float u1) {
  const uint32_t g = pack_bf16(g0, g1), u = pack_bf16(u0, u1);
  uint32_t t, p, z, th, e, r;
  asm("mul.rn.bf16x2 %0, %1, %1;" : "=r"(t) : "r"(g));
  asm("fma.rn.bf16x2 %0, %1, %2, %3;" : "=r"(p) : "r"(t), "r"(0x3d123d12u), "r"(0x3f4c3f4cu));
  asm("mul.rn.bf16x2 %0, %1, %2;" : "=r"(z) : "r"(g), "r"(p));
  asm("tanh.approx.bf16x2 %0, %1;" : "=r"(th) : "r"(z));
  asm("fma.rn.bf16x2 %0, %1, %2, %1;" : "=r"(e) : "r"(g), "r"(th));
  asm("mul.rn.bf16x2 %0, %1, %2;" : "=r"(r) : "r"(e), "r"(u));
  return r;
}
__device__ __forceinline__ uint4 lds128(uint32_t addr) { uint4 v; asm volatile("ld.shared.v4.b32 {%0,%1,%2,%3}, [%4];" : "=r"(v.x), "=r"(v.y), "=r"(v.z), "=r"(v.w) : "r"(addr) : "memory"); return v; }
__device__ __forceinline__ void stmatrix_x4(uint32_t addr, uint32_t a, uint32_t b, uint32_t c, uint32_t d) {
  asm volatile("stmatrix.sync.aligned.m8n8.x4.shared.b16 [%0], {%1, %2, %3, %4};" ::"r"(addr), "r"(a), "r"(b), "r"(c), "r"(d) : "memory");
}
__device__ __forceinline__ void ldmatrix_x4(uint32_t addr, uint32_t (&r)[4]) {
  asm volatile("ldmatrix.sync.aligned.m8n8.x4.shared.b16 {%0, %1, %2, %3}, [%4];" : "=r"(r[0]), "=r"(r[1]), "=r"(r[2]), "=r"(r[3]) : "r"(addr) : "memory");
}
__device__ __forceinline__ void sts128(uint32_t addr, uint4 v) { asm volatile("st.shared.v4.b32 [%0], {%1,%2,%3,%4};" ::"r"(addr), "r"(v.x), "r"(v.y), "r"(v.z), "r"(v.w) : "memory"); }
__device__ __forceinline__ void bulk_s2g(void* dst, uint32_t src, uint32_t bytes) {
  asm volatile("cp.async.bulk.global.shared::cta.bulk_group [%0], [%1], %2;" ::"l"(dst), "r"(src), "r"(bytes) : "memory");
}
__device__ __forceinline__ void tma_store_2d(const CUtensorMap* map, uint32_t src, int c0, int c1) {
  asm volatile("cp.async.bulk.tensor.2d.global.shared::cta.bulk_group [%0, {%2, %3}], [%1];" ::"l"(map), "r"(src), "r"(c0), "r"(c1) : "memory");
}
__device__ __forceinline__ void bulk_commit_wait() {
  asm volatile("cp.async.bulk.commit_group;" ::: "memory");
  asm volatile("cp.async.bulk.wait_group 0;" ::: "memory");
}
__device__ __forceinline__ void named_arrive(int id, int n) { asm volatile("bar.arrive %0, %1;" ::"r"(id), "r"(n) : "memory"); }
__device__ __forceinline__ void fence_async_all() { asm volatile("fence.proxy.async.global;" ::: "memory"); }
__device__ __forceinline__ void cnt_add(int idx) {
  asm volatile("red.release.gpu.global.add.u32 [%0], 1;" ::"l"(g_cnt + idx * 32) : "memory");
}
__device__ __forceinline__ void cnt_add_done(int idx) {
  asm volatile("red.relaxed.gpu.global.add.u32 [%0], 1;" ::"l"(g_cnt + idx * 32) : "memory");
}
__device__ __forceinline__ void cnt_wait(int idx, uint32_t target) {
  const unsigned int* p = g_cnt + idx * 32;
#pragma unroll 1
  for (int it = 0; it < (1 << 18); it++) {
    uint32_t v; asm volatile("ld.acquire.gpu.global.u32 %0, [%1];" : "=r"(v) : "l"(p) : "memory");
    if (v >= target) break;
  }
}

template <int TB>
__device__ __forceinline__ void wg_ss128_init(float (&d)[64], uint64_t da, uint64_t db) {
  asm volatile(
    "wgmma.mma_async.sync.aligned.m64n128k16.f32.bf16.bf16 {%0, %1, %2, %3, %4, %5, %6, %7, %8, %9, %10, %11, %12, %13, %14, %15, %16, %17, %18, %19, %20, %21, %22, %23, %24, %25, %26, %27, %28, %29, %30, %31, %32, %33, %34, %35, %36, %37, %38, %39, %40, %41, %42, %43, %44, %45, %46, %47, %48, %49, %50, %51, %52, %53, %54, %55, %56, %57, %58, %59, %60, %61, %62, %63}, %64, %65, 0, 1, 1, 0, %66;"
    : "=f"(d[0]), "=f"(d[1]), "=f"(d[2]), "=f"(d[3]), "=f"(d[4]), "=f"(d[5]), "=f"(d[6]), "=f"(d[7]), "=f"(d[8]), "=f"(d[9]), "=f"(d[10]), "=f"(d[11]), "=f"(d[12]), "=f"(d[13]), "=f"(d[14]), "=f"(d[15]), "=f"(d[16]), "=f"(d[17]), "=f"(d[18]), "=f"(d[19]), "=f"(d[20]), "=f"(d[21]), "=f"(d[22]), "=f"(d[23]), "=f"(d[24]), "=f"(d[25]), "=f"(d[26]), "=f"(d[27]), "=f"(d[28]), "=f"(d[29]), "=f"(d[30]), "=f"(d[31]), "=f"(d[32]), "=f"(d[33]), "=f"(d[34]), "=f"(d[35]), "=f"(d[36]), "=f"(d[37]), "=f"(d[38]), "=f"(d[39]), "=f"(d[40]), "=f"(d[41]), "=f"(d[42]), "=f"(d[43]), "=f"(d[44]), "=f"(d[45]), "=f"(d[46]), "=f"(d[47]), "=f"(d[48]), "=f"(d[49]), "=f"(d[50]), "=f"(d[51]), "=f"(d[52]), "=f"(d[53]), "=f"(d[54]), "=f"(d[55]), "=f"(d[56]), "=f"(d[57]), "=f"(d[58]), "=f"(d[59]), "=f"(d[60]), "=f"(d[61]), "=f"(d[62]), "=f"(d[63])
    : "l"(da), "l"(db), "n"(TB));
}
template <int TB>
__device__ __forceinline__ void wg_ss128(float (&d)[64], uint64_t da, uint64_t db) {
  asm volatile(
    "wgmma.mma_async.sync.aligned.m64n128k16.f32.bf16.bf16 {%0, %1, %2, %3, %4, %5, %6, %7, %8, %9, %10, %11, %12, %13, %14, %15, %16, %17, %18, %19, %20, %21, %22, %23, %24, %25, %26, %27, %28, %29, %30, %31, %32, %33, %34, %35, %36, %37, %38, %39, %40, %41, %42, %43, %44, %45, %46, %47, %48, %49, %50, %51, %52, %53, %54, %55, %56, %57, %58, %59, %60, %61, %62, %63}, %64, %65, 1, 1, 1, 0, %66;"
    : "+f"(d[0]), "+f"(d[1]), "+f"(d[2]), "+f"(d[3]), "+f"(d[4]), "+f"(d[5]), "+f"(d[6]), "+f"(d[7]), "+f"(d[8]), "+f"(d[9]), "+f"(d[10]), "+f"(d[11]), "+f"(d[12]), "+f"(d[13]), "+f"(d[14]), "+f"(d[15]), "+f"(d[16]), "+f"(d[17]), "+f"(d[18]), "+f"(d[19]), "+f"(d[20]), "+f"(d[21]), "+f"(d[22]), "+f"(d[23]), "+f"(d[24]), "+f"(d[25]), "+f"(d[26]), "+f"(d[27]), "+f"(d[28]), "+f"(d[29]), "+f"(d[30]), "+f"(d[31]), "+f"(d[32]), "+f"(d[33]), "+f"(d[34]), "+f"(d[35]), "+f"(d[36]), "+f"(d[37]), "+f"(d[38]), "+f"(d[39]), "+f"(d[40]), "+f"(d[41]), "+f"(d[42]), "+f"(d[43]), "+f"(d[44]), "+f"(d[45]), "+f"(d[46]), "+f"(d[47]), "+f"(d[48]), "+f"(d[49]), "+f"(d[50]), "+f"(d[51]), "+f"(d[52]), "+f"(d[53]), "+f"(d[54]), "+f"(d[55]), "+f"(d[56]), "+f"(d[57]), "+f"(d[58]), "+f"(d[59]), "+f"(d[60]), "+f"(d[61]), "+f"(d[62]), "+f"(d[63])
    : "l"(da), "l"(db), "n"(TB));
}
template <int TB>
__device__ __forceinline__ void wg_ss256(float (&d)[128], uint64_t da, uint64_t db) {
  asm volatile(
    "wgmma.mma_async.sync.aligned.m64n256k16.f32.bf16.bf16 {%0, %1, %2, %3, %4, %5, %6, %7, %8, %9, %10, %11, %12, %13, %14, %15, %16, %17, %18, %19, %20, %21, %22, %23, %24, %25, %26, %27, %28, %29, %30, %31, %32, %33, %34, %35, %36, %37, %38, %39, %40, %41, %42, %43, %44, %45, %46, %47, %48, %49, %50, %51, %52, %53, %54, %55, %56, %57, %58, %59, %60, %61, %62, %63, %64, %65, %66, %67, %68, %69, %70, %71, %72, %73, %74, %75, %76, %77, %78, %79, %80, %81, %82, %83, %84, %85, %86, %87, %88, %89, %90, %91, %92, %93, %94, %95, %96, %97, %98, %99, %100, %101, %102, %103, %104, %105, %106, %107, %108, %109, %110, %111, %112, %113, %114, %115, %116, %117, %118, %119, %120, %121, %122, %123, %124, %125, %126, %127}, %128, %129, 1, 1, 1, 0, %130;"
    : "+f"(d[0]), "+f"(d[1]), "+f"(d[2]), "+f"(d[3]), "+f"(d[4]), "+f"(d[5]), "+f"(d[6]), "+f"(d[7]), "+f"(d[8]), "+f"(d[9]), "+f"(d[10]), "+f"(d[11]), "+f"(d[12]), "+f"(d[13]), "+f"(d[14]), "+f"(d[15]), "+f"(d[16]), "+f"(d[17]), "+f"(d[18]), "+f"(d[19]), "+f"(d[20]), "+f"(d[21]), "+f"(d[22]), "+f"(d[23]), "+f"(d[24]), "+f"(d[25]), "+f"(d[26]), "+f"(d[27]), "+f"(d[28]), "+f"(d[29]), "+f"(d[30]), "+f"(d[31]), "+f"(d[32]), "+f"(d[33]), "+f"(d[34]), "+f"(d[35]), "+f"(d[36]), "+f"(d[37]), "+f"(d[38]), "+f"(d[39]), "+f"(d[40]), "+f"(d[41]), "+f"(d[42]), "+f"(d[43]), "+f"(d[44]), "+f"(d[45]), "+f"(d[46]), "+f"(d[47]), "+f"(d[48]), "+f"(d[49]), "+f"(d[50]), "+f"(d[51]), "+f"(d[52]), "+f"(d[53]), "+f"(d[54]), "+f"(d[55]), "+f"(d[56]), "+f"(d[57]), "+f"(d[58]), "+f"(d[59]), "+f"(d[60]), "+f"(d[61]), "+f"(d[62]), "+f"(d[63]), "+f"(d[64]), "+f"(d[65]), "+f"(d[66]), "+f"(d[67]), "+f"(d[68]), "+f"(d[69]), "+f"(d[70]), "+f"(d[71]), "+f"(d[72]), "+f"(d[73]), "+f"(d[74]), "+f"(d[75]), "+f"(d[76]), "+f"(d[77]), "+f"(d[78]), "+f"(d[79]), "+f"(d[80]), "+f"(d[81]), "+f"(d[82]), "+f"(d[83]), "+f"(d[84]), "+f"(d[85]), "+f"(d[86]), "+f"(d[87]), "+f"(d[88]), "+f"(d[89]), "+f"(d[90]), "+f"(d[91]), "+f"(d[92]), "+f"(d[93]), "+f"(d[94]), "+f"(d[95]), "+f"(d[96]), "+f"(d[97]), "+f"(d[98]), "+f"(d[99]), "+f"(d[100]), "+f"(d[101]), "+f"(d[102]), "+f"(d[103]), "+f"(d[104]), "+f"(d[105]), "+f"(d[106]), "+f"(d[107]), "+f"(d[108]), "+f"(d[109]), "+f"(d[110]), "+f"(d[111]), "+f"(d[112]), "+f"(d[113]), "+f"(d[114]), "+f"(d[115]), "+f"(d[116]), "+f"(d[117]), "+f"(d[118]), "+f"(d[119]), "+f"(d[120]), "+f"(d[121]), "+f"(d[122]), "+f"(d[123]), "+f"(d[124]), "+f"(d[125]), "+f"(d[126]), "+f"(d[127])
    : "l"(da), "l"(db), "n"(TB));
}
template <int TB>
__device__ __forceinline__ void wg_ss32(float (&d)[16], uint64_t da, uint64_t db) {
  asm volatile(
    "wgmma.mma_async.sync.aligned.m64n32k16.f32.bf16.bf16 {%0, %1, %2, %3, %4, %5, %6, %7, %8, %9, %10, %11, %12, %13, %14, %15}, %16, %17, 1, 1, 1, 0, %18;"
    : "+f"(d[0]), "+f"(d[1]), "+f"(d[2]), "+f"(d[3]), "+f"(d[4]), "+f"(d[5]), "+f"(d[6]), "+f"(d[7]), "+f"(d[8]), "+f"(d[9]), "+f"(d[10]), "+f"(d[11]), "+f"(d[12]), "+f"(d[13]), "+f"(d[14]), "+f"(d[15])
    : "l"(da), "l"(db), "n"(TB));
}
template <int TB>
__device__ __forceinline__ void wg_rs256(float (&d)[128], uint32_t a0, uint32_t a1, uint32_t a2, uint32_t a3, uint64_t db) {
  asm volatile(
    "wgmma.mma_async.sync.aligned.m64n256k16.f32.bf16.bf16 {%0, %1, %2, %3, %4, %5, %6, %7, %8, %9, %10, %11, %12, %13, %14, %15, %16, %17, %18, %19, %20, %21, %22, %23, %24, %25, %26, %27, %28, %29, %30, %31, %32, %33, %34, %35, %36, %37, %38, %39, %40, %41, %42, %43, %44, %45, %46, %47, %48, %49, %50, %51, %52, %53, %54, %55, %56, %57, %58, %59, %60, %61, %62, %63, %64, %65, %66, %67, %68, %69, %70, %71, %72, %73, %74, %75, %76, %77, %78, %79, %80, %81, %82, %83, %84, %85, %86, %87, %88, %89, %90, %91, %92, %93, %94, %95, %96, %97, %98, %99, %100, %101, %102, %103, %104, %105, %106, %107, %108, %109, %110, %111, %112, %113, %114, %115, %116, %117, %118, %119, %120, %121, %122, %123, %124, %125, %126, %127}, {%128, %129, %130, %131}, %132, 1, 1, 1, %133;"
    : "+f"(d[0]), "+f"(d[1]), "+f"(d[2]), "+f"(d[3]), "+f"(d[4]), "+f"(d[5]), "+f"(d[6]), "+f"(d[7]), "+f"(d[8]), "+f"(d[9]), "+f"(d[10]), "+f"(d[11]), "+f"(d[12]), "+f"(d[13]), "+f"(d[14]), "+f"(d[15]), "+f"(d[16]), "+f"(d[17]), "+f"(d[18]), "+f"(d[19]), "+f"(d[20]), "+f"(d[21]), "+f"(d[22]), "+f"(d[23]), "+f"(d[24]), "+f"(d[25]), "+f"(d[26]), "+f"(d[27]), "+f"(d[28]), "+f"(d[29]), "+f"(d[30]), "+f"(d[31]), "+f"(d[32]), "+f"(d[33]), "+f"(d[34]), "+f"(d[35]), "+f"(d[36]), "+f"(d[37]), "+f"(d[38]), "+f"(d[39]), "+f"(d[40]), "+f"(d[41]), "+f"(d[42]), "+f"(d[43]), "+f"(d[44]), "+f"(d[45]), "+f"(d[46]), "+f"(d[47]), "+f"(d[48]), "+f"(d[49]), "+f"(d[50]), "+f"(d[51]), "+f"(d[52]), "+f"(d[53]), "+f"(d[54]), "+f"(d[55]), "+f"(d[56]), "+f"(d[57]), "+f"(d[58]), "+f"(d[59]), "+f"(d[60]), "+f"(d[61]), "+f"(d[62]), "+f"(d[63]), "+f"(d[64]), "+f"(d[65]), "+f"(d[66]), "+f"(d[67]), "+f"(d[68]), "+f"(d[69]), "+f"(d[70]), "+f"(d[71]), "+f"(d[72]), "+f"(d[73]), "+f"(d[74]), "+f"(d[75]), "+f"(d[76]), "+f"(d[77]), "+f"(d[78]), "+f"(d[79]), "+f"(d[80]), "+f"(d[81]), "+f"(d[82]), "+f"(d[83]), "+f"(d[84]), "+f"(d[85]), "+f"(d[86]), "+f"(d[87]), "+f"(d[88]), "+f"(d[89]), "+f"(d[90]), "+f"(d[91]), "+f"(d[92]), "+f"(d[93]), "+f"(d[94]), "+f"(d[95]), "+f"(d[96]), "+f"(d[97]), "+f"(d[98]), "+f"(d[99]), "+f"(d[100]), "+f"(d[101]), "+f"(d[102]), "+f"(d[103]), "+f"(d[104]), "+f"(d[105]), "+f"(d[106]), "+f"(d[107]), "+f"(d[108]), "+f"(d[109]), "+f"(d[110]), "+f"(d[111]), "+f"(d[112]), "+f"(d[113]), "+f"(d[114]), "+f"(d[115]), "+f"(d[116]), "+f"(d[117]), "+f"(d[118]), "+f"(d[119]), "+f"(d[120]), "+f"(d[121]), "+f"(d[122]), "+f"(d[123]), "+f"(d[124]), "+f"(d[125]), "+f"(d[126]), "+f"(d[127])
    : "r"(a0), "r"(a1), "r"(a2), "r"(a3), "l"(db), "n"(TB));
}
template <int TB>
__device__ __forceinline__ void wg_rs32(float (&d)[16], uint32_t a0, uint32_t a1, uint32_t a2, uint32_t a3, uint64_t db) {
  asm volatile(
    "wgmma.mma_async.sync.aligned.m64n32k16.f32.bf16.bf16 {%0, %1, %2, %3, %4, %5, %6, %7, %8, %9, %10, %11, %12, %13, %14, %15}, {%16, %17, %18, %19}, %20, 1, 1, 1, %21;"
    : "+f"(d[0]), "+f"(d[1]), "+f"(d[2]), "+f"(d[3]), "+f"(d[4]), "+f"(d[5]), "+f"(d[6]), "+f"(d[7]), "+f"(d[8]), "+f"(d[9]), "+f"(d[10]), "+f"(d[11]), "+f"(d[12]), "+f"(d[13]), "+f"(d[14]), "+f"(d[15])
    : "r"(a0), "r"(a1), "r"(a2), "r"(a3), "l"(db), "n"(TB));
}
template <int TB>
__device__ __forceinline__ void wg_cv128(float (&d)[64], uint32_t a0, uint32_t a1, uint32_t a2, uint32_t a3, uint64_t db) {
  asm volatile(
    "wgmma.mma_async.sync.aligned.m64n128k16.f32.bf16.bf16 {%0, %1, %2, %3, %4, %5, %6, %7, %8, %9, %10, %11, %12, %13, %14, %15, %16, %17, %18, %19, %20, %21, %22, %23, %24, %25, %26, %27, %28, %29, %30, %31, %32, %33, %34, %35, %36, %37, %38, %39, %40, %41, %42, %43, %44, %45, %46, %47, %48, %49, %50, %51, %52, %53, %54, %55, %56, %57, %58, %59, %60, %61, %62, %63}, {%64, %65, %66, %67}, %68, 1, 1, 1, %69;"
    : "+f"(d[0]), "+f"(d[1]), "+f"(d[2]), "+f"(d[3]), "+f"(d[4]), "+f"(d[5]), "+f"(d[6]), "+f"(d[7]), "+f"(d[8]), "+f"(d[9]), "+f"(d[10]), "+f"(d[11]), "+f"(d[12]), "+f"(d[13]), "+f"(d[14]), "+f"(d[15]), "+f"(d[16]), "+f"(d[17]), "+f"(d[18]), "+f"(d[19]), "+f"(d[20]), "+f"(d[21]), "+f"(d[22]), "+f"(d[23]), "+f"(d[24]), "+f"(d[25]), "+f"(d[26]), "+f"(d[27]), "+f"(d[28]), "+f"(d[29]), "+f"(d[30]), "+f"(d[31]), "+f"(d[32]), "+f"(d[33]), "+f"(d[34]), "+f"(d[35]), "+f"(d[36]), "+f"(d[37]), "+f"(d[38]), "+f"(d[39]), "+f"(d[40]), "+f"(d[41]), "+f"(d[42]), "+f"(d[43]), "+f"(d[44]), "+f"(d[45]), "+f"(d[46]), "+f"(d[47]), "+f"(d[48]), "+f"(d[49]), "+f"(d[50]), "+f"(d[51]), "+f"(d[52]), "+f"(d[53]), "+f"(d[54]), "+f"(d[55]), "+f"(d[56]), "+f"(d[57]), "+f"(d[58]), "+f"(d[59]), "+f"(d[60]), "+f"(d[61]), "+f"(d[62]), "+f"(d[63])
    : "r"(a0), "r"(a1), "r"(a2), "r"(a3), "l"(db), "n"(TB));
}
template <int TB>
__device__ __forceinline__ void wg_cv96(float (&d)[48], uint32_t a0, uint32_t a1, uint32_t a2, uint32_t a3, uint64_t db) {
  asm volatile(
    "wgmma.mma_async.sync.aligned.m64n96k16.f32.bf16.bf16 {%0, %1, %2, %3, %4, %5, %6, %7, %8, %9, %10, %11, %12, %13, %14, %15, %16, %17, %18, %19, %20, %21, %22, %23, %24, %25, %26, %27, %28, %29, %30, %31, %32, %33, %34, %35, %36, %37, %38, %39, %40, %41, %42, %43, %44, %45, %46, %47}, {%48, %49, %50, %51}, %52, 1, 1, 1, %53;"
    : "+f"(d[0]), "+f"(d[1]), "+f"(d[2]), "+f"(d[3]), "+f"(d[4]), "+f"(d[5]), "+f"(d[6]), "+f"(d[7]), "+f"(d[8]), "+f"(d[9]), "+f"(d[10]), "+f"(d[11]), "+f"(d[12]), "+f"(d[13]), "+f"(d[14]), "+f"(d[15]), "+f"(d[16]), "+f"(d[17]), "+f"(d[18]), "+f"(d[19]), "+f"(d[20]), "+f"(d[21]), "+f"(d[22]), "+f"(d[23]), "+f"(d[24]), "+f"(d[25]), "+f"(d[26]), "+f"(d[27]), "+f"(d[28]), "+f"(d[29]), "+f"(d[30]), "+f"(d[31]), "+f"(d[32]), "+f"(d[33]), "+f"(d[34]), "+f"(d[35]), "+f"(d[36]), "+f"(d[37]), "+f"(d[38]), "+f"(d[39]), "+f"(d[40]), "+f"(d[41]), "+f"(d[42]), "+f"(d[43]), "+f"(d[44]), "+f"(d[45]), "+f"(d[46]), "+f"(d[47])
    : "r"(a0), "r"(a1), "r"(a2), "r"(a3), "l"(db), "n"(TB));
}
template <int TB>
__device__ __forceinline__ void wg_cv64(float (&d)[32], uint32_t a0, uint32_t a1, uint32_t a2, uint32_t a3, uint64_t db) {
  asm volatile(
    "wgmma.mma_async.sync.aligned.m64n64k16.f32.bf16.bf16 {%0, %1, %2, %3, %4, %5, %6, %7, %8, %9, %10, %11, %12, %13, %14, %15, %16, %17, %18, %19, %20, %21, %22, %23, %24, %25, %26, %27, %28, %29, %30, %31}, {%32, %33, %34, %35}, %36, 1, 1, 1, %37;"
    : "+f"(d[0]), "+f"(d[1]), "+f"(d[2]), "+f"(d[3]), "+f"(d[4]), "+f"(d[5]), "+f"(d[6]), "+f"(d[7]), "+f"(d[8]), "+f"(d[9]), "+f"(d[10]), "+f"(d[11]), "+f"(d[12]), "+f"(d[13]), "+f"(d[14]), "+f"(d[15]), "+f"(d[16]), "+f"(d[17]), "+f"(d[18]), "+f"(d[19]), "+f"(d[20]), "+f"(d[21]), "+f"(d[22]), "+f"(d[23]), "+f"(d[24]), "+f"(d[25]), "+f"(d[26]), "+f"(d[27]), "+f"(d[28]), "+f"(d[29]), "+f"(d[30]), "+f"(d[31])
    : "r"(a0), "r"(a1), "r"(a2), "r"(a3), "l"(db), "n"(TB));
}
template <int TB>
__device__ __forceinline__ void wg_cv128_init(float (&d)[64], uint32_t a0, uint32_t a1, uint32_t a2, uint32_t a3, uint64_t db) {
  asm volatile(
    "wgmma.mma_async.sync.aligned.m64n128k16.f32.bf16.bf16 {%0, %1, %2, %3, %4, %5, %6, %7, %8, %9, %10, %11, %12, %13, %14, %15, %16, %17, %18, %19, %20, %21, %22, %23, %24, %25, %26, %27, %28, %29, %30, %31, %32, %33, %34, %35, %36, %37, %38, %39, %40, %41, %42, %43, %44, %45, %46, %47, %48, %49, %50, %51, %52, %53, %54, %55, %56, %57, %58, %59, %60, %61, %62, %63}, {%64, %65, %66, %67}, %68, 0, 1, 1, %69;"
    : "=f"(d[0]), "=f"(d[1]), "=f"(d[2]), "=f"(d[3]), "=f"(d[4]), "=f"(d[5]), "=f"(d[6]), "=f"(d[7]), "=f"(d[8]), "=f"(d[9]), "=f"(d[10]), "=f"(d[11]), "=f"(d[12]), "=f"(d[13]), "=f"(d[14]), "=f"(d[15]), "=f"(d[16]), "=f"(d[17]), "=f"(d[18]), "=f"(d[19]), "=f"(d[20]), "=f"(d[21]), "=f"(d[22]), "=f"(d[23]), "=f"(d[24]), "=f"(d[25]), "=f"(d[26]), "=f"(d[27]), "=f"(d[28]), "=f"(d[29]), "=f"(d[30]), "=f"(d[31]), "=f"(d[32]), "=f"(d[33]), "=f"(d[34]), "=f"(d[35]), "=f"(d[36]), "=f"(d[37]), "=f"(d[38]), "=f"(d[39]), "=f"(d[40]), "=f"(d[41]), "=f"(d[42]), "=f"(d[43]), "=f"(d[44]), "=f"(d[45]), "=f"(d[46]), "=f"(d[47]), "=f"(d[48]), "=f"(d[49]), "=f"(d[50]), "=f"(d[51]), "=f"(d[52]), "=f"(d[53]), "=f"(d[54]), "=f"(d[55]), "=f"(d[56]), "=f"(d[57]), "=f"(d[58]), "=f"(d[59]), "=f"(d[60]), "=f"(d[61]), "=f"(d[62]), "=f"(d[63])
    : "r"(a0), "r"(a1), "r"(a2), "r"(a3), "l"(db), "n"(TB));
}
template <int TB>
__device__ __forceinline__ void wg_rs256_init(float (&d)[128], uint32_t a0, uint32_t a1, uint32_t a2, uint32_t a3, uint64_t db) {
  asm volatile(
    "wgmma.mma_async.sync.aligned.m64n256k16.f32.bf16.bf16 {%0, %1, %2, %3, %4, %5, %6, %7, %8, %9, %10, %11, %12, %13, %14, %15, %16, %17, %18, %19, %20, %21, %22, %23, %24, %25, %26, %27, %28, %29, %30, %31, %32, %33, %34, %35, %36, %37, %38, %39, %40, %41, %42, %43, %44, %45, %46, %47, %48, %49, %50, %51, %52, %53, %54, %55, %56, %57, %58, %59, %60, %61, %62, %63, %64, %65, %66, %67, %68, %69, %70, %71, %72, %73, %74, %75, %76, %77, %78, %79, %80, %81, %82, %83, %84, %85, %86, %87, %88, %89, %90, %91, %92, %93, %94, %95, %96, %97, %98, %99, %100, %101, %102, %103, %104, %105, %106, %107, %108, %109, %110, %111, %112, %113, %114, %115, %116, %117, %118, %119, %120, %121, %122, %123, %124, %125, %126, %127}, {%128, %129, %130, %131}, %132, 0, 1, 1, %133;"
    : "=f"(d[0]), "=f"(d[1]), "=f"(d[2]), "=f"(d[3]), "=f"(d[4]), "=f"(d[5]), "=f"(d[6]), "=f"(d[7]), "=f"(d[8]), "=f"(d[9]), "=f"(d[10]), "=f"(d[11]), "=f"(d[12]), "=f"(d[13]), "=f"(d[14]), "=f"(d[15]), "=f"(d[16]), "=f"(d[17]), "=f"(d[18]), "=f"(d[19]), "=f"(d[20]), "=f"(d[21]), "=f"(d[22]), "=f"(d[23]), "=f"(d[24]), "=f"(d[25]), "=f"(d[26]), "=f"(d[27]), "=f"(d[28]), "=f"(d[29]), "=f"(d[30]), "=f"(d[31]), "=f"(d[32]), "=f"(d[33]), "=f"(d[34]), "=f"(d[35]), "=f"(d[36]), "=f"(d[37]), "=f"(d[38]), "=f"(d[39]), "=f"(d[40]), "=f"(d[41]), "=f"(d[42]), "=f"(d[43]), "=f"(d[44]), "=f"(d[45]), "=f"(d[46]), "=f"(d[47]), "=f"(d[48]), "=f"(d[49]), "=f"(d[50]), "=f"(d[51]), "=f"(d[52]), "=f"(d[53]), "=f"(d[54]), "=f"(d[55]), "=f"(d[56]), "=f"(d[57]), "=f"(d[58]), "=f"(d[59]), "=f"(d[60]), "=f"(d[61]), "=f"(d[62]), "=f"(d[63]), "=f"(d[64]), "=f"(d[65]), "=f"(d[66]), "=f"(d[67]), "=f"(d[68]), "=f"(d[69]), "=f"(d[70]), "=f"(d[71]), "=f"(d[72]), "=f"(d[73]), "=f"(d[74]), "=f"(d[75]), "=f"(d[76]), "=f"(d[77]), "=f"(d[78]), "=f"(d[79]), "=f"(d[80]), "=f"(d[81]), "=f"(d[82]), "=f"(d[83]), "=f"(d[84]), "=f"(d[85]), "=f"(d[86]), "=f"(d[87]), "=f"(d[88]), "=f"(d[89]), "=f"(d[90]), "=f"(d[91]), "=f"(d[92]), "=f"(d[93]), "=f"(d[94]), "=f"(d[95]), "=f"(d[96]), "=f"(d[97]), "=f"(d[98]), "=f"(d[99]), "=f"(d[100]), "=f"(d[101]), "=f"(d[102]), "=f"(d[103]), "=f"(d[104]), "=f"(d[105]), "=f"(d[106]), "=f"(d[107]), "=f"(d[108]), "=f"(d[109]), "=f"(d[110]), "=f"(d[111]), "=f"(d[112]), "=f"(d[113]), "=f"(d[114]), "=f"(d[115]), "=f"(d[116]), "=f"(d[117]), "=f"(d[118]), "=f"(d[119]), "=f"(d[120]), "=f"(d[121]), "=f"(d[122]), "=f"(d[123]), "=f"(d[124]), "=f"(d[125]), "=f"(d[126]), "=f"(d[127])
    : "r"(a0), "r"(a1), "r"(a2), "r"(a3), "l"(db), "n"(TB));
}
template <int TB>
__device__ __forceinline__ void wg_rs32_init(float (&d)[16], uint32_t a0, uint32_t a1, uint32_t a2, uint32_t a3, uint64_t db) {
  asm volatile(
    "wgmma.mma_async.sync.aligned.m64n32k16.f32.bf16.bf16 {%0, %1, %2, %3, %4, %5, %6, %7, %8, %9, %10, %11, %12, %13, %14, %15}, {%16, %17, %18, %19}, %20, 0, 1, 1, %21;"
    : "=f"(d[0]), "=f"(d[1]), "=f"(d[2]), "=f"(d[3]), "=f"(d[4]), "=f"(d[5]), "=f"(d[6]), "=f"(d[7]), "=f"(d[8]), "=f"(d[9]), "=f"(d[10]), "=f"(d[11]), "=f"(d[12]), "=f"(d[13]), "=f"(d[14]), "=f"(d[15])
    : "r"(a0), "r"(a1), "r"(a2), "r"(a3), "l"(db), "n"(TB));
}


constexpr int NST = 7, SLOT = 9216;
constexpr uint32_t SM_XN = 0, SM_HIN = 147456, SM_RING = 163840, SM_BAR = SM_RING + 7 * SLOT;
constexpr uint32_t SM_KD = SM_BAR + 256, SMEM_BYTES = SM_KD + 3840;
constexpr uint32_t B_FULL = 0, B_EMPTY = 56, B_XN = 112, B_K2048 = 176, B_HF = 184, B_HE = 200, B_CV = 216, B_PT = 224, B_YT = 232, B_SG = 240, B_X = 248;
constexpr uint32_t PR_LN = 65536, PR_PAR = 98304, PR_K0 = SM_HIN + 12288;
constexpr uint32_t T_U = 0, T_KP = 17408, T_K0 = 51200, T_X0 = 53248, T_X1 = SM_HIN + 4 * 18432, T_YT = 0, T_STG = 65536, T_PART = SM_HIN;
constexpr uint32_t U_BYTES = U_LEN * 2, KP_BYTES = KP_LEN * 4, IMG = 18432;

struct Params {
  CUtensorMap xn, gate, up, dn, dn5, dp, dp5, x, x5, y, y5, out, out5;
  const __nv_bfloat16 *xp, *logA, *Aim, *Cre, *Cim, *logdt, *Dsk;
};

struct KgIn { uint32_t la, ai, cr, ci, ldt, dsk; };
__device__ __forceinline__ void kgen_load(const Params& p, int ch0, int tid, KgIn& in) {
  const int e = ch0 * (NM_ / 2) + tid;
  in.la = __ldg((const uint32_t*)p.logA + e); in.ai = __ldg((const uint32_t*)p.Aim + e);
  in.cr = __ldg((const uint32_t*)p.Cre + e); in.ci = __ldg((const uint32_t*)p.Cim + e);
  in.ldt = __ldg((const unsigned short*)p.logdt + ch0 + (tid >> 6)); in.dsk = __ldg((const unsigned short*)p.Dsk + ch0 + (tid >> 6));
}
struct KgState { float acc[5][4]; float v; };
struct cf { float r, i; };
__device__ __forceinline__ cf cmul(cf a, cf b) { return {fmaf(a.r, b.r, -(a.i * b.i)), fmaf(a.r, b.i, a.i * b.r)}; }
__device__ __forceinline__ cf csq(cf a) { return {fmaf(a.r, a.r, -(a.i * a.i)), (a.r + a.r) * a.i}; }
__device__ __forceinline__ cf cexp2(float lm, float th) {
  float m; asm("ex2.approx.ftz.f32 %0, %1;" : "=f"(m) : "f"(lm));
  return {m * __cosf(th), m * __sinf(th)};
}
__device__ __forceinline__ float turns(float w) { return (w - rintf(w)) * 6.283185307179586f; }
__device__ __forceinline__ void kgen_params(unsigned char* sm, int tid, KgIn in, KgState& st) {
  const int warp = tid >> 5, lane = tid & 31;
  float4* par = (float4*)(sm + PR_PAR + warp * 6144) + lane;
  const float dt = bf_round(expf(bf_lo(in.ldt)));
  float v = 0.f;
#pragma unroll 1
  for (int r = 0; r < 2; r++) {
    const float x = -bf_round(expf(bf_lo(in.la))) * dt * 1.4426950408889634f;
    const float w = bf_lo(in.ai) * dt * 0.15915494309189535f;
    const cf c = {2.f * bf_lo(in.cr) * dt, 2.f * bf_lo(in.ci) * dt};
    const cf e2 = cexp2(2.f * x, turns(2.f * w)), e64 = cexp2(64.f * x, turns(64.f * w));
    const cf e4 = csq(e2), e6 = cmul(e2, e4), e128 = csq(e64), e256 = csq(e128), e512 = csq(e256), e1024 = csq(e512);
    const cf c1 = cmul(c, e128), c256 = cmul(c, e256), c512 = cmul(c, e512), c4 = cmul(c, e1024);
    const cf c516 = cmul(c512, e4), c258 = cmul(c256, e2), c260 = cmul(c256, e4), c262 = cmul(c256, e6);
    v += fmaf(c4.r, e1024.r, -(c4.i * e1024.i));
    par[0] = make_float4(x, turns(w), turns(8.f * w), turns(128.f * w));
    par[64] = make_float4(c.r, c.i, c1.r, c1.i);
    par[128] = make_float4(c4.r, c4.i, e64.r, e64.i);
    par[192] = make_float4(c512.r, c512.i, c516.r, c516.i);
    par[256] = make_float4(c256.r, c256.i, c258.r, c258.i);
    par[320] = make_float4(c260.r, c260.i, c262.r, c262.i);
    par += 32;
    in.la >>= 16; in.ai >>= 16; in.cr >>= 16; in.ci >>= 16;
  }
#pragma unroll
  for (int o = 16; o; o >>= 1) v += __shfl_xor_sync(0xffffffffu, v, o);
  __syncwarp();
#pragma unroll
  for (int t = 0; t < 5; t++) { st.acc[t][0] = st.acc[t][1] = st.acc[t][2] = st.acc[t][3] = 0.f; }
  if (lane == 0 && !(warp & 1)) st.acc[0][0] = bf_lo(in.dsk);
  st.v = v;
}
__device__ __forceinline__ void kgen_steps(unsigned char* sm, int tid, KgState& st) {
  const int warp = tid >> 5, lane = tid & 31, g = lane >> 2, q = lane & 3;
  const float4* par = (const float4*)(sm + PR_PAR + warp * 6144) + q;
  const float2* p3 = (const float2*)(par + 192) + (g & 1);
  const float2* p2 = (const float2*)(par + 256 + 64 * ((g >> 1) & 1)) + (g & 1);
  const float g1 = (float)g, g8 = 8.f * g1, g128 = 128.f * g1;
  const int l1 = 4 * (g >> 1) + q, l2 = 4 * (g >> 2) + q;
#pragma unroll 4
  for (int ks = 0; ks < 16; ks++) {
    const float4 P = par[4 * ks], Q = par[64 + 4 * ks], R = par[128 + 4 * ks];
    const float2 c3 = p3[8 * ks], c2 = p2[8 * ks];
    const cf e = cexp2(P.x * g1, P.y * g1), a1 = cexp2(P.x * g8, P.z * g1), t = cexp2(P.x * g128, P.w * g1);
    const cf a2 = cmul(a1, cf{R.z, R.w});
    const cf t1 = {__shfl_sync(0xffffffffu, t.r, l1), __shfl_sync(0xffffffffu, t.i, l1)};
    const cf t2 = {__shfl_sync(0xffffffffu, t.r, l2), __shfl_sync(0xffffffffu, t.i, l2)};
    auto mma = [&](float (&d)[4], cf u, float cr, float ci) {
      const float b0 = fmaf(u.r, cr, -(u.i * ci)), b1 = fmaf(-u.r, ci, -(u.i * cr));
      asm("mma.sync.aligned.m16n8k8.row.col.f32.tf32.tf32.f32 {%0,%1,%2,%3}, {%4,%5,%6,%7}, {%8,%9}, {%0,%1,%2,%3};"
          : "+f"(d[0]), "+f"(d[1]), "+f"(d[2]), "+f"(d[3])
          : "r"(__float_as_uint(a1.r)), "r"(__float_as_uint(a2.r)), "r"(__float_as_uint(a1.i)), "r"(__float_as_uint(a2.i)),
            "r"(__float_as_uint(b0)), "r"(__float_as_uint(b1)));
    };
    mma(st.acc[0], e, Q.x, Q.y);
    mma(st.acc[1], e, Q.z, Q.w);
    mma(st.acc[4], t, R.x, R.y);
    mma(st.acc[2], t2, c2.x, c2.y);
    mma(st.acc[3], t1, c3.x, c3.y);
  }
}
__device__ __forceinline__ void kgen_finish(unsigned char* sm, unsigned short* kd, unsigned short* k2048, int tid, KgState& st) {
  const int warp = tid >> 5, lane = tid & 31, g = lane >> 2, q = lane & 3;
  float4* red = (float4*)(sm + SM_HIN + (warp >> 1) * 3072) + lane;
  if (warp & 1) {
#pragma unroll
    for (int t = 0; t < 5; t++) red[t * 32] = make_float4(st.acc[t][0], st.acc[t][1], st.acc[t][2], st.acc[t][3]);
    red[160].x = st.v;
  }
  named_bar(3, 256);
  if (!(warp & 1)) {
    uint32_t lo[5], hi[5];
#pragma unroll
    for (int t = 0; t < 5; t++) {
      const float4 r = red[t * 32];
      lo[t] = pack_bf16(st.acc[t][0] + r.x, st.acc[t][1] + r.y); hi[t] = pack_bf16(st.acc[t][2] + r.z, st.acc[t][3] + r.w);
    }
    *k2048 = (unsigned short)pack_bf16(st.v + red[160].x, 0.f);
    uint32_t* kw = (uint32_t*)kd;
    kw[lane] = lo[0]; kw[32 + lane] = hi[0]; kw[64 + lane] = lo[1]; kw[96 + lane] = hi[1];
    kw[128 + 2 * g + (q & 1) + 32 * (q >> 1)] = lo[2]; kw[144 + 2 * g + (q & 1) + 32 * (q >> 1)] = hi[2];
    kw[192 + g + 16 * q] = lo[3]; kw[200 + g + 16 * q] = hi[3];
    kd[512 + g + 32 * q] = (unsigned short)lo[4]; kd[528 + g + 32 * q] = (unsigned short)(lo[4] >> 16);
    kd[520 + g + 32 * q] = (unsigned short)hi[4]; kd[536 + g + 32 * q] = (unsigned short)(hi[4] >> 16);
  }
}
constexpr int kd_index(int l) {
  if (l < 256) return l;
  const int sh = l < 512 ? 1 : l < 1024 ? 2 : 3;
  return ((l + (1 << (sh - 1)) - 1 + ((l >> sh) & 1)) >> sh) + 128 * sh;
}
struct KTab { unsigned int e[512 * 4]; };
constexpr KTab make_ktab() {
  KTab t = {};
  for (int it = 0; it < 511; it++) {
    const int l0 = 4 * it, b1 = kd_index(l0) & ~1;
    const unsigned int np = 0x54 + 0x22 * (l0 ? kd_index(l0 - 1) - b1 : 0);
    unsigned int n[4] = {0, 0, 0, 0};
    for (int k = 0; k < 4; k++) n[k] = 0x10 + 0x22 * (kd_index(l0 + k) - b1);
    t.e[4 * it] = 2 * b1 | ((b1 < 638 ? 4u : 0u) << 16);
    t.e[4 * it + 1] = (n[0] + 0x44) | (np << 8) | (n[1] << 16) | (n[0] << 24);
    t.e[4 * it + 2] = n[2] | (n[1] << 8) | (n[3] << 16) | (n[2] << 24);
    t.e[4 * it + 3] = l0 ? 0xffffffffu : 0xffffu;
  }
  return t;
}
__device__ __align__(16) const KTab g_ktab = make_ktab();
template <int NT>
__device__ __forceinline__ void kexpand(uint32_t sb, uint32_t k0, uint32_t k1, uint32_t k2048, int tid, uint4 e) {
#pragma unroll 1
  for (int it = tid; it < 511; it += NT) {
    const uint4 en = __ldg((const uint4*)g_ktab.e + min(it + NT, 511));
    const uint32_t o = e.x & 0xffffu, o2 = o + (e.x >> 16), dst = sb + T_KP + 64 + 16 * it;
#pragma unroll
    for (int c = 0; c < 4; c++) {
      const uint32_t a = c ? k1 + 1280 * (c - 1) : k0;
      const uint32_t x0 = lds32(a + o - 4), x1 = lds32(a + o), x2 = lds32(a + o2);
      sts128(dst + c * KP_BYTES, make_uint4(__byte_perm(x0, x1, e.y) & e.w, __byte_perm(x1, x2, e.y >> 16), __byte_perm(x1, x2, e.z), __byte_perm(x1, x2, e.z >> 16)));
    }
    e = en;
  }
  if (tid < 36) {
    const int c = tid / 9, i = tid - 9 * c;
    uint4 v = make_uint4(0u, 0u, 0u, 0u);
    if (i == 4) {
      uint32_t z, y;
      asm volatile("ld.shared.u16 %0, [%1];" : "=r"(z) : "r"(k2048 + 2 * c) : "memory");
      asm volatile("ld.shared.u16 %0, [%1];" : "=r"(y) : "r"((c ? k1 + 1280 * (c - 1) : k0) + 1278) : "memory");
      v = make_uint4(z | (y << 16), z * 0x10001u, z * 0x10001u, z * 0x10001u);
    }
    sts128(sb + T_KP + c * KP_BYTES + 16 * (i < 4 ? i : 511 + i), v);
  }
  if (tid < 64) sts128(sb + T_U + (tid >> 4) * U_BYTES + (tid & 15) * 16, make_uint4(0u, 0u, 0u, 0u));
  fence_async_smem();
}

template <int NR>
__device__ __forceinline__ void conv_mma(float (&d)[NR], const uint32_t* a, uint64_t db) {
  if constexpr (NR == 64) wg_cv128<0>(d, a[0], a[1], a[2], a[3], db);
  else if constexpr (NR == 48) wg_cv96<0>(d, a[0], a[1], a[2], a[3], db);
  else if constexpr (NR == 32) wg_cv64<0>(d, a[0], a[1], a[2], a[3], db);
  else wg_rs32<0>(d, a[0], a[1], a[2], a[3], db);
}
__device__ __forceinline__ void conv_load(uint32_t (&a)[8], uint32_t o) {
#pragma unroll
  for (int c = 0; c < 2; c++) {
    a[4 * c + 0] = lds32(o + c * KP_BYTES); a[4 * c + 1] = lds32(o + c * KP_BYTES + 512);
    a[4 * c + 2] = lds32(o + c * KP_BYTES - 32); a[4 * c + 3] = lds32(o + c * KP_BYTES + 480);
  }
}
template <int NR>
__device__ __forceinline__ void conv_phase(float (&dA)[NR], float (&dB)[NR], uint32_t (&a)[4][8], uint32_t kp, uint64_t dU) {
#pragma unroll
  for (int i = 0; i < 2; i++) {
#pragma unroll
    for (int k = 0; k < 4; k++) {
      wg_fence();
      if constexpr (NR == 64) {
        if (i == 0 && k == 0) { wg_cv128_init<0>(dA, a[0][0], a[0][1], a[0][2], a[0][3], dU); wg_cv128_init<0>(dB, a[0][4], a[0][5], a[0][6], a[0][7], dU + (U_BYTES >> 4)); }
        else { conv_mma<NR>(dA, a[k], dU - 2 * k); conv_mma<NR>(dB, a[k] + 4, dU - 2 * k + (U_BYTES >> 4)); }
      } else { conv_mma<NR>(dA, a[k], dU - 2 * k); conv_mma<NR>(dB, a[k] + 4, dU - 2 * k + (U_BYTES >> 4)); }
      wg_commit();
      wg_wait<1>();
      if (k == 2 && i) kp += 64 * 24;
      conv_load(a[(k + 2) & 3], kp + 64 * (k + 2));
    }
    kp += 256;
    dU -= 8;
  }
  wg_wait<0>();
  reg_fence(dA); reg_fence(dB);
}
template <int NR>
__device__ __forceinline__ void upper_copy(float (&dst)[NR - 16], const float (&src)[NR]) {
#pragma unroll
  for (int i = 0; i < NR - 16; i++) asm volatile("mov.b32 %0, %1;" : "=f"(dst[i]) : "f"(src[i + 16]));
}
__device__ __forceinline__ void conv2(uint32_t sb, int wg, int w, int lane, uint32_t bar_free) {
  const int g = lane >> 2, q = lane & 3;
  float dA[64], dB[64];
  uint32_t a[4][8];
  const uint32_t kp = sb + T_KP + 2 * wg * KP_BYTES + 4 * (16 + 256 * (w >> 1) + 8 * (w & 1) + g - 2 * q);
  const uint64_t dU = mk_desc(sb + T_U + 2 * wg * U_BYTES + 256, 16, 256, 3);
  conv_load(a[0], kp); conv_load(a[1], kp + 64);
  conv_phase<64>(dA, dB, a, kp, dU);
  float eA[48], eB[48];
  upper_copy<64>(eA, dA); upper_copy<64>(eB, dB);
  conv_phase<48>(eA, eB, a, kp + 2048, dU);
  float fA[32], fB[32];
  upper_copy<48>(fA, eA); upper_copy<48>(fB, eB);
  conv_phase<32>(fA, fB, a, kp + 4096, dU);
  float gA[16], gB[16];
  upper_copy<32>(gA, fA); upper_copy<32>(gB, fB);
  conv_phase<16>(gA, gB, a, kp + 6144, dU);
#pragma unroll
  for (int i = 0; i < 16; i++) {
    dA[16 + i] = eA[i]; dA[32 + i] = fA[i]; dA[48 + i] = gA[i];
    dB[16 + i] = eB[i]; dB[32 + i] = fB[i]; dB[48 + i] = gB[i];
  }
  float z[2][16][2];
#pragma unroll
  for (int m = 0; m < 16; m++)
#pragma unroll
    for (int e = 0; e < 2; e++) {
      z[0][m][e] = m ? dA[4 * m + e] + dA[4 * m - 2 + e] : dA[e];
      z[1][m][e] = m ? dB[4 * m + e] + dB[4 * m - 2 + e] : dB[e];
    }
  if (bar_free) mbar_wait(bar_free, 0);
  const uint32_t xb = sb + T_X0 + wg * 8192, xc = wg ? T_X1 - T_X0 - 8192 : 4096;
  const uint32_t xw = xb + (w * 32 + lane) * 16, xr = xb + ((w ^ 2) * 32 + lane) * 16;
  float k[2][8][2];
  if (w < 2) {
#pragma unroll
    for (int c = 0; c < 2; c++)
#pragma unroll
      for (int m = 0; m < 8; m += 4) {
        sts128(xw + c * xc + (m >> 2) * 2048, make_uint4(pack_bf16(z[c][8 + m][0], z[c][8 + m][1]), pack_bf16(z[c][9 + m][0], z[c][9 + m][1]),
                                                          pack_bf16(z[c][10 + m][0], z[c][10 + m][1]), pack_bf16(z[c][11 + m][0], z[c][11 + m][1])));
#pragma unroll
        for (int i = 0; i < 4; i++) { k[c][m + i][0] = z[c][m + i][0]; k[c][m + i][1] = z[c][m + i][1]; }
      }
  } else {
#pragma unroll
    for (int c = 0; c < 2; c++)
#pragma unroll
      for (int m = 0; m < 8; m += 4) {
        sts128(xw + c * xc + (m >> 2) * 2048, make_uint4(m ? pack_bf16(z[c][m - 2][0], z[c][m - 2][1]) : 0u, m ? pack_bf16(z[c][m - 1][0], z[c][m - 1][1]) : 0u,
                                                          pack_bf16(z[c][m][0], z[c][m][1]), pack_bf16(z[c][m + 1][0], z[c][m + 1][1])));
#pragma unroll
        for (int i = 0; i < 4; i++) { k[c][m + i][0] = z[c][6 + m + i][0]; k[c][m + i][1] = z[c][6 + m + i][1]; }
      }
  }
  named_bar(1 + wg, 128);
  const uint32_t yb = sb + T_U + 2 * wg * U_BYTES;
#pragma unroll
  for (int c = 0; c < 2; c++)
#pragma unroll
    for (int m = 0; m < 8; m += 4) {
      const uint4 u = lds128(xr + c * xc + (m >> 2) * 2048);
      stmatrix_x4_t(yb + c * 4096 + (64 * (w >> 1) + 8 * m + lane) * 32 + 16 * (w & 1),
                    pack_bf16(k[c][m][0] + bf_lo(u.x), k[c][m][1] + bf_hi(u.x)), pack_bf16(k[c][m + 1][0] + bf_lo(u.y), k[c][m + 1][1] + bf_hi(u.y)),
                    pack_bf16(k[c][m + 2][0] + bf_lo(u.z), k[c][m + 2][1] + bf_hi(u.z)), pack_bf16(k[c][m + 3][0] + bf_lo(u.w), k[c][m + 3][1] + bf_hi(u.w)));
    }
  fence_async_smem();
  named_arrive(10 + wg, 160);
}
__device__ __forceinline__ void conv_ship(uint32_t sb, uint32_t bar, int wg, int ch, int cnt, bool el) {
  named_bar(10 + wg, 160);
  if (el) {
    bulk_s2g(g_y + (size_t)ch * L_, sb + T_U + 2 * wg * U_BYTES, 8192);
    bulk_commit_wait();
    cnt_add_done(cnt);
    mbar_arrive(bar + B_SG);
  }
  __syncwarp();
}

__global__ void __cluster_dims__(2, 1, 1) __launch_bounds__(384, 1) fused_kernel(const __grid_constant__ Params p) {
  extern __shared__ __align__(1024) unsigned char smem_raw[];
  const uint32_t sb = smem_u32(smem_raw);
  const uint32_t bar = sb + SM_BAR;
  const uint32_t vb = blockIdx.x;
  const int j = vb & 1, pair = vb >> 1, mt = pair & 15, sp = pair >> 4;
  const bool spare = pair >= 64;
  const int warp = __shfl_sync(0xffffffffu, threadIdx.x >> 5, 0), wg = warp >> 2, w = warp & 3;
  const int row0 = mt * 128 + (2 * sp + j) * 16;
  const int f0 = sp * 1152;
  KgIn kin;
  if (wg < 2) kgen_load(p, spare ? 512 + ((int)vb - 128) * 16 : vb * 4, threadIdx.x, kin);
  if (threadIdx.x >= 288 && threadIdx.x < 301) prefetch_map(&p.xn + (threadIdx.x - 288));
  if (threadIdx.x == 256) {
    mbar_init(bar + B_X, 1);
    if (!spare) {
      mbar_expect_tx(bar + B_X, 16 * D_ * 2);
      bulk_g2s(sb + PR_LN, p.xp + (size_t)row0 * D_, 16 * D_ * 2, bar + B_X);
    }
#pragma unroll
    for (int i = 0; i < 30; i++) if (i != 22) mbar_init(bar + 8 * i, (i >= 7 && i < 14) ? 8 : (i == 27 && !spare) ? 4 : 1);
    mbar_init(bar + B_SG, 2);
    mbar_expect_tx(bar + B_HF, 8192); mbar_expect_tx(bar + B_HF + 8, 8192);
    asm volatile("fence.mbarrier_init.release.cluster;" ::: "memory");
  }
  __syncthreads();
  asm volatile("barrier.cluster.arrive.relaxed.aligned;" ::: "memory");

  if (wg == 2) {
    const int t = threadIdx.x & 127, lane = t & 31;
    const bool el = elect_one();
    if (!spare) {
      const uint32_t ra = sb + PR_LN + (t >> 3) * (D_ * 2) + (t & 7) * 16;
      if (w == 1 && el) {
#pragma unroll 1
        for (int u = 0; u < NST; u++) {
          const uint32_t dst = sb + SM_RING + u * SLOT, fb = bar + B_FULL + 8 * u;
          mbar_expect_tx(fb, 8192);
          tma_2d(dst, &p.gate, f0 + 64 * j, 32 * u, fb);
          tma_2d(dst + 4096, &p.up, f0 + 64 * j, 32 * u, fb);
        }
      }
      mbar_wait(bar + B_X, 0);
      uint4 v[9];
#pragma unroll
      for (int i = 0; i < 9; i++) v[i] = lds128(ra + i * 128);
      uint32_t* u = (uint32_t*)v;
      const float x0 = bf_lo(__shfl_sync(0xffffffffu, u[0], lane & 24));
      float s = 0.f, s2 = 0.f, q = 0.f, q2 = 0.f;
#pragma unroll
      for (int i = 0; i < 36; i++) {
        const float a = bf_lo(u[i]) - x0, b = bf_hi(u[i]) - x0;
        s += a; s2 += b; q = fmaf(a, a, q); q2 = fmaf(b, b, q2);
      }
      s += s2; q += q2;
#pragma unroll
      for (int o = 4; o; o >>= 1) { s += __shfl_xor_sync(0xffffffffu, s, o); q += __shfl_xor_sync(0xffffffffu, q, o); }
      s *= (1.0f / D_);
      const __nv_bfloat162 mb = __float2bfloat162_rn(s + x0);
      const float rinv = 1.0f / bf_round(sqrtf(bf_round(bf_round(fmaxf(fmaf(-s, s, q * (1.0f / D_)), 0.f)) + 1e-5f)));
#pragma unroll
      for (int i = 0; i < 36; i++) {
        const __nv_bfloat162 d2 = __hsub2(*(const __nv_bfloat162*)&u[i], mb);
        const uint32_t d = *(const uint32_t*)&d2;
        u[i] = pack_bf16(bf_lo(d) * rinv, bf_hi(d) * rinv);
      }
#pragma unroll
      for (int i = 0; i < 9; i++) sts128(ra + i * 128, v[i]);
      fence_async_smem();
      named_bar(5, 128);
      if (w == 0 && el) bulk_s2g(g_xn + (size_t)row0 * D_, sb + PR_LN, 16 * D_ * 2);
    }
    asm volatile("barrier.cluster.wait.aligned;" ::: "memory");
    asm volatile("setmaxnreg.dec.sync.aligned.u32 24;");
    if (w == 0) {
      if (!spare) {
        if (el) {
          bulk_commit_wait();
          cnt_add_done(C_LN + mt);
        }
        __syncwarp();
        cnt_wait(C_LN + mt, 8);
        fence_async_all();
#pragma unroll 1
        for (int kb = 0; kb < 6; kb++) {
          if (el) {
            mbar_expect_tx(bar + B_XN + 8 * kb, 16384);
            tma_2d(sb + SM_XN + kb * 16384, &p.xn, kb * 64, mt * 128, bar + B_XN + 8 * kb);
          }
        }
        named_bar(4, 384);
        uint32_t slot = 0, ph = 0;
#pragma unroll 1
        for (int c = 0; c <= 9; c++) {
          const int fc = f0 + c * 128;
          if (c < 9) {
            for (int u = c ? 0 : NST; u < 18; u++) {
              mbar_wait(bar + B_EMPTY + 8 * slot, ph);
              if (el) {
                const uint32_t dst = sb + SM_RING + slot * SLOT, fb = bar + B_FULL + 8 * slot;
                mbar_expect_tx(fb, 8192);
                tma_2d(dst, &p.gate, fc + 64 * j, 32 * u, fb);
                tma_2d(dst + 4096, &p.up, fc + 64 * j, 32 * u, fb);
                if (c == 0 && u < 10) {
                  const int kb = u - 1;
                  if (kb < 8) mbar_expect_tx(bar + B_XN + 8 * kb, kb < 7 ? 16384 : 32768);
                  tma_2d(sb + SM_XN + kb * 16384, &p.xn, kb * 64, mt * 128, bar + B_XN + 8 * min(kb, 7));
                }
              }
              if (++slot == NST) { slot = 0; ph ^= 1; }
            }
          }
          const int fp = (fc - 128 + 64 * (1 - j)) >> 3, fo = fc + 64 * j;
#pragma unroll
          for (int i = 0; i < 8; i++) {
            const bool isP = i < 4;
            const int u = i & 3;
            if (isP ? (c == 0) : (c == 9)) continue;
            mbar_wait(bar + B_EMPTY + 8 * slot, ph);
            if (el) {
              const uint32_t dst = sb + SM_RING + slot * SLOT, fb = bar + B_FULL + 8 * slot;
              mbar_expect_tx(fb, 9216);
              if (isP) {
                tma_5d(dst, &p.dp, 0, 0, fp + 4 * (u >> 1), 2 * (u & 1), 4 * j, fb);
                tma_4d(dst + 8192, &p.dp5, 512 + 32 * j, 0, fp + 4 * (u >> 1), 2 * (u & 1), fb);
              } else {
                tma_3d(dst, &p.dn, 0, fo + 16 * u, 4 * j, fb);
                tma_2d(dst + 8192, &p.dn5, 512 + 32 * j, fo + 16 * u, fb);
              }
            }
            if (++slot == NST) { slot = 0; ph ^= 1; }
          }
        }
        const int ch0 = vb * 4;
        cnt_wait(C_U, 384);
        fence_async_all();
        if (el) {
          mbar_expect_tx(bar + B_CV, 4 * L_ * 2);
#pragma unroll 1
          for (int c = 0; c < 4; c++) bulk_g2s(sb + T_U + c * U_BYTES + 256, g_u + (size_t)(ch0 + c) * L_, L_ * 2, bar + B_CV);
        }
        unsigned char* img = g_part + (size_t)(2 * mt + j) * 16 * IMG;
        mbar_wait(bar + B_SG, 0);
        if (lane < 6) {
          const int r = (sp + 1 + (lane >> 1)) & 3;
          if (lane & 1) bulk_s2g(img + (r * 4 + sp) * IMG + 16384, sb + T_STG + 65536 + (r >> 1) * 8192 + (r & 1) * 2048, 2048);
          else bulk_s2g(img + (r * 4 + sp) * IMG, sb + T_STG + r * 16384, 16384);
          bulk_commit_wait();
        } else if (lane == 6) {
          mbar_expect_tx(bar + B_PT, 3 * IMG);
          mbar_expect_tx(bar + B_X, IMG);
          tma_2d(sb + T_PART + 3 * IMG, &p.x, 256 * j + 64 * sp, mt * 128, bar + B_X);
          tma_2d(sb + T_PART + 3 * IMG + 16384, &p.x5, 512 + 32 * j, mt * 128 + 32 * sp, bar + B_X);
        }
        __syncwarp();
        if (el) cnt_add_done(C_PART + 2 * mt + j);
        cnt_wait(C_PART + 2 * mt + j, 4);
        fence_async_all();
        if (lane < 3) bulk_g2s(sb + T_PART + lane * IMG, img + (sp * 4 + ((sp + 1 + lane) & 3)) * IMG, IMG, bar + B_PT);
        cnt_wait(C_Y5, 32);
        mbar_wait(bar + B_SG, 1);
        if (el) {
          mbar_expect_tx(bar + B_YT, IMG);
          tma_2d(sb + T_YT + 16384, &p.y5, mt * 128 + 32 * sp, 512 + 32 * j, bar + B_YT);
        }
        cnt_wait(C_Y + 4 * j + sp, 32);
        fence_async_all();
        if (el) {
          tma_2d(sb + T_YT, &p.y, mt * 128, 256 * j + 64 * sp, bar + B_YT);
          tma_2d(sb + T_YT + 8192, &p.y, mt * 128 + 64, 256 * j + 64 * sp, bar + B_YT);
        }
      } else {
        named_bar(7, 288);
        cnt_wait(C_U, 384);
        fence_async_all();
#pragma unroll 1
        for (int grp = 0; grp < 4; grp++) {
          const int ch0 = 512 + ((int)vb - 128) * 16 + grp * 4;
          if (grp) mbar_wait(bar + B_SG, (grp - 1) & 1);
          if (el) {
            mbar_expect_tx(bar + B_CV, 4 * L_ * 2);
#pragma unroll 1
            for (int c = 0; c < 4; c++) bulk_g2s(sb + T_U + c * U_BYTES + 256, g_u + (size_t)(ch0 + c) * L_, L_ * 2, bar + B_CV);
          }
        }
      }
      unsigned int old = 0;
      if (el) old = atomicAdd(g_cnt + C_DONE * 32, 1u) + 1;
      if (__any_sync(0xffffffffu, old == gridDim.x)) { g_cnt[lane * 32] = 0u; g_cnt[(lane + 32) * 32] = 0u; }
    } else {
      if (!spare) {
        named_bar(4, 384);
        uint4 k0v = make_uint4(0u, 0u, 0u, 0u);
        if (t < 112) k0v = lds128(sb + PR_K0 + (t - 32) * 16);
        named_bar(8, 96);
        if (t == 32) { mbar_arrive_remote(mapa(bar + B_HE, j ^ 1)); mbar_arrive_remote(mapa(bar + B_HE + 8, j ^ 1)); }
#pragma unroll 1
        for (int i = 0; i < 8; i++) mbar_wait(bar + B_XN + 8 * i, 0);
        const int tok = 8 * ((lane & 7) >> 1) + 2 * (lane >> 3) + (lane & 1);
#pragma unroll 1
        for (int it = w - 1; it < 36; it += 3) {
          const int oc = 9 * (2 * sp + j) + (it >> 2), tg = it & 3;
          uint4 v;
          ldmatrix_x4_t(sb + SM_XN + (oc >> 3) * 16384 + (32 * tg + tok) * 128 + (((oc ^ tok) & 7) << 4), v.x, v.y, v.z, v.w);
          ((uint4*)(g_u + (size_t)(8 * oc + (lane >> 2)) * L_ + mt * 128))[(4 * tg + (lane & 3)) ^ (tg >> 1)] = v;
        }
        __syncwarp();
        if (lane == 0) { fence_async_all(); cnt_add(C_U); }
        const uint4 e0 = __ldg((const uint4*)g_ktab.e + (t - 32));
        named_bar(9, 352);
        if (t < 112) sts128(sb + T_K0 + (t - 32) * 16, k0v);
        named_bar(8, 96);
        kexpand<96>(sb, sb + T_K0, sb + SM_KD, bar + B_K2048, t - 32, e0);
        __syncwarp();
        if (lane == 0) mbar_arrive(bar + B_CV);
        if (w < 3) conv_ship(sb, bar, w - 1, vb * 4 + 2 * (w - 1), C_Y + (vb >> 4), el);
      } else if (w < 3) {
#pragma unroll 1
        for (int grp = 0; grp < 4; grp++) conv_ship(sb, bar, w - 1, 512 + ((int)vb - 128) * 16 + grp * 4 + 2 * (w - 1), C_Y5, el);
      }
    }
  } else {
    const int t = threadIdx.x & 127, lane = t & 31;
    KgState kst;
    kgen_params(smem_raw, threadIdx.x, kin, kst);
    if (!spare) {
      kgen_steps(smem_raw, threadIdx.x, kst);
      kgen_finish(smem_raw, (unsigned short*)(smem_raw + (warp < 2 ? PR_K0 : SM_KD + ((warp >> 1) - 1) * 1280)),
                  (unsigned short*)(smem_raw + SM_BAR + B_K2048) + (warp >> 1), threadIdx.x, kst);
      named_arrive(4, 384);
    } else {
      const int c0 = 512 + ((int)vb - 128) * 16;
#pragma unroll 1
      for (int grp = 0; grp < 4; grp++) {
        if (grp) { kgen_load(p, c0 + grp * 4, threadIdx.x, kin); kgen_params(smem_raw, threadIdx.x, kin, kst); }
        kgen_steps(smem_raw, threadIdx.x, kst);
        kgen_finish(smem_raw, (unsigned short*)(smem_raw + SM_RING + (grp * 4 + (warp >> 1)) * 1280),
                    (unsigned short*)(smem_raw + SM_KD) + grp * 4 + (warp >> 1), threadIdx.x, kst);
        named_bar(3, 256);
      }
      named_arrive(7, 288);
    }
    asm volatile("barrier.cluster.wait.aligned;" ::: "memory");
    asm volatile("setmaxnreg.inc.sync.aligned.u32 240;");
    if (!spare) {
      const bool leader = (t == 0);
      float O1[128], O2[16];
      uint32_t slot = 0, ph = 0, prev = 0;
      const uint32_t hin = sb + SM_HIN + wg * 8192;
      const uint32_t r_hin = mapa(hin + (16 * w + (lane >> 2)) * 128 + (((lane & 3) ^ (lane >> 2)) << 4), j ^ 1);
      const uint32_t r_hf = mapa(bar + B_HF + 8 * wg, j ^ 1), r_he = mapa(bar + B_HE + 8 * wg, j ^ 1);
      const uint64_t dA0 = mk_desc(sb + SM_XN + wg * 8192, 16, 1024, 1);
      const uint64_t dH0 = mk_desc(hin, 16, 1024, 1);
      const uint64_t dG0 = mk_desc(sb + SM_RING, 4096, 1024, 1);
      const uint64_t dW0 = mk_desc(sb + SM_RING, 2048, 1024, 1);
      const uint64_t dX0 = mk_desc(sb + SM_RING + 8192, 512, 512, 2);
      auto adv = [&]() { prev = slot; if (++slot == NST) { slot = 0; ph ^= 1; } };
      auto release = [&](uint32_t s) { if (lane == 0) mbar_arrive(bar + B_EMPTY + 8 * s); };
      auto peer_begin = [&](int cp) {
        mbar_wait(bar + B_HF + 8 * wg, cp & 1);
        if (leader && cp < 8) mbar_expect_tx(bar + B_HF + 8 * wg, 8192);
        fence_async_smem();
      };
      auto peer_unit = [&](int u) {
        wg_fence();
        wg_ss256<1>(O1, dH0 + 2 * u, dW0 + (uint64_t)(slot * (SLOT >> 4)));
        wg_ss32<1>(O2, dH0 + 2 * u, dX0 + (uint64_t)(slot * (SLOT >> 4)));
        wg_commit();
      };
      auto chunk = [&](auto first_c, const int c) {
        constexpr bool FIRST = decltype(first_c)::value;
        float S[64];
        {
          if (FIRST) mbar_wait(bar + B_XN, 0);
          mbar_wait(bar + B_FULL + 8 * slot, ph);
          const uint64_t db = dG0 + (uint64_t)(slot * (SLOT >> 4));
          wg_fence();
          wg_ss128_init<1>(S, dA0, db);
          wg_ss128<1>(S, dA0 + 2, db + 128);
          wg_commit();
          adv();
        }
#pragma unroll 1
        for (int u = 1; u < 18; u++) {
          if (FIRST && !(u & 1) && u < 16) mbar_wait(bar + B_XN + 8 * (u >> 1), 0);
          mbar_wait(bar + B_FULL + 8 * slot, ph);
          const uint64_t da = dA0 + (uint64_t)((u >> 1) * 1024 + (u & 1) * 4);
          const uint64_t db = dG0 + (uint64_t)(slot * (SLOT >> 4));
          wg_fence();
          wg_ss128<1>(S, da, db);
          wg_ss128<1>(S, da + 2, db + 128);
          wg_commit();
          if constexpr (!FIRST) { if (u == 12) peer_begin(c - 1); }
          wg_wait<1>();
          release(prev);
          if (c == 8 && u == 8) named_bar(9, 352);
          adv();
        }
        uint32_t H[16];
        if constexpr (FIRST) { wg_wait<0>(); release(prev); }
        uint32_t rs = prev;
        auto rel_next = [&]() { release(rs); if (++rs == NST) rs = 0; };
        auto P = [&](int u) {
          mbar_wait(bar + B_FULL + 8 * slot, ph);
          peer_unit(u);
          if (u) { wg_wait<2>(); rel_next(); }
          adv();
        };
        auto E = [&](int u) {
#pragma unroll
          for (int i = 8 * u; i < 8 * u + 8; i++) asm volatile("" : "+f"(S[i]), "+f"(S[32 + i])::"memory");
#pragma unroll
          for (int g = 2 * u; g < 2 * u + 2; g++) {
            H[2 * g] = geglu2(S[4 * g], S[4 * g + 1], S[32 + 4 * g], S[33 + 4 * g]);
            H[2 * g + 1] = geglu2(S[4 * g + 2], S[4 * g + 3], S[34 + 4 * g], S[35 + 4 * g]);
          }
#pragma unroll
          for (int i = 4 * u; i < 4 * u + 4; i++) asm volatile("" : "+r"(H[i])::"memory");
        };
        auto O = [&](int u) {
          mbar_wait(bar + B_FULL + 8 * slot, ph);
          wg_fence();
          if (FIRST && u == 0) {
            wg_rs256_init<1>(O1, H[0], H[1], H[2], H[3], dW0 + (uint64_t)(slot * (SLOT >> 4)));
            wg_rs32_init<1>(O2, H[0], H[1], H[2], H[3], dX0 + (uint64_t)(slot * (SLOT >> 4)));
            rs = slot;
          } else {
            wg_rs256<1>(O1, H[4 * u], H[4 * u + 1], H[4 * u + 2], H[4 * u + 3], dW0 + (uint64_t)(slot * (SLOT >> 4)));
            wg_rs32<1>(O2, H[4 * u], H[4 * u + 1], H[4 * u + 2], H[4 * u + 3], dX0 + (uint64_t)(slot * (SLOT >> 4)));
          }
          wg_commit();
          if (u == 3) {
            mbar_wait(bar + B_HE + 8 * wg, c & 1);
            st_async_v4(r_hin, H[0], H[2], H[4], H[6], r_hf);
            st_async_v4(r_hin ^ 64, H[8], H[10], H[12], H[14], r_hf);
            st_async_v4(r_hin + 1024, H[1], H[3], H[5], H[7], r_hf);
            st_async_v4((r_hin ^ 64) + 1024, H[9], H[11], H[13], H[15], r_hf);
          }
          if (!FIRST || u >= 2) { wg_wait<2>(); rel_next(); }
          if (u == 1) { if constexpr (!FIRST) { if (leader) mbar_arrive_remote(r_he); } }
          if (u == 3) { wg_wait<1>(); rel_next(); wg_wait<0>(); rel_next(); }
          adv();
        };
        if constexpr (FIRST) { E(0); O(0); E(1); O(1); E(2); O(2); E(3); O(3); }
        else { P(0); P(1); E(0); P(2); E(1); P(3); O(0); E(2); O(1); O(2); E(3); O(3); }
      };
      chunk(std::true_type{}, 0);
#pragma unroll 1
      for (int c = 1; c < 9; c++) chunk(std::false_type{}, c);
      peer_begin(8);
#pragma unroll 1
      for (int u = 0; u < 4; u++) { mbar_wait(bar + B_FULL + 8 * slot, ph); peer_unit(u); adv(); }
      wg_wait<0>();
      reg_fence(O1); reg_fence(O2);
      const int mi = lane >> 3, li = lane & 7;
      {
        const int row = 16 * w + 8 * (mi & 1) + li;
        const uint32_t stg = sb + T_STG + wg * 8192 + row * 128;
#pragma unroll
        for (int g = 0; g < 32; g += 2)
          stmatrix_x4(stg + (g >> 3) * 16384 + ((((g & 7) + (mi >> 1)) ^ li) << 4), pack_bf16(O1[4 * g], O1[4 * g + 1]), pack_bf16(O1[4 * g + 2], O1[4 * g + 3]),
                      pack_bf16(O1[4 * g + 4], O1[4 * g + 5]), pack_bf16(O1[4 * g + 6], O1[4 * g + 7]));
#pragma unroll
        for (int g = 0; g < 4; g += 2)
          stmatrix_x4(stg + 65536 - row * 64 + (((g + (mi >> 1)) ^ (li >> 1)) << 4), pack_bf16(O2[4 * g], O2[4 * g + 1]), pack_bf16(O2[4 * g + 2], O2[4 * g + 3]),
                      pack_bf16(O2[4 * g + 4], O2[4 * g + 5]), pack_bf16(O2[4 * g + 6], O2[4 * g + 7]));
        fence_async_smem();
        named_bar(1 + wg, 128);
        if (leader) mbar_arrive(bar + B_SG);
      }
      mbar_wait(bar + B_CV, 0);
      conv2(sb, wg, w, lane, bar + B_SG);
      const uint32_t rowi = 8 * (mi & 1) + li;
      const uint32_t own_m = sb + T_STG + sp * 16384, own_t = sb + T_STG + 65536 - 16384 + (sp >> 1) * 8192 + (sp & 1) * 2048;
      auto off = [&](int k) -> uint32_t {
        return k < 4 ? (16 * warp + rowi) * 128 + (((2 * k + (mi >> 1)) ^ li) << 4) : 16384 + (16 * warp + rowi) * 64 + (((2 * (k - 4) + (mi >> 1)) ^ (li >> 1)) << 4);
      };
      float f[6][8];
#pragma unroll
      for (int k = 0; k < 6; k++)
#pragma unroll
        for (int i = 0; i < 8; i++) f[k][i] = 0.f;
      named_bar(3, 256);
#pragma unroll 1
      for (int rep = 0; rep < 2; rep++) {
      mbar_wait(bar + (rep ? B_PT : B_X), rep ^ 1);
#pragma unroll 1
      for (int s = 2 * rep; s < 2 + 3 * rep; s++) {
        const uint32_t am = s ? sb + T_PART + (4 - s) * IMG : own_m, at = s ? am : own_t;
        const float sc = s == 1 ? 1.f : 0.5f;
#pragma unroll
        for (int k = 0; k < 6; k++) {
          if (k >= 4 && warp >= 2) break;
          uint32_t r[4];
          ldmatrix_x4((k < 4 ? am : at) + off(k), r);
#pragma unroll
          for (int i = 0; i < 4; i++) { f[k][2 * i] = fmaf(bf_lo(r[i]), sc, f[k][2 * i]); f[k][2 * i + 1] = fmaf(bf_hi(r[i]), sc, f[k][2 * i + 1]); }
        }
      }
      if (rep) mbar_wait(bar + B_YT, 0);
#pragma unroll
      for (int k = 0; k < 6; k++) {
        if (k >= 4 && warp >= 2) break;
        const uint32_t ya = k < 4 ? (warp >> 2) * 8192 + (16 * k + 8 * (mi >> 1) + li) * 128 + (((2 * (warp & 3) + (mi & 1)) ^ li) << 4)
                                  : 16384 + (16 * (k - 4) + 8 * (mi >> 1) + li) * 64 + (((2 * warp + (mi & 1)) ^ (li >> 1)) << 4);
        uint32_t y0, y1, y2, y3;
        ldmatrix_x4_t(sb + T_YT + ya, y0, y1, y2, y3);
        stmatrix_x4((k < 4 ? own_m : own_t) + off(k), pack_bf16(f[k][0] + bf_lo(y0), f[k][1] + bf_hi(y0)), pack_bf16(f[k][2] + bf_lo(y1), f[k][3] + bf_hi(y1)),
                    pack_bf16(f[k][4] + bf_lo(y2), f[k][5] + bf_hi(y2)), pack_bf16(f[k][6] + bf_lo(y3), f[k][7] + bf_hi(y3)));
      }
      fence_async_smem();
      __syncwarp();
      }
      if (lane == 0) {
        tma_store_2d(&p.out, own_m + warp * 2048, 256 * j + 64 * sp, mt * 128 + 16 * warp);
        if (warp < 2) tma_store_2d(&p.out5, own_t + 16384 + warp * 1024, 512 + 32 * j, mt * 128 + 32 * sp + 16 * warp);
        asm volatile("cp.async.bulk.commit_group;" ::: "memory");
        asm volatile("cp.async.bulk.wait_group.read 0;" ::: "memory");
      }
    } else {
#pragma unroll 1
      for (int grp = 0; grp < 4; grp++) {
        if (grp) mbar_wait(bar + B_SG, (grp - 1) & 1);
        kexpand<256>(sb, sb + SM_RING + grp * 5120, sb + SM_RING + grp * 5120 + 1280, sb + SM_KD + 8 * grp, threadIdx.x, __ldg((const uint4*)g_ktab.e + threadIdx.x));
        named_bar(3, 256);
        mbar_wait(bar + B_CV, grp & 1);
        conv2(sb, wg, w, lane, 0);
        named_bar(3, 256);
      }
    }
  }
}

typedef CUresult (*PFN_enc)(CUtensorMap*, CUtensorMapDataType, cuuint32_t, void*, const cuuint64_t*, const cuuint64_t*, const cuuint32_t*,
                            const cuuint32_t*, CUtensorMapInterleave, CUtensorMapSwizzle, CUtensorMapL2promotion, CUtensorMapFloatOOBfill);

void enc(PFN_enc fn, CUtensorMap* m, void* ptr, int rank, const cuuint64_t* dims, const cuuint64_t* strides, const cuuint32_t* box, CUtensorMapSwizzle sw) {
  cuuint32_t es[5] = {1, 1, 1, 1, 1};
  fn(m, CU_TENSOR_MAP_DATA_TYPE_BFLOAT16, rank, ptr, dims, strides, box, es, CU_TENSOR_MAP_INTERLEAVE_NONE, sw,
     CU_TENSOR_MAP_L2_PROMOTION_L2_128B, CU_TENSOR_MAP_FLOAT_OOB_FILL_NONE);
}

}

extern "C" void kernel_launch(void* const* d_in, const int* in_sizes, int n_in, void* d_out, int out_size) {
  static Params pr;
  static void* key[5] = {nullptr, nullptr, nullptr, nullptr, nullptr};
  if (key[0] != d_in[8] || key[1] != d_in[9] || key[2] != d_in[10] || key[3] != d_in[0] || key[4] != d_out) {
    key[0] = d_in[8]; key[1] = d_in[9]; key[2] = d_in[10]; key[3] = d_in[0]; key[4] = d_out;
    void* fnp = nullptr; cudaDriverEntryPointQueryResult st;
    cudaGetDriverEntryPoint("cuTensorMapEncodeTiled", &fnp, cudaEnableDefault, &st);
    PFN_enc fn = (PFN_enc)fnp;
    void *p_xn, *p_y;
    cudaGetSymbolAddress(&p_xn, g_xn); cudaGetSymbolAddress(&p_y, g_y);
    { cuuint64_t d[2] = {D_, L_}, s[1] = {D_ * 2};
      { cuuint32_t b[2] = {64, 128}; enc(fn, &pr.xn, p_xn, 2, d, s, b, CU_TENSOR_MAP_SWIZZLE_128B); }
      { cuuint32_t b[2] = {64, 128}; enc(fn, &pr.x, d_in[0], 2, d, s, b, CU_TENSOR_MAP_SWIZZLE_128B); }
      { cuuint32_t b[2] = {64, 16}; enc(fn, &pr.out, d_out, 2, d, s, b, CU_TENSOR_MAP_SWIZZLE_128B); }
      { cuuint32_t b[2] = {32, 32}; enc(fn, &pr.x5, d_in[0], 2, d, s, b, CU_TENSOR_MAP_SWIZZLE_64B); }
      { cuuint32_t b[2] = {32, 16}; enc(fn, &pr.out5, d_out, 2, d, s, b, CU_TENSOR_MAP_SWIZZLE_64B); } }
    { cuuint64_t d[2] = {F_, D_}, s[1] = {F_ * 2}; cuuint32_t b[2] = {64, 32};
      enc(fn, &pr.gate, d_in[8], 2, d, s, b, CU_TENSOR_MAP_SWIZZLE_128B); enc(fn, &pr.up, d_in[9], 2, d, s, b, CU_TENSOR_MAP_SWIZZLE_128B); }
    { void* wd = d_in[10];
      { cuuint64_t d[3] = {64, F_, 9}, s[2] = {D_ * 2, 128}; cuuint32_t b[3] = {64, 16, 4}; enc(fn, &pr.dn, wd, 3, d, s, b, CU_TENSOR_MAP_SWIZZLE_128B); }
      { cuuint64_t d[2] = {D_, F_}, s[1] = {D_ * 2}; cuuint32_t b[2] = {32, 16}; enc(fn, &pr.dn5, wd, 2, d, s, b, CU_TENSOR_MAP_SWIZZLE_64B); }
      { cuuint64_t d[5] = {64, 2, F_ / 8, 4, 9}, s[4] = {D_ * 2, D_ * 16, D_ * 4, 128}; cuuint32_t b[5] = {64, 2, 4, 2, 4};
        enc(fn, &pr.dp, wd, 5, d, s, b, CU_TENSOR_MAP_SWIZZLE_128B); }
      { cuuint64_t d[4] = {D_, 2, F_ / 8, 4}, s[3] = {D_ * 2, D_ * 16, D_ * 4}; cuuint32_t b[4] = {32, 2, 4, 2};
        enc(fn, &pr.dp5, wd, 4, d, s, b, CU_TENSOR_MAP_SWIZZLE_64B); }
    }
    { cuuint64_t d[2] = {L_, D_}, s[1] = {L_ * 2};
      { cuuint32_t b[2] = {64, 64}; enc(fn, &pr.y, p_y, 2, d, s, b, CU_TENSOR_MAP_SWIZZLE_128B); }
      { cuuint32_t b[2] = {32, 32}; enc(fn, &pr.y5, p_y, 2, d, s, b, CU_TENSOR_MAP_SWIZZLE_64B); } }
    cudaFuncSetAttribute(fused_kernel, cudaFuncAttributeMaxDynamicSharedMemorySize, SMEM_BYTES);
  }
  const __nv_bfloat16* const* in = (const __nv_bfloat16* const*)d_in;
  pr.xp = in[0]; pr.logA = in[1]; pr.Aim = in[2]; pr.Cre = in[3]; pr.Cim = in[4]; pr.logdt = in[5]; pr.Dsk = in[6];
  fused_kernel<<<132, 384, SMEM_BYTES>>>(pr);
}
```

```cpp
#include <cuda_runtime.h>
#include <cuda_bf16.h>
#include <cuda.h>
#include <stdint.h>
#include <type_traits>

namespace {

constexpr int L_ = 2048, D_ = 576, F_ = 4608, NM_ = 128;
constexpr int KP_LEN = 2080;
constexpr int U_LEN = 2176;

__device__ __align__(1024) __nv_bfloat16 g_xn[L_ * D_];
__device__ __align__(1024) __nv_bfloat16 g_u[D_ * L_];
__device__ __align__(1024) unsigned char g_part[32 * 16 * 18432];
__device__ __align__(1024) __nv_bfloat16 g_y[D_ * L_];
__device__ __align__(1024) unsigned int g_cnt[64 * 32];
constexpr int C_LN = 0, C_PART = 16, C_U = 48, C_Y = 49, C_Y5 = 57, C_DONE = 58;

__device__ __forceinline__ uint32_t smem_u32(const void* p) { return (uint32_t)__cvta_generic_to_shared(p); }
__device__ __forceinline__ void mbar_init(uint32_t bar, uint32_t cnt) { asm volatile("mbarrier.init.shared::cta.b64 [%0], %1;" ::"r"(bar), "r"(cnt)); }
__device__ __forceinline__ void mbar_expect_tx(uint32_t bar, uint32_t bytes) { asm volatile("mbarrier.arrive.expect_tx.shared::cta.b64 _, [%0], %1;" ::"r"(bar), "r"(bytes) : "memory"); }
__device__ __forceinline__ void mbar_arrive(uint32_t bar) { asm volatile("mbarrier.arrive.shared::cta.b64 _, [%0];" ::"r"(bar) : "memory"); }
__device__ __forceinline__ void mbar_arrive_remote(uint32_t bar) { asm volatile("mbarrier.arrive.shared::cluster.b64 _, [%0];" ::"r"(bar) : "memory"); }
__device__ __forceinline__ void mbar_wait(uint32_t bar, uint32_t parity) {
  asm volatile("{\n.reg .pred p, q;\n.reg .u32 n;\nmov.u32 n, 0;\nLW:\nmbarrier.try_wait.parity.shared::cta.b64 p, [%0], %1;\n"
               "add.u32 n, n, 1;\nsetp.lt.and.u32 q, n, 65536, !p;\n@q bra LW;\n}" ::"r"(bar), "r"(parity) : "memory");
}
__device__ __forceinline__ bool elect_one() {
  uint32_t ok;
  asm volatile("{\n.reg .pred p;\nelect.sync _|p, 0xffffffff;\nselp.u32 %0, 1, 0, p;\n}" : "=r"(ok));
  return ok;
}
__device__ __forceinline__ void tma_2d(uint32_t dst, const CUtensorMap* map, int c0, int c1, uint32_t bar) {
  asm volatile("cp.async.bulk.tensor.2d.shared::cluster.global.mbarrier::complete_tx::bytes [%0], [%1, {%3, %4}], [%2];"
               ::"r"(dst), "l"(map), "r"(bar), "r"(c0), "r"(c1) : "memory");
}
__device__ __forceinline__ void tma_3d(uint32_t dst, const CUtensorMap* map, int c0, int c1, int c2, uint32_t bar) {
  asm volatile("cp.async.bulk.tensor.3d.shared::cluster.global.mbarrier::complete_tx::bytes [%0], [%1, {%3, %4, %5}], [%2];"
               ::"r"(dst), "l"(map), "r"(bar), "r"(c0), "r"(c1), "r"(c2) : "memory");
}
__device__ __forceinline__ void bulk_g2s(uint32_t dst, const void* src, uint32_t bytes, uint32_t bar) {
  asm volatile("cp.async.bulk.shared::cluster.global.mbarrier::complete_tx::bytes [%0], [%1], %2, [%3];"
               ::"r"(dst), "l"(src), "r"(bytes), "r"(bar) : "memory");
}
__device__ __forceinline__ uint32_t mapa(uint32_t addr, uint32_t rank) { uint32_t r; asm volatile("mapa.shared::cluster.u32 %0, %1, %2;" : "=r"(r) : "r"(addr), "r"(rank)); return r; }
__device__ __forceinline__ void fence_async_smem() { asm volatile("fence.proxy.async.shared::cta;" ::: "memory"); }
__device__ __forceinline__ void wg_fence() { asm volatile("wgmma.fence.sync.aligned;" ::: "memory"); }
__device__ __forceinline__ void wg_commit() { asm volatile("wgmma.commit_group.sync.aligned;" ::: "memory"); }
template <int N> __device__ __forceinline__ void wg_wait() { asm volatile("wgmma.wait_group.sync.aligned %0;" ::"n"(N) : "memory"); }
template <int N> __device__ __forceinline__ void reg_fence(float (&d)[N]) {
#pragma unroll
  for (int i = 0; i < N; i++) asm volatile("" : "+f"(d[i])::"memory");
}
__device__ __forceinline__ void named_bar(int id, int n) { asm volatile("bar.sync %0, %1;" ::"r"(id), "r"(n) : "memory"); }
__device__ __forceinline__ uint64_t mk_desc(uint32_t addr, uint32_t lbo, uint32_t sbo, uint32_t sw) {
  return (uint64_t)((addr & 0x3FFFF) >> 4) | ((uint64_t)(lbo >> 4) << 16) | ((uint64_t)(sbo >> 4) << 32) | ((uint64_t)sw << 62);
}
__device__ __forceinline__ uint32_t pack_bf16(float lo, float hi) {
  uint32_t r; asm("cvt.rn.bf16x2.f32 %0, %1, %2;" : "=r"(r) : "f"(hi), "f"(lo)); return r;
}
__device__ __forceinline__ float bf_lo(uint32_t v) { return __uint_as_float(v << 16); }
__device__ __forceinline__ float bf_hi(uint32_t v) { return __uint_as_float(v & 0xffff0000u); }
__device__ __forceinline__ float bf_round(float x) { return __bfloat162float(__float2bfloat16_rn(x)); }
__device__ __forceinline__ void st_async_v4(uint32_t addr, uint32_t a, uint32_t b, uint32_t c, uint32_t d, uint32_t bar) {
  asm volatile("st.async.weak.shared::cluster.mbarrier::complete_tx::bytes.v4.b32 [%0], {%1, %2, %3, %4}, [%5];"
               ::"r"(addr), "r"(a), "r"(b), "r"(c), "r"(d), "r"(bar) : "memory");
}
__device__ __forceinline__ void stmatrix_x4_t(uint32_t addr, uint32_t a, uint32_t b, uint32_t c, uint32_t d) {
  asm volatile("stmatrix.sync.aligned.m8n8.x4.trans.shared.b16 [%0], {%1, %2, %3, %4};" ::"r"(addr), "r"(a), "r"(b), "r"(c), "r"(d) : "memory");
}
__device__ __forceinline__ void ldmatrix_x4_t(uint32_t addr, uint32_t& a, uint32_t& b, uint32_t& c, uint32_t& d) {
  asm volatile("ldmatrix.sync.aligned.m8n8.x4.trans.shared.b16 {%0, %1, %2, %3}, [%4];" : "=r"(a), "=r"(b), "=r"(c), "=r"(d) : "r"(addr) : "memory");
}
__device__ __forceinline__ uint32_t lds32(uint32_t addr) { uint32_t v; asm volatile("ld.shared.b32 %0, [%1];" : "=r"(v) : "r"(addr) : "memory"); return v; }

__device__ __forceinline__ uint32_t geglu2(float g0, float g1, float u0, float u1) {
  const uint32_t g = pack_bf16(g0, g1), u = pack_bf16(u0, u1);
  uint32_t t, p, z, th, e, r;
  asm("mul.rn.bf16x2 %0, %1, %1;" : "=r"(t) : "r"(g));
  asm("fma.rn.bf16x2 %0, %1, %2, %3;" : "=r"(p) : "r"(t), "r"(0x3d123d12u), "r"(0x3f4c3f4cu));
  asm("mul.rn.bf16x2 %0, %1, %2;" : "=r"(z) : "r"(g), "r"(p));
  asm("tanh.approx.bf16x2 %0, %1;" : "=r"(th) : "r"(z));
  asm("fma.rn.bf16x2 %0, %1, %2, %1;" : "=r"(e) : "r"(g), "r"(th));
  asm("mul.rn.bf16x2 %0, %1, %2;" : "=r"(r) : "r"(e), "r"(u));
  return r;
}
__device__ __forceinline__ uint4 lds128(uint32_t addr) { uint4 v; asm volatile("ld.shared.v4.b32 {%0,%1,%2,%3}, [%4];" : "=r"(v.x), "=r"(v.y), "=r"(v.z), "=r"(v.w) : "r"(addr) : "memory"); return v; }
__device__ __forceinline__ void stmatrix_x4(uint32_t addr, uint32_t a, uint32_t b, uint32_t c, uint32_t d) {
  asm volatile("stmatrix.sync.aligned.m8n8.x4.shared.b16 [%0], {%1, %2, %3, %4};" ::"r"(addr), "r"(a), "r"(b), "r"(c), "r"(d) : "memory");
}
__device__ __forceinline__ void ldmatrix_x4(uint32_t addr, uint32_t (&r)[4]) {
  asm volatile("ldmatrix.sync.aligned.m8n8.x4.shared.b16 {%0, %1, %2, %3}, [%4];" : "=r"(r[0]), "=r"(r[1]), "=r"(r[2]), "=r"(r[3]) : "r"(addr) : "memory");
}
__device__ __forceinline__ void sts128(uint32_t addr, uint4 v) { asm volatile("st.shared.v4.b32 [%0], {%1,%2,%3,%4};" ::"r"(addr), "r"(v.x), "r"(v.y), "r"(v.z), "r"(v.w) : "memory"); }
__device__ __forceinline__ void bulk_s2g(void* dst, uint32_t src, uint32_t bytes) {
  asm volatile("cp.async.bulk.global.shared::cta.bulk_group [%0], [%1], %2;" ::"l"(dst), "r"(src), "r"(bytes) : "memory");
}
__device__ __forceinline__ void tma_store_2d(const CUtensorMap* map, uint32_t src, int c0, int c1) {
  asm volatile("cp.async.bulk.tensor.2d.global.shared::cta.bulk_group [%0, {%2, %3}], [%1];" ::"l"(map), "r"(src), "r"(c0), "r"(c1) : "memory");
}
__device__ __forceinline__ void bulk_commit_wait() {
  asm volatile("cp.async.bulk.commit_group;" ::: "memory");
  asm volatile("cp.async.bulk.wait_group 0;" ::: "memory");
}
__device__ __forceinline__ void named_arrive(int id, int n) { asm volatile("bar.arrive %0, %1;" ::"r"(id), "r"(n) : "memory"); }
__device__ __forceinline__ void fence_async_all() { asm volatile("fence.proxy.async.global;" ::: "memory"); }
__device__ __forceinline__ void cnt_add(int idx) {
  asm volatile("red.release.gpu.global.add.u32 [%0], 1;" ::"l"(g_cnt + idx * 32) : "memory");
}
__device__ __forceinline__ void cnt_add_done(int idx) {
  asm volatile("red.relaxed.gpu.global.add.u32 [%0], 1;" ::"l"(g_cnt + idx * 32) : "memory");
}
__device__ __forceinline__ void cnt_wait(int idx, uint32_t target) {
  const unsigned int* p = g_cnt + idx * 32;
#pragma unroll 1
  for (int it = 0; it < (1 << 18); it++) {
    uint32_t v; asm volatile("ld.acquire.gpu.global.u32 %0, [%1];" : "=r"(v) : "l"(p) : "memory");
    if (v >= target) break;
  }
}

template <int TB>
__device__ __forceinline__ void wg_ss128_init(float (&d)[64], uint64_t da, uint64_t db) {
  asm volatile(
    "wgmma.mma_async.sync.aligned.m64n128k16.f32.bf16.bf16 {%0, %1, %2, %3, %4, %5, %6, %7, %8, %9, %10, %11, %12, %13, %14, %15, %16, %17, %18, %19, %20, %21, %22, %23, %24, %25, %26, %27, %28, %29, %30, %31, %32, %33, %34, %35, %36, %37, %38, %39, %40, %41, %42, %43, %44, %45, %46, %47, %48, %49, %50, %51, %52, %53, %54, %55, %56, %57, %58, %59, %60, %61, %62, %63}, %64, %65, 0, 1, 1, 0, %66;"
    : "=f"(d[0]), "=f"(d[1]), "=f"(d[2]), "=f"(d[3]), "=f"(d[4]), "=f"(d[5]), "=f"(d[6]), "=f"(d[7]), "=f"(d[8]), "=f"(d[9]), "=f"(d[10]), "=f"(d[11]), "=f"(d[12]), "=f"(d[13]), "=f"(d[14]), "=f"(d[15]), "=f"(d[16]), "=f"(d[17]), "=f"(d[18]), "=f"(d[19]), "=f"(d[20]), "=f"(d[21]), "=f"(d[22]), "=f"(d[23]), "=f"(d[24]), "=f"(d[25]), "=f"(d[26]), "=f"(d[27]), "=f"(d[28]), "=f"(d[29]), "=f"(d[30]), "=f"(d[31]), "=f"(d[32]), "=f"(d[33]), "=f"(d[34]), "=f"(d[35]), "=f"(d[36]), "=f"(d[37]), "=f"(d[38]), "=f"(d[39]), "=f"(d[40]), "=f"(d[41]), "=f"(d[42]), "=f"(d[43]), "=f"(d[44]), "=f"(d[45]), "=f"(d[46]), "=f"(d[47]), "=f"(d[48]), "=f"(d[49]), "=f"(d[50]), "=f"(d[51]), "=f"(d[52]), "=f"(d[53]), "=f"(d[54]), "=f"(d[55]), "=f"(d[56]), "=f"(d[57]), "=f"(d[58]), "=f"(d[59]), "=f"(d[60]), "=f"(d[61]), "=f"(d[62]), "=f"(d[63])
    : "l"(da), "l"(db), "n"(TB));
}
template <int TB>
__device__ __forceinline__ void wg_ss128(float (&d)[64], uint64_t da, uint64_t db) {
  asm volatile(
    "wgmma.mma_async.sync.aligned.m64n128k16.f32.bf16.bf16 {%0, %1, %2, %3, %4, %5, %6, %7, %8, %9, %10, %11, %12, %13, %14, %15, %16, %17, %18, %19, %20, %21, %22, %23, %24, %25, %26, %27, %28, %29, %30, %31, %32, %33, %34, %35, %36, %37, %38, %39, %40, %41, %42, %43, %44, %45, %46, %47, %48, %49, %50, %51, %52, %53, %54, %55, %56, %57, %58, %59, %60, %61, %62, %63}, %64, %65, 1, 1, 1, 0, %66;"
    : "+f"(d[0]), "+f"(d[1]), "+f"(d[2]), "+f"(d[3]), "+f"(d[4]), "+f"(d[5]), "+f"(d[6]), "+f"(d[7]), "+f"(d[8]), "+f"(d[9]), "+f"(d[10]), "+f"(d[11]), "+f"(d[12]), "+f"(d[13]), "+f"(d[14]), "+f"(d[15]), "+f"(d[16]), "+f"(d[17]), "+f"(d[18]), "+f"(d[19]), "+f"(d[20]), "+f"(d[21]), "+f"(d[22]), "+f"(d[23]), "+f"(d[24]), "+f"(d[25]), "+f"(d[26]), "+f"(d[27]), "+f"(d[28]), "+f"(d[29]), "+f"(d[30]), "+f"(d[31]), "+f"(d[32]), "+f"(d[33]), "+f"(d[34]), "+f"(d[35]), "+f"(d[36]), "+f"(d[37]), "+f"(d[38]), "+f"(d[39]), "+f"(d[40]), "+f"(d[41]), "+f"(d[42]), "+f"(d[43]), "+f"(d[44]), "+f"(d[45]), "+f"(d[46]), "+f"(d[47]), "+f"(d[48]), "+f"(d[49]), "+f"(d[50]), "+f"(d[51]), "+f"(d[52]), "+f"(d[53]), "+f"(d[54]), "+f"(d[55]), "+f"(d[56]), "+f"(d[57]), "+f"(d[58]), "+f"(d[59]), "+f"(d[60]), "+f"(d[61]), "+f"(d[62]), "+f"(d[63])
    : "l"(da), "l"(db), "n"(TB));
}
template <int TB>
__device__ __forceinline__ void wg_rs256(float (&d)[128], uint32_t a0, uint32_t a1, uint32_t a2, uint32_t a3, uint64_t db) {
  asm volatile(
    "wgmma.mma_async.sync.aligned.m64n256k16.f32.bf16.bf16 {%0, %1, %2, %3, %4, %5, %6, %7, %8, %9, %10, %11, %12, %13, %14, %15, %16, %17, %18, %19, %20, %21, %22, %23, %24, %25, %26, %27, %28, %29, %30, %31, %32, %33, %34, %35, %36, %37, %38, %39, %40, %41, %42, %43, %44, %45, %46, %47, %48, %49, %50, %51, %52, %53, %54, %55, %56, %57, %58, %59, %60, %61, %62, %63, %64, %65, %66, %67, %68, %69, %70, %71, %72, %73, %74, %75, %76, %77, %78, %79, %80, %81, %82, %83, %84, %85, %86, %87, %88, %89, %90, %91, %92, %93, %94, %95, %96, %97, %98, %99, %100, %101, %102, %103, %104, %105, %106, %107, %108, %109, %110, %111, %112, %113, %114, %115, %116, %117, %118, %119, %120, %121, %122, %123, %124, %125, %126, %127}, {%128, %129, %130, %131}, %132, 1, 1, 1, %133;"
    : "+f"(d[0]), "+f"(d[1]), "+f"(d[2]), "+f"(d[3]), "+f"(d[4]), "+f"(d[5]), "+f"(d[6]), "+f"(d[7]), "+f"(d[8]), "+f"(d[9]), "+f"(d[10]), "+f"(d[11]), "+f"(d[12]), "+f"(d[13]), "+f"(d[14]), "+f"(d[15]), "+f"(d[16]), "+f"(d[17]), "+f"(d[18]), "+f"(d[19]), "+f"(d[20]), "+f"(d[21]), "+f"(d[22]), "+f"(d[23]), "+f"(d[24]), "+f"(d[25]), "+f"(d[26]), "+f"(d[27]), "+f"(d[28]), "+f"(d[29]), "+f"(d[30]), "+f"(d[31]), "+f"(d[32]), "+f"(d[33]), "+f"(d[34]), "+f"(d[35]), "+f"(d[36]), "+f"(d[37]), "+f"(d[38]), "+f"(d[39]), "+f"(d[40]), "+f"(d[41]), "+f"(d[42]), "+f"(d[43]), "+f"(d[44]), "+f"(d[45]), "+f"(d[46]), "+f"(d[47]), "+f"(d[48]), "+f"(d[49]), "+f"(d[50]), "+f"(d[51]), "+f"(d[52]), "+f"(d[53]), "+f"(d[54]), "+f"(d[55]), "+f"(d[56]), "+f"(d[57]), "+f"(d[58]), "+f"(d[59]), "+f"(d[60]), "+f"(d[61]), "+f"(d[62]), "+f"(d[63]), "+f"(d[64]), "+f"(d[65]), "+f"(d[66]), "+f"(d[67]), "+f"(d[68]), "+f"(d[69]), "+f"(d[70]), "+f"(d[71]), "+f"(d[72]), "+f"(d[73]), "+f"(d[74]), "+f"(d[75]), "+f"(d[76]), "+f"(d[77]), "+f"(d[78]), "+f"(d[79]), "+f"(d[80]), "+f"(d[81]), "+f"(d[82]), "+f"(d[83]), "+f"(d[84]), "+f"(d[85]), "+f"(d[86]), "+f"(d[87]), "+f"(d[88]), "+f"(d[89]), "+f"(d[90]), "+f"(d[91]), "+f"(d[92]), "+f"(d[93]), "+f"(d[94]), "+f"(d[95]), "+f"(d[96]), "+f"(d[97]), "+f"(d[98]), "+f"(d[99]), "+f"(d[100]), "+f"(d[101]), "+f"(d[102]), "+f"(d[103]), "+f"(d[104]), "+f"(d[105]), "+f"(d[106]), "+f"(d[107]), "+f"(d[108]), "+f"(d[109]), "+f"(d[110]), "+f"(d[111]), "+f"(d[112]), "+f"(d[113]), "+f"(d[114]), "+f"(d[115]), "+f"(d[116]), "+f"(d[117]), "+f"(d[118]), "+f"(d[119]), "+f"(d[120]), "+f"(d[121]), "+f"(d[122]), "+f"(d[123]), "+f"(d[124]), "+f"(d[125]), "+f"(d[126]), "+f"(d[127])
    : "r"(a0), "r"(a1), "r"(a2), "r"(a3), "l"(db), "n"(TB));
}
template <int TB>
__device__ __forceinline__ void wg_rs32(float (&d)[16], uint32_t a0, uint32_t a1, uint32_t a2, uint32_t a3, uint64_t db) {
  asm volatile(
    "wgmma.mma_async.sync.aligned.m64n32k16.f32.bf16.bf16 {%0, %1, %2, %3, %4, %5, %6, %7, %8, %9, %10, %11, %12, %13, %14, %15}, {%16, %17, %18, %19}, %20, 1, 1, 1, %21;"
    : "+f"(d[0]), "+f"(d[1]), "+f"(d[2]), "+f"(d[3]), "+f"(d[4]), "+f"(d[5]), "+f"(d[6]), "+f"(d[7]), "+f"(d[8]), "+f"(d[9]), "+f"(d[10]), "+f"(d[11]), "+f"(d[12]), "+f"(d[13]), "+f"(d[14]), "+f"(d[15])
    : "r"(a0), "r"(a1), "r"(a2), "r"(a3), "l"(db), "n"(TB));
}
template <int TB>
__device__ __forceinline__ void wg_cv128(float (&d)[64], uint32_t a0, uint32_t a1, uint32_t a2, uint32_t a3, uint64_t db) {
  asm volatile(
    "wgmma.mma_async.sync.aligned.m64n128k16.f32.bf16.bf16 {%0, %1, %2, %3, %4, %5, %6, %7, %8, %9, %10, %11, %12, %13, %14, %15, %16, %17, %18, %19, %20, %21, %22, %23, %24, %25, %26, %27, %28, %29, %30, %31, %32, %33, %34, %35, %36, %37, %38, %39, %40, %41, %42, %43, %44, %45, %46, %47, %48, %49, %50, %51, %52, %53, %54, %55, %56, %57, %58, %59, %60, %61, %62, %63}, {%64, %65, %66, %67}, %68, 1, 1, 1, %69;"
    : "+f"(d[0]), "+f"(d[1]), "+f"(d[2]), "+f"(d[3]), "+f"(d[4]), "+f"(d[5]), "+f"(d[6]), "+f"(d[7]), "+f"(d[8]), "+f"(d[9]), "+f"(d[10]), "+f"(d[11]), "+f"(d[12]), "+f"(d[13]), "+f"(d[14]), "+f"(d[15]), "+f"(d[16]), "+f"(d[17]), "+f"(d[18]), "+f"(d[19]), "+f"(d[20]), "+f"(d[21]), "+f"(d[22]), "+f"(d[23]), "+f"(d[24]), "+f"(d[25]), "+f"(d[26]), "+f"(d[27]), "+f"(d[28]), "+f"(d[29]), "+f"(d[30]), "+f"(d[31]), "+f"(d[32]), "+f"(d[33]), "+f"(d[34]), "+f"(d[35]), "+f"(d[36]), "+f"(d[37]), "+f"(d[38]), "+f"(d[39]), "+f"(d[40]), "+f"(d[41]), "+f"(d[42]), "+f"(d[43]), "+f"(d[44]), "+f"(d[45]), "+f"(d[46]), "+f"(d[47]), "+f"(d[48]), "+f"(d[49]), "+f"(d[50]), "+f"(d[51]), "+f"(d[52]), "+f"(d[53]), "+f"(d[54]), "+f"(d[55]), "+f"(d[56]), "+f"(d[57]), "+f"(d[58]), "+f"(d[59]), "+f"(d[60]), "+f"(d[61]), "+f"(d[62]), "+f"(d[63])
    : "r"(a0), "r"(a1), "r"(a2), "r"(a3), "l"(db), "n"(TB));
}
template <int TB>
__device__ __forceinline__ void wg_cv96(float (&d)[48], uint32_t a0, uint32_t a1, uint32_t a2, uint32_t a3, uint64_t db) {
  asm volatile(
    "wgmma.mma_async.sync.aligned.m64n96k16.f32.bf16.bf16 {%0, %1, %2, %3, %4, %5, %6, %7, %8, %9, %10, %11, %12, %13, %14, %15, %16, %17, %18, %19, %20, %21, %22, %23, %24, %25, %26, %27, %28, %29, %30, %31, %32, %33, %34, %35, %36, %37, %38, %39, %40, %41, %42, %43, %44, %45, %46, %47}, {%48, %49, %50, %51}, %52, 1, 1, 1, %53;"
    : "+f"(d[0]), "+f"(d[1]), "+f"(d[2]), "+f"(d[3]), "+f"(d[4]), "+f"(d[5]), "+f"(d[6]), "+f"(d[7]), "+f"(d[8]), "+f"(d[9]), "+f"(d[10]), "+f"(d[11]), "+f"(d[12]), "+f"(d[13]), "+f"(d[14]), "+f"(d[15]), "+f"(d[16]), "+f"(d[17]), "+f"(d[18]), "+f"(d[19]), "+f"(d[20]), "+f"(d[21]), "+f"(d[22]), "+f"(d[23]), "+f"(d[24]), "+f"(d[25]), "+f"(d[26]), "+f"(d[27]), "+f"(d[28]), "+f"(d[29]), "+f"(d[30]), "+f"(d[31]), "+f"(d[32]), "+f"(d[33]), "+f"(d[34]), "+f"(d[35]), "+f"(d[36]), "+f"(d[37]), "+f"(d[38]), "+f"(d[39]), "+f"(d[40]), "+f"(d[41]), "+f"(d[42]), "+f"(d[43]), "+f"(d[44]), "+f"(d[45]), "+f"(d[46]), "+f"(d[47])
    : "r"(a0), "r"(a1), "r"(a2), "r"(a3), "l"(db), "n"(TB));
}
template <int TB>
__device__ __forceinline__ void wg_cv64(float (&d)[32], uint32_t a0, uint32_t a1, uint32_t a2, uint32_t a3, uint64_t db) {
  asm volatile(
    "wgmma.mma_async.sync.aligned.m64n64k16.f32.bf16.bf16 {%0, %1, %2, %3, %4, %5, %6, %7, %8, %9, %10, %11, %12, %13, %14, %15, %16, %17, %18, %19, %20, %21, %22, %23, %24, %25, %26, %27, %28, %29, %30, %31}, {%32, %33, %34, %35}, %36, 1, 1, 1, %37;"
    : "+f"(d[0]), "+f"(d[1]), "+f"(d[2]), "+f"(d[3]), "+f"(d[4]), "+f"(d[5]), "+f"(d[6]), "+f"(d[7]), "+f"(d[8]), "+f"(d[9]), "+f"(d[10]), "+f"(d[11]), "+f"(d[12]), "+f"(d[13]), "+f"(d[14]), "+f"(d[15]), "+f"(d[16]), "+f"(d[17]), "+f"(d[18]), "+f"(d[19]), "+f"(d[20]), "+f"(d[21]), "+f"(d[22]), "+f"(d[23]), "+f"(d[24]), "+f"(d[25]), "+f"(d[26]), "+f"(d[27]), "+f"(d[28]), "+f"(d[29]), "+f"(d[30]), "+f"(d[31])
    : "r"(a0), "r"(a1), "r"(a2), "r"(a3), "l"(db), "n"(TB));
}
template <int TB>
__device__ __forceinline__ void wg_cv128_init(float (&d)[64], uint32_t a0, uint32_t a1, uint32_t a2, uint32_t a3, uint64_t db) {
  asm volatile(
    "wgmma.mma_async.sync.aligned.m64n128k16.f32.bf16.bf16 {%0, %1, %2, %3, %4, %5, %6, %7, %8, %9, %10, %11, %12, %13, %14, %15, %16, %17, %18, %19, %20, %21, %22, %23, %24, %25, %26, %27, %28, %29, %30, %31, %32, %33, %34, %35, %36, %37, %38, %39, %40, %41, %42, %43, %44, %45, %46, %47, %48, %49, %50, %51, %52, %53, %54, %55, %56, %57, %58, %59, %60, %61, %62, %63}, {%64, %65, %66, %67}, %68, 0, 1, 1, %69;"
    : "=f"(d[0]), "=f"(d[1]), "=f"(d[2]), "=f"(d[3]), "=f"(d[4]), "=f"(d[5]), "=f"(d[6]), "=f"(d[7]), "=f"(d[8]), "=f"(d[9]), "=f"(d[10]), "=f"(d[11]), "=f"(d[12]), "=f"(d[13]), "=f"(d[14]), "=f"(d[15]), "=f"(d[16]), "=f"(d[17]), "=f"(d[18]), "=f"(d[19]), "=f"(d[20]), "=f"(d[21]), "=f"(d[22]), "=f"(d[23]), "=f"(d[24]), "=f"(d[25]), "=f"(d[26]), "=f"(d[27]), "=f"(d[28]), "=f"(d[29]), "=f"(d[30]), "=f"(d[31]), "=f"(d[32]), "=f"(d[33]), "=f"(d[34]), "=f"(d[35]), "=f"(d[36]), "=f"(d[37]), "=f"(d[38]), "=f"(d[39]), "=f"(d[40]), "=f"(d[41]), "=f"(d[42]), "=f"(d[43]), "=f"(d[44]), "=f"(d[45]), "=f"(d[46]), "=f"(d[47]), "=f"(d[48]), "=f"(d[49]), "=f"(d[50]), "=f"(d[51]), "=f"(d[52]), "=f"(d[53]), "=f"(d[54]), "=f"(d[55]), "=f"(d[56]), "=f"(d[57]), "=f"(d[58]), "=f"(d[59]), "=f"(d[60]), "=f"(d[61]), "=f"(d[62]), "=f"(d[63])
    : "r"(a0), "r"(a1), "r"(a2), "r"(a3), "l"(db), "n"(TB));
}
template <int TB>
__device__ __forceinline__ void wg_rs256_init(float (&d)[128], uint32_t a0, uint32_t a1, uint32_t a2, uint32_t a3, uint64_t db) {
  asm volatile(
    "wgmma.mma_async.sync.aligned.m64n256k16.f32.bf16.bf16 {%0, %1, %2, %3, %4, %5, %6, %7, %8, %9, %10, %11, %12, %13, %14, %15, %16, %17, %18, %19, %20, %21, %22, %23, %24, %25, %26, %27, %28, %29, %30, %31, %32, %33, %34, %35, %36, %37, %38, %39, %40, %41, %42, %43, %44, %45, %46, %47, %48, %49, %50, %51, %52, %53, %54, %55, %56, %57, %58, %59, %60, %61, %62, %63, %64, %65, %66, %67, %68, %69, %70, %71, %72, %73, %74, %75, %76, %77, %78, %79, %80, %81, %82, %83, %84, %85, %86, %87, %88, %89, %90, %91, %92, %93, %94, %95, %96, %97, %98, %99, %100, %101, %102, %103, %104, %105, %106, %107, %108, %109, %110, %111, %112, %113, %114, %115, %116, %117, %118, %119, %120, %121, %122, %123, %124, %125, %126, %127}, {%128, %129, %130, %131}, %132, 0, 1, 1, %133;"
    : "=f"(d[0]), "=f"(d[1]), "=f"(d[2]), "=f"(d[3]), "=f"(d[4]), "=f"(d[5]), "=f"(d[6]), "=f"(d[7]), "=f"(d[8]), "=f"(d[9]), "=f"(d[10]), "=f"(d[11]), "=f"(d[12]), "=f"(d[13]), "=f"(d[14]), "=f"(d[15]), "=f"(d[16]), "=f"(d[17]), "=f"(d[18]), "=f"(d[19]), "=f"(d[20]), "=f"(d[21]), "=f"(d[22]), "=f"(d[23]), "=f"(d[24]), "=f"(d[25]), "=f"(d[26]), "=f"(d[27]), "=f"(d[28]), "=f"(d[29]), "=f"(d[30]), "=f"(d[31]), "=f"(d[32]), "=f"(d[33]), "=f"(d[34]), "=f"(d[35]), "=f"(d[36]), "=f"(d[37]), "=f"(d[38]), "=f"(d[39]), "=f"(d[40]), "=f"(d[41]), "=f"(d[42]), "=f"(d[43]), "=f"(d[44]), "=f"(d[45]), "=f"(d[46]), "=f"(d[47]), "=f"(d[48]), "=f"(d[49]), "=f"(d[50]), "=f"(d[51]), "=f"(d[52]), "=f"(d[53]), "=f"(d[54]), "=f"(d[55]), "=f"(d[56]), "=f"(d[57]), "=f"(d[58]), "=f"(d[59]), "=f"(d[60]), "=f"(d[61]), "=f"(d[62]), "=f"(d[63]), "=f"(d[64]), "=f"(d[65]), "=f"(d[66]), "=f"(d[67]), "=f"(d[68]), "=f"(d[69]), "=f"(d[70]), "=f"(d[71]), "=f"(d[72]), "=f"(d[73]), "=f"(d[74]), "=f"(d[75]), "=f"(d[76]), "=f"(d[77]), "=f"(d[78]), "=f"(d[79]), "=f"(d[80]), "=f"(d[81]), "=f"(d[82]), "=f"(d[83]), "=f"(d[84]), "=f"(d[85]), "=f"(d[86]), "=f"(d[87]), "=f"(d[88]), "=f"(d[89]), "=f"(d[90]), "=f"(d[91]), "=f"(d[92]), "=f"(d[93]), "=f"(d[94]), "=f"(d[95]), "=f"(d[96]), "=f"(d[97]), "=f"(d[98]), "=f"(d[99]), "=f"(d[100]), "=f"(d[101]), "=f"(d[102]), "=f"(d[103]), "=f"(d[104]), "=f"(d[105]), "=f"(d[106]), "=f"(d[107]), "=f"(d[108]), "=f"(d[109]), "=f"(d[110]), "=f"(d[111]), "=f"(d[112]), "=f"(d[113]), "=f"(d[114]), "=f"(d[115]), "=f"(d[116]), "=f"(d[117]), "=f"(d[118]), "=f"(d[119]), "=f"(d[120]), "=f"(d[121]), "=f"(d[122]), "=f"(d[123]), "=f"(d[124]), "=f"(d[125]), "=f"(d[126]), "=f"(d[127])
    : "r"(a0), "r"(a1), "r"(a2), "r"(a3), "l"(db), "n"(TB));
}
template <int TB>
__device__ __forceinline__ void wg_rs32_init(float (&d)[16], uint32_t a0, uint32_t a1, uint32_t a2, uint32_t a3, uint64_t db) {
  asm volatile(
    "wgmma.mma_async.sync.aligned.m64n32k16.f32.bf16.bf16 {%0, %1, %2, %3, %4, %5, %6, %7, %8, %9, %10, %11, %12, %13, %14, %15}, {%16, %17, %18, %19}, %20, 0, 1, 1, %21;"
    : "=f"(d[0]), "=f"(d[1]), "=f"(d[2]), "=f"(d[3]), "=f"(d[4]), "=f"(d[5]), "=f"(d[6]), "=f"(d[7]), "=f"(d[8]), "=f"(d[9]), "=f"(d[10]), "=f"(d[11]), "=f"(d[12]), "=f"(d[13]), "=f"(d[14]), "=f"(d[15])
    : "r"(a0), "r"(a1), "r"(a2), "r"(a3), "l"(db), "n"(TB));
}


constexpr int NST = 7, SLOT = 9216;
constexpr uint32_t SM_XN = 0, SM_HIN = 147456, SM_RING = 163840, SM_BAR = SM_RING + 7 * SLOT;
constexpr uint32_t SM_KD = SM_BAR + 256, SMEM_BYTES = SM_KD + 3840;
constexpr uint32_t B_FULL = 0, B_EMPTY = 56, B_XN = 112, B_K2048 = 176, B_HF = 184, B_HE = 200, B_CV = 216, B_PT = 224, B_YT = 232, B_SG = 240, B_X = 248;
constexpr uint32_t PR_LN = 65536, PR_PAR = 98304, PR_K0 = SM_HIN + 12288;
constexpr uint32_t T_U = 0, T_KP = 17408, T_K0 = 51200, T_X0 = 53248, T_X1 = SM_HIN + 4 * 18432, T_YT = 0, T_STG = 65536, T_PART = SM_HIN;
constexpr uint32_t U_BYTES = U_LEN * 2, KP_BYTES = KP_LEN * 4, IMG = 18432;

struct Params {
  const __nv_bfloat16 *xp, *logA, *Aim, *Cre, *Cim, *logdt, *Dsk;
  CUtensorMap xn, gate, up, dn, dn5, x, x5, y, y5, out, out5;
};

struct KgIn { uint32_t la, ai, cr, ci, ldt, dsk; };
__device__ __forceinline__ void kgen_load(const Params& p, int ch0, int tid, KgIn& in) {
  const int e = ch0 * (NM_ / 2) + tid;
  in.la = __ldg((const uint32_t*)p.logA + e); in.ai = __ldg((const uint32_t*)p.Aim + e);
  in.cr = __ldg((const uint32_t*)p.Cre + e); in.ci = __ldg((const uint32_t*)p.Cim + e);
  in.ldt = __ldg((const unsigned short*)p.logdt + ch0 + (tid >> 6)); in.dsk = __ldg((const unsigned short*)p.Dsk + ch0 + (tid >> 6));
}
struct KgState { float acc[5][4]; float v; };
struct cf { float r, i; };
__device__ __forceinline__ cf cmul(cf a, cf b) { return {fmaf(a.r, b.r, -(a.i * b.i)), fmaf(a.r, b.i, a.i * b.r)}; }
__device__ __forceinline__ cf csq(cf a) { return {fmaf(a.r, a.r, -(a.i * a.i)), (a.r + a.r) * a.i}; }
__device__ __forceinline__ cf cexp2(float lm, float th) {
  float m; asm("ex2.approx.ftz.f32 %0, %1;" : "=f"(m) : "f"(lm));
  return {m * __cosf(th), m * __sinf(th)};
}
__device__ __forceinline__ float turns(float w) { return (w - rintf(w)) * 6.283185307179586f; }
__device__ __forceinline__ void kgen_params(unsigned char* sm, int tid, KgIn in, KgState& st) {
  const int warp = tid >> 5, lane = tid & 31;
  float4* par = (float4*)(sm + PR_PAR + warp * 6144) + lane;
  const float dt = bf_round(expf(bf_lo(in.ldt)));
  float v = 0.f;
#pragma unroll 1
  for (int r = 0; r < 2; r++) {
    const float x = -bf_round(expf(bf_lo(in.la))) * dt * 1.4426950408889634f;
    const float w = bf_lo(in.ai) * dt * 0.15915494309189535f;
    const cf c = {2.f * bf_lo(in.cr) * dt, 2.f * bf_lo(in.ci) * dt};
    const cf e2 = cexp2(2.f * x, turns(2.f * w)), e64 = cexp2(64.f * x, turns(64.f * w));
    const cf e4 = csq(e2), e6 = cmul(e2, e4), e128 = csq(e64), e256 = csq(e128), e512 = csq(e256), e1024 = csq(e512);
    const cf c1 = cmul(c, e128), c256 = cmul(c, e256), c512 = cmul(c, e512), c4 = cmul(c, e1024);
    const cf c516 = cmul(c512, e4), c258 = cmul(c256, e2), c260 = cmul(c256, e4), c262 = cmul(c256, e6);
    v += fmaf(c4.r, e1024.r, -(c4.i * e1024.i));
    par[0] = make_float4(x, turns(w), turns(8.f * w), turns(128.f * w));
    par[64] = make_float4(c.r, c.i, c1.r, c1.i);
    par[128] = make_float4(c4.r, c4.i, e64.r, e64.i);
    par[192] = make_float4(c512.r, c512.i, c516.r, c516.i);
    par[256] = make_float4(c256.r, c256.i, c258.r, c258.i);
    par[320] = make_float4(c260.r, c260.i, c262.r, c262.i);
    par += 32;
    in.la >>= 16; in.ai >>= 16; in.cr >>= 16; in.ci >>= 16;
  }
#pragma unroll
  for (int o = 16; o; o >>= 1) v += __shfl_xor_sync(0xffffffffu, v, o);
  __syncwarp();
#pragma unroll
  for (int t = 0; t < 5; t++) { st.acc[t][0] = st.acc[t][1] = st.acc[t][2] = st.acc[t][3] = 0.f; }
  if (lane == 0 && !(warp & 1)) st.acc[0][0] = bf_lo(in.dsk);
  st.v = v;
}
__device__ __forceinline__ void kgen_steps(unsigned char* sm, int tid, KgState& st) {
  const int warp = tid >> 5, lane = tid & 31, g = lane >> 2, q = lane & 3;
  const float4* par = (const float4*)(sm + PR_PAR + warp * 6144) + q;
  const float2* p3 = (const float2*)(par + 192) + (g & 1);
  const float2* p2 = (const float2*)(par + 256 + 64 * ((g >> 1) & 1)) + (g & 1);
  const float g1 = (float)g, g8 = 8.f * g1, g128 = 128.f * g1;
  const int l1 = 4 * (g >> 1) + q, l2 = 4 * (g >> 2) + q;
#pragma unroll 4
  for (int ks = 0; ks < 16; ks++) {
    const float4 P = par[4 * ks], Q = par[64 + 4 * ks], R = par[128 + 4 * ks];
    const float2 c3 = p3[8 * ks], c2 = p2[8 * ks];
    const cf e = cexp2(P.x * g1, P.y * g1), a1 = cexp2(P.x * g8, P.z * g1), t = cexp2(P.x * g128, P.w * g1);
    const cf a2 = cmul(a1, cf{R.z, R.w});
    const cf t1 = {__shfl_sync(0xffffffffu, t.r, l1), __shfl_sync(0xffffffffu, t.i, l1)};
    const cf t2 = {__shfl_sync(0xffffffffu, t.r, l2), __shfl_sync(0xffffffffu, t.i, l2)};
    auto mma = [&](float (&d)[4], cf u, float cr, float ci) {
      const float b0 = fmaf(u.r, cr, -(u.i * ci)), b1 = fmaf(-u.r, ci, -(u.i * cr));
      asm("mma.sync.aligned.m16n8k8.row.col.f32.tf32.tf32.f32 {%0,%1,%2,%3}, {%4,%5,%6,%7}, {%8,%9}, {%0,%1,%2,%3};"
          : "+f"(d[0]), "+f"(d[1]), "+f"(d[2]), "+f"(d[3])
          : "r"(__float_as_uint(a1.r)), "r"(__float_as_uint(a2.r)), "r"(__float_as_uint(a1.i)), "r"(__float_as_uint(a2.i)),
            "r"(__float_as_uint(b0)), "r"(__float_as_uint(b1)));
    };
    mma(st.acc[0], e, Q.x, Q.y);
    mma(st.acc[1], e, Q.z, Q.w);
    mma(st.acc[4], t, R.x, R.y);
    mma(st.acc[2], t2, c2.x, c2.y);
    mma(st.acc[3], t1, c3.x, c3.y);
  }
}
__device__ __forceinline__ void kgen_finish(unsigned char* sm, unsigned short* kd, unsigned short* k2048, int tid, KgState& st) {
  const int warp = tid >> 5, lane = tid & 31, g = lane >> 2, q = lane & 3;
  float4* red = (float4*)(sm + SM_HIN + (warp >> 1) * 3072) + lane;
  if (warp & 1) {
#pragma unroll
    for (int t = 0; t < 5; t++) red[t * 32] = make_float4(st.acc[t][0], st.acc[t][1], st.acc[t][2], st.acc[t][3]);
    red[160].x = st.v;
  }
  named_bar(3, 256);
  if (!(warp & 1)) {
    uint32_t lo[5], hi[5];
#pragma unroll
    for (int t = 0; t < 5; t++) {
      const float4 r = red[t * 32];
      lo[t] = pack_bf16(st.acc[t][0] + r.x, st.acc[t][1] + r.y); hi[t] = pack_bf16(st.acc[t][2] + r.z, st.acc[t][3] + r.w);
    }
    *k2048 = (unsigned short)pack_bf16(st.v + red[160].x, 0.f);
    uint32_t* kw = (uint32_t*)kd;
    kw[lane] = lo[0]; kw[32 + lane] = hi[0]; kw[64 + lane] = lo[1]; kw[96 + lane] = hi[1];
    kw[128 + 2 * g + (q & 1) + 32 * (q >> 1)] = lo[2]; kw[144 + 2 * g + (q & 1) + 32 * (q >> 1)] = hi[2];
    kw[192 + g + 16 * q] = lo[3]; kw[200 + g + 16 * q] = hi[3];
    kd[512 + g + 32 * q] = (unsigned short)lo[4]; kd[528 + g + 32 * q] = (unsigned short)(lo[4] >> 16);
    kd[520 + g + 32 * q] = (unsigned short)hi[4]; kd[536 + g + 32 * q] = (unsigned short)(hi[4] >> 16);
  }
}
constexpr int kd_index(int l) {
  if (l < 256) return l;
  const int sh = l < 512 ? 1 : l < 1024 ? 2 : 3;
  return ((l + (1 << (sh - 1)) - 1 + ((l >> sh) & 1)) >> sh) + 128 * sh;
}
struct KTab { unsigned int e[512 * 4]; };
constexpr KTab make_ktab() {
  KTab t = {};
  for (int it = 0; it < 511; it++) {
    const int l0 = 4 * it, b1 = kd_index(l0) & ~1;
    const unsigned int np = 0x54 + 0x22 * (l0 ? kd_index(l0 - 1) - b1 : 0);
    unsigned int n[4] = {0, 0, 0, 0};
    for (int k = 0; k < 4; k++) n[k] = 0x10 + 0x22 * (kd_index(l0 + k) - b1);
    t.e[4 * it] = 2 * b1 | ((b1 < 638 ? 4u : 0u) << 16);
    t.e[4 * it + 1] = (n[0] + 0x44) | (np << 8) | (n[1] << 16) | (n[0] << 24);
    t.e[4 * it + 2] = n[2] | (n[1] << 8) | (n[3] << 16) | (n[2] << 24);
    t.e[4 * it + 3] = l0 ? 0xffffffffu : 0xffffu;
  }
  return t;
}
__device__ __align__(16) const KTab g_ktab = make_ktab();
template <int NT>
__device__ __forceinline__ void kexpand(uint32_t sb, uint32_t k0, uint32_t k1, uint32_t k2048, int tid, uint4 e) {
#pragma unroll 1
  for (int it = tid; it < 511; it += NT) {
    const uint4 en = __ldg((const uint4*)g_ktab.e + min(it + NT, 511));
    const uint32_t o = e.x & 0xffffu, o2 = o + (e.x >> 16), dst = sb + T_KP + 64 + 16 * it;
#pragma unroll
    for (int c = 0; c < 4; c++) {
      const uint32_t a = c ? k1 + 1280 * (c - 1) : k0;
      const uint32_t x0 = lds32(a + o - 4), x1 = lds32(a + o), x2 = lds32(a + o2);
      sts128(dst + c * KP_BYTES, make_uint4(__byte_perm(x0, x1, e.y) & e.w, __byte_perm(x1, x2, e.y >> 16), __byte_perm(x1, x2, e.z), __byte_perm(x1, x2, e.z >> 16)));
    }
    e = en;
  }
  if (tid < 36) {
    const int c = tid / 9, i = tid - 9 * c;
    uint4 v = make_uint4(0u, 0u, 0u, 0u);
    if (i == 4) {
      uint32_t z, y;
      asm volatile("ld.shared.u16 %0, [%1];" : "=r"(z) : "r"(k2048 + 2 * c) : "memory");
      asm volatile("ld.shared.u16 %0, [%1];" : "=r"(y) : "r"((c ? k1 + 1280 * (c - 1) : k0) + 1278) : "memory");
      v = make_uint4(z | (y << 16), z * 0x10001u, z * 0x10001u, z * 0x10001u);
    }
    sts128(sb + T_KP + c * KP_BYTES + 16 * (i < 4 ? i : 511 + i), v);
  }
  if (tid < 64) sts128(sb + T_U + (tid >> 4) * U_BYTES + (tid & 15) * 16, make_uint4(0u, 0u, 0u, 0u));
  fence_async_smem();
}

template <int NR>
__device__ __forceinline__ void conv_mma(float (&d)[NR], const uint32_t* a, uint64_t db) {
  if constexpr (NR == 64) wg_cv128<0>(d, a[0], a[1], a[2], a[3], db);
  else if constexpr (NR == 48) wg_cv96<0>(d, a[0], a[1], a[2], a[3], db);
  else if constexpr (NR == 32) wg_cv64<0>(d, a[0], a[1], a[2], a[3], db);
  else wg_rs32<0>(d, a[0], a[1], a[2], a[3], db);
}
__device__ __forceinline__ void conv_load(uint32_t (&a)[8], uint32_t o) {
#pragma unroll
  for (int c = 0; c < 2; c++) {
    a[4 * c + 0] = lds32(o + c * KP_BYTES); a[4 * c + 1] = lds32(o + c * KP_BYTES + 512);
    a[4 * c + 2] = lds32(o + c * KP_BYTES - 32); a[4 * c + 3] = lds32(o + c * KP_BYTES + 480);
  }
}
template <int NR>
__device__ __forceinline__ void conv_phase(float (&dA)[NR], float (&dB)[NR], uint32_t (&a)[4][8], uint32_t kp, uint64_t dU) {
#pragma unroll
  for (int i = 0; i < 2; i++) {
#pragma unroll
    for (int k = 0; k < 4; k++) {
      wg_fence();
      if constexpr (NR == 64) {
        if (i == 0 && k == 0) { wg_cv128_init<0>(dA, a[0][0], a[0][1], a[0][2], a[0][3], dU); wg_cv128_init<0>(dB, a[0][4], a[0][5], a[0][6], a[0][7], dU + (U_BYTES >> 4)); }
        else { conv_mma<NR>(dA, a[k], dU - 2 * k); conv_mma<NR>(dB, a[k] + 4, dU - 2 * k + (U_BYTES >> 4)); }
      } else { conv_mma<NR>(dA, a[k], dU - 2 * k); conv_mma<NR>(dB, a[k] + 4, dU - 2 * k + (U_BYTES >> 4)); }
      wg_commit();
      wg_wait<1>();
      if (k == 2 && i) kp += 64 * 24;
      conv_load(a[(k + 2) & 3], kp + 64 * (k + 2));
    }
    kp += 256;
    dU -= 8;
  }
  wg_wait<0>();
  reg_fence(dA); reg_fence(dB);
}
template <int NR>
__device__ __forceinline__ void upper_copy(float (&dst)[NR - 16], const float (&src)[NR]) {
#pragma unroll
  for (int i = 0; i < NR - 16; i++) asm volatile("mov.b32 %0, %1;" : "=f"(dst[i]) : "f"(src[i + 16]));
}
__device__ __forceinline__ void conv2(uint32_t sb, int wg, int w, int lane, uint32_t bar_free) {
  const int g = lane >> 2, q = lane & 3;
  float dA[64], dB[64];
  uint32_t a[4][8];
  const uint32_t kp = sb + T_KP + 2 * wg * KP_BYTES + 4 * (16 + 256 * (w >> 1) + 8 * (w & 1) + g - 2 * q);
  const uint64_t dU = mk_desc(sb + T_U + 2 * wg * U_BYTES + 256, 16, 256, 3);
  conv_load(a[0], kp); conv_load(a[1], kp + 64);
  conv_phase<64>(dA, dB, a, kp, dU);
  float eA[48], eB[48];
  upper_copy<64>(eA, dA); upper_copy<64>(eB, dB);
  conv_phase<48>(eA, eB, a, kp + 2048, dU);
  float fA[32], fB[32];
  upper_copy<48>(fA, eA); upper_copy<48>(fB, eB);
  conv_phase<32>(fA, fB, a, kp + 4096, dU);
  float gA[16], gB[16];
  upper_copy<32>(gA, fA); upper_copy<32>(gB, fB);
  conv_phase<16>(gA, gB, a, kp + 6144, dU);
#pragma unroll
  for (int i = 0; i < 16; i++) {
    dA[16 + i] = eA[i]; dA[32 + i] = fA[i]; dA[48 + i] = gA[i];
    dB[16 + i] = eB[i]; dB[32 + i] = fB[i]; dB[48 + i] = gB[i];
  }
  float z[2][16][2];
#pragma unroll
  for (int m = 0; m < 16; m++)
#pragma unroll
    for (int e = 0; e < 2; e++) {
      z[0][m][e] = m ? dA[4 * m + e] + dA[4 * m - 2 + e] : dA[e];
      z[1][m][e] = m ? dB[4 * m + e] + dB[4 * m - 2 + e] : dB[e];
    }
  if (bar_free) mbar_wait(bar_free, 0);
  const uint32_t xb = sb + T_X0 + wg * 8192, xc = wg ? T_X1 - T_X0 - 8192 : 4096;
  const uint32_t xw = xb + (w * 32 + lane) * 16, xr = xb + ((w ^ 2) * 32 + lane) * 16;
  float k[2][8][2];
  if (w < 2) {
#pragma unroll
    for (int c = 0; c < 2; c++)
#pragma unroll
      for (int m = 0; m < 8; m += 4) {
        sts128(xw + c * xc + (m >> 2) * 2048, make_uint4(pack_bf16(z[c][8 + m][0], z[c][8 + m][1]), pack_bf16(z[c][9 + m][0], z[c][9 + m][1]),
                                                          pack_bf16(z[c][10 + m][0], z[c][10 + m][1]), pack_bf16(z[c][11 + m][0], z[c][11 + m][1])));
#pragma unroll
        for (int i = 0; i < 4; i++) { k[c][m + i][0] = z[c][m + i][0]; k[c][m + i][1] = z[c][m + i][1]; }
      }
  } else {
#pragma unroll
    for (int c = 0; c < 2; c++)
#pragma unroll
      for (int m = 0; m < 8; m += 4) {
        sts128(xw + c * xc + (m >> 2) * 2048, make_uint4(m ? pack_bf16(z[c][m - 2][0], z[c][m - 2][1]) : 0u, m ? pack_bf16(z[c][m - 1][0], z[c][m - 1][1]) : 0u,
                                                          pack_bf16(z[c][m][0], z[c][m][1]), pack_bf16(z[c][m + 1][0], z[c][m + 1][1])));
#pragma unroll
        for (int i = 0; i < 4; i++) { k[c][m + i][0] = z[c][6 + m + i][0]; k[c][m + i][1] = z[c][6 + m + i][1]; }
      }
  }
  named_bar(1 + wg, 128);
  const uint32_t yb = sb + T_U + 2 * wg * U_BYTES;
#pragma unroll
  for (int c = 0; c < 2; c++)
#pragma unroll
    for (int m = 0; m < 8; m += 4) {
      const uint4 u = lds128(xr + c * xc + (m >> 2) * 2048);
      stmatrix_x4_t(yb + c * 4096 + (64 * (w >> 1) + 8 * m + lane) * 32 + 16 * (w & 1),
                    pack_bf16(k[c][m][0] + bf_lo(u.x), k[c][m][1] + bf_hi(u.x)), pack_bf16(k[c][m + 1][0] + bf_lo(u.y), k[c][m + 1][1] + bf_hi(u.y)),
                    pack_bf16(k[c][m + 2][0] + bf_lo(u.z), k[c][m + 2][1] + bf_hi(u.z)), pack_bf16(k[c][m + 3][0] + bf_lo(u.w), k[c][m + 3][1] + bf_hi(u.w)));
    }
  fence_async_smem();
  named_arrive(10 + wg, 160);
}
__device__ __forceinline__ void conv_ship(uint32_t sb, uint32_t bar, int wg, int ch, int cnt, bool el) {
  named_bar(10 + wg, 160);
  if (el) {
    bulk_s2g(g_y + (size_t)ch * L_, sb + T_U + 2 * wg * U_BYTES, 8192);
    bulk_commit_wait();
    cnt_add_done(cnt);
    mbar_arrive(bar + B_SG);
  }
  __syncwarp();
}

__global__ void __cluster_dims__(2, 1, 1) __launch_bounds__(384, 1) fused_kernel(const __grid_constant__ Params p) {
  extern __shared__ __align__(1024) unsigned char smem_raw[];
  const uint32_t sb = smem_u32(smem_raw);
  const uint32_t bar = sb + SM_BAR;
  const uint32_t vb = blockIdx.x;
  const int j = vb & 1, pair = vb >> 1, mt = pair & 15, sp = pair >> 4;
  const bool spare = pair >= 64;
  const int warp = __shfl_sync(0xffffffffu, threadIdx.x >> 5, 0), wg = warp >> 2, w = warp & 3;
  const int row0 = mt * 128 + (2 * sp + j) * 16;
  const int f0 = sp * 1152;
  KgIn kin;
  if (wg < 2) kgen_load(p, spare ? 512 + ((int)vb - 128) * 16 : vb * 4, threadIdx.x, kin);
  if (threadIdx.x == 256) {
    mbar_init(bar + B_X, 1);
    if (!spare) {
      mbar_expect_tx(bar + B_X, 16 * D_ * 2);
      bulk_g2s(sb + PR_LN, p.xp + (size_t)row0 * D_, 16 * D_ * 2, bar + B_X);
    }
#pragma unroll
    for (int i = 0; i < 30; i++) if (i != 22) mbar_init(bar + 8 * i, (i >= 7 && i < 14) ? 8 : ((i == 27 && !spare) || i == 25 || i == 26) ? 4 : 1);
    mbar_init(bar + B_SG, 2);
    mbar_expect_tx(bar + B_HF, 8192); mbar_expect_tx(bar + B_HF + 8, 8192);
    asm volatile("fence.mbarrier_init.release.cluster;" ::: "memory");
  }
  __syncthreads();
  asm volatile("barrier.cluster.arrive.relaxed.aligned;" ::: "memory");

  if (wg == 2) {
    const int t = threadIdx.x & 127, lane = t & 31;
    const bool el = elect_one();
    if (!spare) {
      const uint32_t ra = sb + PR_LN + (t >> 3) * (D_ * 2) + (t & 7) * 16;
      if (w == 1 && el) {
#pragma unroll 1
        for (int u = 0; u < NST; u++) {
          const uint32_t dst = sb + SM_RING + u * SLOT, fb = bar + B_FULL + 8 * u;
          mbar_expect_tx(fb, 8192);
          tma_2d(dst, &p.gate, f0 + 64 * j, 32 * u, fb);
          tma_2d(dst + 4096, &p.up, f0 + 64 * j, 32 * u, fb);
        }
      }
      mbar_wait(bar + B_X, 0);
      uint4 v[9];
#pragma unroll
      for (int i = 0; i < 9; i++) v[i] = lds128(ra + i * 128);
      uint32_t* u = (uint32_t*)v;
      const float x0 = bf_lo(__shfl_sync(0xffffffffu, u[0], lane & 24));
      float s = 0.f, s2 = 0.f, q = 0.f, q2 = 0.f;
#pragma unroll
      for (int i = 0; i < 36; i++) {
        const float a = bf_lo(u[i]) - x0, b = bf_hi(u[i]) - x0;
        s += a; s2 += b; q = fmaf(a, a, q); q2 = fmaf(b, b, q2);
      }
      s += s2; q += q2;
#pragma unroll
      for (int o = 4; o; o >>= 1) { s += __shfl_xor_sync(0xffffffffu, s, o); q += __shfl_xor_sync(0xffffffffu, q, o); }
      s *= (1.0f / D_);
      const __nv_bfloat162 mb = __float2bfloat162_rn(s + x0);
      const float rinv = 1.0f / bf_round(sqrtf(bf_round(bf_round(fmaxf(fmaf(-s, s, q * (1.0f / D_)), 0.f)) + 1e-5f)));
#pragma unroll
      for (int i = 0; i < 36; i++) {
        const __nv_bfloat162 d2 = __hsub2(*(const __nv_bfloat162*)&u[i], mb);
        const uint32_t d = *(const uint32_t*)&d2;
        u[i] = pack_bf16(bf_lo(d) * rinv, bf_hi(d) * rinv);
      }
#pragma unroll
      for (int i = 0; i < 9; i++) sts128(ra + i * 128, v[i]);
      fence_async_smem();
      named_bar(5, 128);
      if (w == 0 && el) bulk_s2g(g_xn + (size_t)row0 * D_, sb + PR_LN, 16 * D_ * 2);
    }
    asm volatile("barrier.cluster.wait.aligned;" ::: "memory");
    asm volatile("setmaxnreg.dec.sync.aligned.u32 24;");
    if (w == 0) {
      if (!spare) {
        if (el) {
          bulk_commit_wait();
          cnt_add_done(C_LN + mt);
        }
        __syncwarp();
        cnt_wait(C_LN + mt, 8);
        fence_async_all();
#pragma unroll 1
        for (int kb = 0; kb < 6; kb++) {
          if (el) {
            mbar_expect_tx(bar + B_XN + 8 * kb, 16384);
            tma_2d(sb + SM_XN + kb * 16384, &p.xn, kb * 64, mt * 128, bar + B_XN + 8 * kb);
          }
        }
        named_bar(4, 384);
        uint32_t slot = 0, ph = 0;
#pragma unroll 1
        for (int c = 0; c <= 9; c++) {
          const int fc = f0 + c * 128;
          if (c < 9) {
            for (int u = c ? 0 : NST; u < 18; u++) {
              mbar_wait(bar + B_EMPTY + 8 * slot, ph);
              if (el) {
                const uint32_t dst = sb + SM_RING + slot * SLOT, fb = bar + B_FULL + 8 * slot;
                mbar_expect_tx(fb, 8192);
                tma_2d(dst, &p.gate, fc + 64 * j, 32 * u, fb);
                tma_2d(dst + 4096, &p.up, fc + 64 * j, 32 * u, fb);
                if (c == 0 && u < 10) {
                  const int kb = u - 1;
                  if (kb < 8) mbar_expect_tx(bar + B_XN + 8 * kb, kb < 7 ? 16384 : 32768);
                  tma_2d(sb + SM_XN + kb * 16384, &p.xn, kb * 64, mt * 128, bar + B_XN + 8 * min(kb, 7));
                }
              }
              if (++slot == NST) { slot = 0; ph ^= 1; }
            }
          }
          const int fp = fc - 128 + 64 * (1 - j), fo = fc + 64 * j;
#pragma unroll
          for (int i = 0; i < 8; i++) {
            const bool isP = i < 4;
            const int u = i & 3;
            if (isP ? (c == 0) : (c == 9)) continue;
            mbar_wait(bar + B_EMPTY + 8 * slot, ph);
            if (el) {
              const uint32_t dst = sb + SM_RING + slot * SLOT, fb = bar + B_FULL + 8 * slot;
              mbar_expect_tx(fb, 9216);
              tma_3d(dst, &p.dn, 0, (isP ? fp : fo) + 16 * u, 4 * j, fb);
              tma_2d(dst + 8192, &p.dn5, 512 + 32 * j, (isP ? fp : fo) + 16 * u, fb);
            }
            if (++slot == NST) { slot = 0; ph ^= 1; }
          }
        }
        const int ch0 = vb * 4;
        cnt_wait(C_U, 384);
        fence_async_all();
        if (el) {
          mbar_expect_tx(bar + B_CV, 4 * L_ * 2);
#pragma unroll 1
          for (int c = 0; c < 4; c++) bulk_g2s(sb + T_U + c * U_BYTES + 256, g_u + (size_t)(ch0 + c) * L_, L_ * 2, bar + B_CV);
        }
        unsigned char* img = g_part + (size_t)(2 * mt + j) * 16 * IMG;
        mbar_wait(bar + B_SG, 0);
        if (lane < 6) {
          const int r = (sp + 1 + (lane >> 1)) & 3;
          if (lane & 1) bulk_s2g(img + (r * 4 + sp) * IMG + 16384, sb + T_STG + 65536 + (r >> 1) * 8192 + (r & 1) * 2048, 2048);
          else bulk_s2g(img + (r * 4 + sp) * IMG, sb + T_STG + r * 16384, 16384);
          bulk_commit_wait();
        } else if (lane == 6) {
          mbar_expect_tx(bar + B_PT, 3 * IMG);
          mbar_expect_tx(bar + B_X, IMG);
          tma_2d(sb + T_PART + 3 * IMG, &p.x, 256 * j + 64 * sp, mt * 128, bar + B_X);
          tma_2d(sb + T_PART + 3 * IMG + 16384, &p.x5, 512 + 32 * j, mt * 128 + 32 * sp, bar + B_X);
        }
        __syncwarp();
        if (el) cnt_add_done(C_PART + 2 * mt + j);
        cnt_wait(C_PART + 2 * mt + j, 4);
        fence_async_all();
        if (lane < 3) bulk_g2s(sb + T_PART + lane * IMG, img + (sp * 4 + ((sp + 1 + lane) & 3)) * IMG, IMG, bar + B_PT);
        cnt_wait(C_Y5, 32);
        mbar_wait(bar + B_SG, 1);
        if (el) {
          mbar_expect_tx(bar + B_YT, IMG);
          tma_2d(sb + T_YT + 16384, &p.y5, mt * 128 + 32 * sp, 512 + 32 * j, bar + B_YT);
        }
        cnt_wait(C_Y + 4 * j + sp, 32);
        fence_async_all();
        if (el) {
          tma_2d(sb + T_YT, &p.y, mt * 128, 256 * j + 64 * sp, bar + B_YT);
          tma_2d(sb + T_YT + 8192, &p.y, mt * 128 + 64, 256 * j + 64 * sp, bar + B_YT);
        }
      } else {
        named_bar(7, 288);
        cnt_wait(C_U, 384);
        fence_async_all();
#pragma unroll 1
        for (int grp = 0; grp < 4; grp++) {
          const int ch0 = 512 + ((int)vb - 128) * 16 + grp * 4;
          if (grp) mbar_wait(bar + B_SG, (grp - 1) & 1);
          if (el) {
            mbar_expect_tx(bar + B_CV, 4 * L_ * 2);
#pragma unroll 1
            for (int c = 0; c < 4; c++) bulk_g2s(sb + T_U + c * U_BYTES + 256, g_u + (size_t)(ch0 + c) * L_, L_ * 2, bar + B_CV);
          }
        }
      }
      unsigned int old = 0;
      if (el) old = atomicAdd(g_cnt + C_DONE * 32, 1u) + 1;
      if (__any_sync(0xffffffffu, old == gridDim.x)) { g_cnt[lane * 32] = 0u; g_cnt[(lane + 32) * 32] = 0u; }
    } else {
      if (!spare) {
        named_bar(4, 384);
        uint4 k0v = make_uint4(0u, 0u, 0u, 0u);
        if (t < 112) k0v = lds128(sb + PR_K0 + (t - 32) * 16);
        named_bar(8, 96);
        if (t < 40) mbar_arrive_remote(mapa(bar + B_HE + 8 * (t & 1), j ^ 1));
#pragma unroll 1
        for (int i = 0; i < 8; i++) mbar_wait(bar + B_XN + 8 * i, 0);
        const int tok = 8 * ((lane & 7) >> 1) + 2 * (lane >> 3) + (lane & 1);
#pragma unroll 1
        for (int it = w - 1; it < 36; it += 3) {
          const int oc = 9 * (2 * sp + j) + (it >> 2), tg = it & 3;
          uint4 v;
          ldmatrix_x4_t(sb + SM_XN + (oc >> 3) * 16384 + (32 * tg + tok) * 128 + (((oc ^ tok) & 7) << 4), v.x, v.y, v.z, v.w);
          ((uint4*)(g_u + (size_t)(8 * oc + (lane >> 2)) * L_ + mt * 128))[(4 * tg + (lane & 3)) ^ (tg >> 1)] = v;
        }
        __syncwarp();
        if (lane == 0) { fence_async_all(); cnt_add(C_U); }
        const uint4 e0 = __ldg((const uint4*)g_ktab.e + (t - 32));
        named_bar(9, 352);
        if (t < 112) sts128(sb + T_K0 + (t - 32) * 16, k0v);
        named_bar(8, 96);
        kexpand<96>(sb, sb + T_K0, sb + SM_KD, bar + B_K2048, t - 32, e0);
        __syncwarp();
        if (lane == 0) mbar_arrive(bar + B_CV);
        if (w < 3) conv_ship(sb, bar, w - 1, vb * 4 + 2 * (w - 1), C_Y + (vb >> 4), el);
      } else if (w < 3) {
#pragma unroll 1
        for (int grp = 0; grp < 4; grp++) conv_ship(sb, bar, w - 1, 512 + ((int)vb - 128) * 16 + grp * 4 + 2 * (w - 1), C_Y5, el);
      }
    }
  } else {
    const int t = threadIdx.x & 127, lane = t & 31;
    KgState kst;
    kgen_params(smem_raw, threadIdx.x, kin, kst);
    if (!spare) {
      kgen_steps(smem_raw, threadIdx.x, kst);
      kgen_finish(smem_raw, (unsigned short*)(smem_raw + (warp < 2 ? PR_K0 : SM_KD + ((warp >> 1) - 1) * 1280)),
                  (unsigned short*)(smem_raw + SM_BAR + B_K2048) + (warp >> 1), threadIdx.x, kst);
      named_arrive(4, 384);
    } else {
      const int c0 = 512 + ((int)vb - 128) * 16;
#pragma unroll 1
      for (int grp = 0; grp < 4; grp++) {
        if (grp) { kgen_load(p, c0 + grp * 4, threadIdx.x, kin); kgen_params(smem_raw, threadIdx.x, kin, kst); }
        kgen_steps(smem_raw, threadIdx.x, kst);
        kgen_finish(smem_raw, (unsigned short*)(smem_raw + SM_RING + (grp * 4 + (warp >> 1)) * 1280),
                    (unsigned short*)(smem_raw + SM_KD) + grp * 4 + (warp >> 1), threadIdx.x, kst);
        named_bar(3, 256);
      }
      named_arrive(7, 288);
    }
    asm volatile("barrier.cluster.wait.aligned;" ::: "memory");
    asm volatile("setmaxnreg.inc.sync.aligned.u32 240;");
    if (!spare) {
      const bool leader = (t == 0);
      float O1[128], O2[16];
      uint32_t slot = 0, ph = 0, prev = 0;
      const uint32_t hin = sb + SM_HIN + wg * 8192;
      const uint32_t l_hin = hin + t * 16, r_hin = mapa(l_hin, j ^ 1);
      const uint32_t r_hf = mapa(bar + B_HF + 8 * wg, j ^ 1), r_he = mapa(bar + B_HE + 8 * wg, j ^ 1);
      const uint64_t dA0 = mk_desc(sb + SM_XN + wg * 8192, 16, 1024, 1);
      const uint64_t dG0 = mk_desc(sb + SM_RING, 4096, 1024, 1);
      const uint64_t dW0 = mk_desc(sb + SM_RING, 2048, 1024, 1);
      const uint64_t dX0 = mk_desc(sb + SM_RING + 8192, 512, 512, 2);
      auto adv = [&]() { prev = slot; if (++slot == NST) { slot = 0; ph ^= 1; } };
      auto release = [&](uint32_t s) { if (lane == 0) mbar_arrive(bar + B_EMPTY + 8 * s); };
      auto peer_begin = [&](int cp) {
        mbar_wait(bar + B_HF + 8 * wg, cp & 1);
        if (leader && cp < 8) mbar_expect_tx(bar + B_HF + 8 * wg, 8192);
      };
      auto peer_unit = [&](int u) {
        const uint4 a = lds128(l_hin + 2048 * u);
        wg_fence();
        wg_rs256<1>(O1, a.x, a.y, a.z, a.w, dW0 + (uint64_t)(slot * (SLOT >> 4)));
        wg_rs32<1>(O2, a.x, a.y, a.z, a.w, dX0 + (uint64_t)(slot * (SLOT >> 4)));
        wg_commit();
      };
      auto chunk = [&](auto first_c, const int c) {
        constexpr bool FIRST = decltype(first_c)::value;
        float S[64];
        {
          if (FIRST) mbar_wait(bar + B_XN, 0);
          mbar_wait(bar + B_FULL + 8 * slot, ph);
          const uint64_t db = dG0 + (uint64_t)(slot * (SLOT >> 4));
          wg_fence();
          wg_ss128_init<1>(S, dA0, db);
          wg_ss128<1>(S, dA0 + 2, db + 128);
          wg_commit();
          adv();
        }
#pragma unroll 1
        for (int u = 1; u < 18; u++) {
          if (FIRST && !(u & 1) && u < 16) mbar_wait(bar + B_XN + 8 * (u >> 1), 0);
          mbar_wait(bar + B_FULL + 8 * slot, ph);
          const uint64_t da = dA0 + (uint64_t)((u >> 1) * 1024 + (u & 1) * 4);
          const uint64_t db = dG0 + (uint64_t)(slot * (SLOT >> 4));
          wg_fence();
          wg_ss128<1>(S, da, db);
          wg_ss128<1>(S, da + 2, db + 128);
          wg_commit();
          if constexpr (!FIRST) { if (u == 12) peer_begin(c - 1); }
          wg_wait<1>();
          release(prev);
          if (c == 8 && u == 8) named_bar(9, 352);
          adv();
        }
        uint32_t H[16];
        if constexpr (FIRST) { wg_wait<0>(); release(prev); }
        uint32_t rs = prev;
        auto rel_next = [&]() { release(rs); if (++rs == NST) rs = 0; };
        auto P = [&](int u) {
          mbar_wait(bar + B_FULL + 8 * slot, ph);
          peer_unit(u);
          wg_wait<1>(); rel_next();
          adv();
        };
        auto E = [&](int u) {
#pragma unroll
          for (int i = 8 * u; i < 8 * u + 8; i++) asm volatile("" : "+f"(S[i]), "+f"(S[32 + i])::"memory");
#pragma unroll
          for (int g = 2 * u; g < 2 * u + 2; g++) {
            H[2 * g] = geglu2(S[4 * g], S[4 * g + 1], S[32 + 4 * g], S[33 + 4 * g]);
            H[2 * g + 1] = geglu2(S[4 * g + 2], S[4 * g + 3], S[34 + 4 * g], S[35 + 4 * g]);
          }
#pragma unroll
          for (int i = 4 * u; i < 4 * u + 4; i++) asm volatile("" : "+r"(H[i])::"memory");
        };
        auto O = [&](int u) {
          mbar_wait(bar + B_FULL + 8 * slot, ph);
          wg_fence();
          if (FIRST && u == 0) {
            wg_rs256_init<1>(O1, H[0], H[1], H[2], H[3], dW0 + (uint64_t)(slot * (SLOT >> 4)));
            wg_rs32_init<1>(O2, H[0], H[1], H[2], H[3], dX0 + (uint64_t)(slot * (SLOT >> 4)));
            rs = slot;
          } else {
            wg_rs256<1>(O1, H[4 * u], H[4 * u + 1], H[4 * u + 2], H[4 * u + 3], dW0 + (uint64_t)(slot * (SLOT >> 4)));
            wg_rs32<1>(O2, H[4 * u], H[4 * u + 1], H[4 * u + 2], H[4 * u + 3], dX0 + (uint64_t)(slot * (SLOT >> 4)));
          }
          wg_commit();
          if (u == 3) {
            mbar_wait(bar + B_HE + 8 * wg, c & 1);
#pragma unroll
            for (int i = 0; i < 4; i++) st_async_v4(r_hin + 2048 * i, H[4 * i], H[4 * i + 1], H[4 * i + 2], H[4 * i + 3], r_hf);
          }
          if (!FIRST || u >= 1) { wg_wait<1>(); rel_next(); }
          if (u == 0) { if constexpr (!FIRST) { if (lane == 0) mbar_arrive_remote(r_he); } }
          if (u == 3) { wg_wait<0>(); rel_next(); }
          adv();
        };
        if constexpr (FIRST) { E(0); O(0); E(1); O(1); E(2); O(2); E(3); O(3); }
        else { P(0); E(0); P(1); P(2); E(1); P(3); O(0); E(2); O(1); O(2); E(3); O(3); }
      };
      chunk(std::true_type{}, 0);
#pragma unroll 1
      for (int c = 1; c < 9; c++) chunk(std::false_type{}, c);
      peer_begin(8);
#pragma unroll
      for (int u = 0; u < 4; u++) { mbar_wait(bar + B_FULL + 8 * slot, ph); peer_unit(u); adv(); }
      wg_wait<0>();
      reg_fence(O1); reg_fence(O2);
      const int mi = lane >> 3, li = lane & 7;
      {
        const int row = 16 * w + 8 * (mi & 1) + li;
        const uint32_t stg = sb + T_STG + wg * 8192 + row * 128;
#pragma unroll
        for (int g = 0; g < 32; g += 2)
          stmatrix_x4(stg + (g >> 3) * 16384 + ((((g & 7) + (mi >> 1)) ^ li) << 4), pack_bf16(O1[4 * g], O1[4 * g + 1]), pack_bf16(O1[4 * g + 2], O1[4 * g + 3]),
                      pack_bf16(O1[4 * g + 4], O1[4 * g + 5]), pack_bf16(O1[4 * g + 6], O1[4 * g + 7]));
#pragma unroll
        for (int g = 0; g < 4; g += 2)
          stmatrix_x4(stg + 65536 - row * 64 + (((g + (mi >> 1)) ^ (li >> 1)) << 4), pack_bf16(O2[4 * g], O2[4 * g + 1]), pack_bf16(O2[4 * g + 2], O2[4 * g + 3]),
                      pack_bf16(O2[4 * g + 4], O2[4 * g + 5]), pack_bf16(O2[4 * g + 6], O2[4 * g + 7]));
        fence_async_smem();
        named_bar(1 + wg, 128);
        if (leader) mbar_arrive(bar + B_SG);
      }
      mbar_wait(bar + B_CV, 0);
      conv2(sb, wg, w, lane, bar + B_SG);
      const uint32_t rowi = 8 * (mi & 1) + li;
      const uint32_t own_m = sb + T_STG + sp * 16384, own_t = sb + T_STG + 65536 - 16384 + (sp >> 1) * 8192 + (sp & 1) * 2048;
      auto off = [&](int k) -> uint32_t {
        return k < 4 ? (16 * warp + rowi) * 128 + (((2 * k + (mi >> 1)) ^ li) << 4) : 16384 + (16 * warp + rowi) * 64 + (((2 * (k - 4) + (mi >> 1)) ^ (li >> 1)) << 4);
      };
      float f[6][8];
#pragma unroll
      for (int k = 0; k < 6; k++)
#pragma unroll
        for (int i = 0; i < 8; i++) f[k][i] = 0.f;
      named_bar(3, 256);
#pragma unroll 1
      for (int rep = 0; rep < 2; rep++) {
      mbar_wait(bar + (rep ? B_PT : B_X), rep ^ 1);
#pragma unroll 1
      for (int s = 2 * rep; s < 2 + 3 * rep; s++) {
        const uint32_t am = s ? sb + T_PART + (4 - s) * IMG : own_m, at = s ? am : own_t;
        const float sc = s == 1 ? 1.f : 0.5f;
#pragma unroll
        for (int k = 0; k < 6; k++) {
          if (k >= 4 && warp >= 2) break;
          uint32_t r[4];
          ldmatrix_x4((k < 4 ? am : at) + off(k), r);
#pragma unroll
          for (int i = 0; i < 4; i++) { f[k][2 * i] = fmaf(bf_lo(r[i]), sc, f[k][2 * i]); f[k][2 * i + 1] = fmaf(bf_hi(r[i]), sc, f[k][2 * i + 1]); }
        }
      }
      if (rep) mbar_wait(bar + B_YT, 0);
#pragma unroll
      for (int k = 0; k < 6; k++) {
        if (k >= 4 && warp >= 2) break;
        const uint32_t ya = k < 4 ? (warp >> 2) * 8192 + (16 * k + 8 * (mi >> 1) + li) * 128 + (((2 * (warp & 3) + (mi & 1)) ^ li) << 4)
                                  : 16384 + (16 * (k - 4) + 8 * (mi >> 1) + li) * 64 + (((2 * warp + (mi & 1)) ^ (li >> 1)) << 4);
        uint32_t y0, y1, y2, y3;
        ldmatrix_x4_t(sb + T_YT + ya, y0, y1, y2, y3);
        stmatrix_x4((k < 4 ? own_m : own_t) + off(k), pack_bf16(f[k][0] + bf_lo(y0), f[k][1] + bf_hi(y0)), pack_bf16(f[k][2] + bf_lo(y1), f[k][3] + bf_hi(y1)),
                    pack_bf16(f[k][4] + bf_lo(y2), f[k][5] + bf_hi(y2)), pack_bf16(f[k][6] + bf_lo(y3), f[k][7] + bf_hi(y3)));
      }
      fence_async_smem();
      __syncwarp();
      }
      if (lane == 0) {
        tma_store_2d(&p.out, own_m + warp * 2048, 256 * j + 64 * sp, mt * 128 + 16 * warp);
        if (warp < 2) tma_store_2d(&p.out5, own_t + 16384 + warp * 1024, 512 + 32 * j, mt * 128 + 32 * sp + 16 * warp);
        asm volatile("cp.async.bulk.commit_group;" ::: "memory");
        asm volatile("cp.async.bulk.wait_group.read 0;" ::: "memory");
      }
    } else {
#pragma unroll 1
      for (int grp = 0; grp < 4; grp++) {
        if (grp) mbar_wait(bar + B_SG, (grp - 1) & 1);
        kexpand<256>(sb, sb + SM_RING + grp * 5120, sb + SM_RING + grp * 5120 + 1280, sb + SM_KD + 8 * grp, threadIdx.x, __ldg((const uint4*)g_ktab.e + threadIdx.x));
        named_bar(3, 256);
        mbar_wait(bar + B_CV, grp & 1);
        conv2(sb, wg, w, lane, 0);
        named_bar(3, 256);
      }
    }
  }
}

typedef CUresult (*PFN_enc)(CUtensorMap*, CUtensorMapDataType, cuuint32_t, void*, const cuuint64_t*, const cuuint64_t*, const cuuint32_t*,
                            const cuuint32_t*, CUtensorMapInterleave, CUtensorMapSwizzle, CUtensorMapL2promotion, CUtensorMapFloatOOBfill);

void enc(PFN_enc fn, CUtensorMap* m, void* ptr, int rank, const cuuint64_t* dims, const cuuint64_t* strides, const cuuint32_t* box, CUtensorMapSwizzle sw) {
  cuuint32_t es[5] = {1, 1, 1, 1, 1};
  fn(m, CU_TENSOR_MAP_DATA_TYPE_BFLOAT16, rank, ptr, dims, strides, box, es, CU_TENSOR_MAP_INTERLEAVE_NONE, sw,
     CU_TENSOR_MAP_L2_PROMOTION_L2_128B, CU_TENSOR_MAP_FLOAT_OOB_FILL_NONE);
}

}

extern "C" void kernel_launch(void* const* d_in, const int* in_sizes, int n_in, void* d_out, int out_size) {
  static Params pr;
  static void* key[5] = {nullptr, nullptr, nullptr, nullptr, nullptr};
  if (key[0] != d_in[8] || key[1] != d_in[9] || key[2] != d_in[10] || key[3] != d_in[0] || key[4] != d_out) {
    key[0] = d_in[8]; key[1] = d_in[9]; key[2] = d_in[10]; key[3] = d_in[0]; key[4] = d_out;
    void* fnp = nullptr; cudaDriverEntryPointQueryResult st;
    cudaGetDriverEntryPoint("cuTensorMapEncodeTiled", &fnp, cudaEnableDefault, &st);
    PFN_enc fn = (PFN_enc)fnp;
    void *p_xn, *p_y;
    cudaGetSymbolAddress(&p_xn, g_xn); cudaGetSymbolAddress(&p_y, g_y);
    { cuuint64_t d[2] = {D_, L_}, s[1] = {D_ * 2};
      { cuuint32_t b[2] = {64, 128}; enc(fn, &pr.xn, p_xn, 2, d, s, b, CU_TENSOR_MAP_SWIZZLE_128B); }
      { cuuint32_t b[2] = {64, 128}; enc(fn, &pr.x, d_in[0], 2, d, s, b, CU_TENSOR_MAP_SWIZZLE_128B); }
      { cuuint32_t b[2] = {64, 16}; enc(fn, &pr.out, d_out, 2, d, s, b, CU_TENSOR_MAP_SWIZZLE_128B); }
      { cuuint32_t b[2] = {32, 32}; enc(fn, &pr.x5, d_in[0], 2, d, s, b, CU_TENSOR_MAP_SWIZZLE_64B); }
      { cuuint32_t b[2] = {32, 16}; enc(fn, &pr.out5, d_out, 2, d, s, b, CU_TENSOR_MAP_SWIZZLE_64B); } }
    { cuuint64_t d[2] = {F_, D_}, s[1] = {F_ * 2}; cuuint32_t b[2] = {64, 32};
      enc(fn, &pr.gate, d_in[8], 2, d, s, b, CU_TENSOR_MAP_SWIZZLE_128B); enc(fn, &pr.up, d_in[9], 2, d, s, b, CU_TENSOR_MAP_SWIZZLE_128B); }
    { void* wd = d_in[10];
      { cuuint64_t d[3] = {64, F_, 9}, s[2] = {D_ * 2, 128}; cuuint32_t b[3] = {64, 16, 4}; enc(fn, &pr.dn, wd, 3, d, s, b, CU_TENSOR_MAP_SWIZZLE_128B); }
      { cuuint64_t d[2] = {D_, F_}, s[1] = {D_ * 2}; cuuint32_t b[2] = {32, 16}; enc(fn, &pr.dn5, wd, 2, d, s, b, CU_TENSOR_MAP_SWIZZLE_64B); }
    }
    { cuuint64_t d[2] = {L_, D_}, s[1] = {L_ * 2};
      { cuuint32_t b[2] = {64, 64}; enc(fn, &pr.y, p_y, 2, d, s, b, CU_TENSOR_MAP_SWIZZLE_128B); }
      { cuuint32_t b[2] = {32, 32}; enc(fn, &pr.y5, p_y, 2, d, s, b, CU_TENSOR_MAP_SWIZZLE_64B); } }
    cudaFuncSetAttribute(fused_kernel, cudaFuncAttributeMaxDynamicSharedMemorySize, SMEM_BYTES);
  }
  const __nv_bfloat16* const* in = (const __nv_bfloat16* const*)d_in;
  pr.xp = in[0]; pr.logA = in[1]; pr.Aim = in[2]; pr.Cre = in[3]; pr.Cim = in[4]; pr.logdt = in[5]; pr.Dsk = in[6];
  fused_kernel<<<132, 384, SMEM_BYTES>>>(pr);
}
```
